```python
import torch

def _softmax(x, axis=-1):
    return torch.softmax(x, dim=axis)

def _gelu(x):
    return torch.nn.functional.gelu(x, approximate='tanh')

def _silu(x):
    return torch.nn.functional.silu(x)

def _sigmoid(x):
    return torch.sigmoid(x)

def _layernorm(x, axis=-1, eps=1e-05):
    m = x.mean(dim=axis, keepdim=True)
    v = x.var(dim=axis, keepdim=True, unbiased=False)
    return (x - m) / torch.sqrt(v + eps)

def _scatter_add(tgt, idx, src, axis=0):
    return tgt.clone().index_add_(axis, idx, src)

def _segment_sum(src, seg, n):
    out = torch.zeros((n,) + src.shape[1:], dtype=src.dtype)
    return out.index_add_(0, seg, src)

def _pad(x, pw):
    flat = tuple((v for pair in reversed(pw) for v in pair))
    return torch.nn.functional.pad(x, flat)
kernel_name = 'standalone__conformer_family_zipformer__speech'

def setup_inputs():

    _w = lambda a: (lambda t: t.to(torch.bfloat16) if t.is_floating_point() else t)(torch.as_tensor(a))
    B, T, D, K, H = (2, 4000, 256, 5, 4)
    sc = 0.1
    return {'x': _w((lambda *s: torch.randn(*s, dtype=torch.bfloat16) * 0.8)(B, T, D)), 'w_ff1a': _w((lambda *s: torch.randn(*s, dtype=torch.bfloat16) * 0.8)(D, 4 * D) * sc), 'w_ff1b': _w((lambda *s: torch.randn(*s, dtype=torch.bfloat16) * 0.8)(4 * D, D) * sc), 'w_qkv': _w((lambda *s: torch.randn(*s, dtype=torch.bfloat16) * 0.8)(D, 3 * D) * sc), 'w_o': _w((lambda *s: torch.randn(*s, dtype=torch.bfloat16) * 1.6)(D, D) * sc), 'w_pw1': _w((lambda *s: torch.randn(*s, dtype=torch.bfloat16) * 1.6)(D, 2 * D) * sc), 'dw': _w((lambda *s: torch.randn(*s, dtype=torch.bfloat16) * 0.4)(K, D)), 'w_pw2': _w((lambda *s: torch.randn(*s, dtype=torch.bfloat16) * 0.4)(D, D) * sc), 'w_ff2a': _w((lambda *s: torch.randn(*s, dtype=torch.bfloat16) * 0.8)(D, 4 * D) * sc), 'w_ff2b': _w((lambda *s: torch.randn(*s, dtype=torch.bfloat16) * 0.8)(4 * D, D) * sc)}

def reference(x, w_ff1a, w_ff1b, w_qkv, w_o, w_pw1, dw, w_pw2, w_ff2a, w_ff2b):
    B, T, D = x.shape
    K = dw.shape[0]
    H = 4
    Dh = D // H
    h = _layernorm(x, axis=-1)
    h = _silu(h @ w_ff1a) @ w_ff1b
    x = x + 0.5 * h
    h = _layernorm(x, axis=-1)
    qkv = h @ w_qkv
    q = (lambda x, *d: x.permute(*d))(qkv[..., :D].reshape(B, T, H, Dh), 0, 2, 1, 3)
    k = (lambda x, *d: x.permute(*d))(qkv[..., D:2 * D].reshape(B, T, H, Dh), 0, 2, 1, 3)
    v = (lambda x, *d: x.permute(*d))(qkv[..., 2 * D:].reshape(B, T, H, Dh), 0, 2, 1, 3)
    scale = Dh ** (-0.5)
    scores = torch.einsum('bhqd,bhkd->bhqk', q, k) * scale
    p = _softmax(scores, axis=-1)
    att = torch.einsum('bhqk,bhkd->bhqd', p, v)
    att = (lambda x, *d: x.permute(*d))(att, 0, 2, 1, 3).reshape(B, T, D)
    x = x + att @ w_o
    h = _layernorm(x, axis=-1)
    h = h @ w_pw1
    a, b = (h[..., :D].clone(), h[..., D:].clone())
    h = a * _sigmoid(b)
    pad = K // 2
    hp = _pad(h, ((0, 0), (pad, pad), (0, 0)))
    c = torch.zeros_like(h)
    for i in range(K):
        c = c + hp[:, i:i + T, :] * dw[i][None, None, :]
    x = x + _silu(c) @ w_pw2
    h = _layernorm(x, axis=-1)
    h = _silu(h @ w_ff2a) @ w_ff2b
    x = x + 0.5 * h
    return _layernorm(x, axis=-1)
```

```cpp
#include <cuda_runtime.h>
#include <cuda_bf16.h>
#include <cuda.h>
#include <stdint.h>

namespace {

constexpr int T_ = 4000;
constexpr int ROWS = 8000;
constexpr int NTILE = 125;

__device__ __nv_bfloat16 g_x1[ROWS * 256];
__device__ __nv_bfloat16 g_qkv[ROWS * 768];
__device__ __nv_bfloat16 g_att[ROWS * 256];
__device__ uint4 g_halo[NTILE * 4 * 32];
__device__ uint32_t g_flag[NTILE * 2];

__device__ __forceinline__ uint32_t smem_u32(const void* p) { return (uint32_t)__cvta_generic_to_shared(p); }
__device__ __forceinline__ void mbar_init(uint32_t bar, uint32_t cnt) { asm volatile("mbarrier.init.shared::cta.b64 [%0], %1;" :: "r"(bar), "r"(cnt) : "memory"); }
__device__ __forceinline__ void mbar_inval(uint32_t bar) { asm volatile("mbarrier.inval.shared::cta.b64 [%0];" :: "r"(bar) : "memory"); }
__device__ __forceinline__ void mbar_expect_tx(uint32_t bar, uint32_t bytes) { asm volatile("mbarrier.arrive.expect_tx.shared::cta.b64 _, [%0], %1;" :: "r"(bar), "r"(bytes) : "memory"); }
__device__ __forceinline__ void mbar_arrive(uint32_t bar) { asm volatile("mbarrier.arrive.shared::cta.b64 _, [%0];" :: "r"(bar) : "memory"); }
__device__ __forceinline__ void mbar_wait(uint32_t bar, uint32_t parity) {
  asm volatile("{\n.reg .pred p;\n.reg .u32 n;\n"
               "mbarrier.try_wait.parity.shared::cta.b64 p, [%0], %1;\n@p bra DONE_%=;\nmov.u32 n, 0;\n"
               "LOOP_%=:\nmbarrier.try_wait.parity.shared::cta.b64 p, [%0], %1;\n@p bra DONE_%=;\n"
               "add.u32 n, n, 1;\nsetp.lt.u32 p, n, 4194304;\n@p bra LOOP_%=;\ntrap;\nDONE_%=:\n}\n" :: "r"(bar), "r"(parity) : "memory");
}
__device__ __forceinline__ void flag_wait(const uint32_t* fl) {
  asm volatile("{\n.reg .pred p;\n.reg .u32 n, v;\nmov.u32 n, 0;\n"
               "LOOP_%=:\nld.acquire.gpu.global.u32 v, [%0];\nsetp.ne.u32 p, v, 0;\n@p bra DONE_%=;\n"
               "add.u32 n, n, 1;\nsetp.lt.u32 p, n, 16777216;\n@p bra LOOP_%=;\ntrap;\nDONE_%=:\n}\n" :: "l"(fl) : "memory");
}
__device__ __forceinline__ void tma_load_3d(uint32_t dst, const CUtensorMap* tm, uint32_t bar, int c0, int c1, int c2) {
  asm volatile("cp.async.bulk.tensor.3d.shared::cluster.global.mbarrier::complete_tx::bytes [%0], [%1, {%3, %4, %5}], [%2];"
    :: "r"(dst), "l"(tm), "r"(bar), "r"(c0), "r"(c1), "r"(c2) : "memory");
}
__device__ __forceinline__ void tma_store_3d(const CUtensorMap* tm, uint32_t src, int c0, int c1, int c2) {
  asm volatile("cp.async.bulk.tensor.3d.global.shared::cta.bulk_group [%0, {%2, %3, %4}], [%1];" :: "l"(tm), "r"(src), "r"(c0), "r"(c1), "r"(c2) : "memory");
}
__device__ __forceinline__ void bulk_commit() { asm volatile("cp.async.bulk.commit_group;" ::: "memory"); }
__device__ __forceinline__ void bulk_wait_read() { asm volatile("cp.async.bulk.wait_group.read 0;" ::: "memory"); }
__device__ __forceinline__ void bulk_wait_all() { asm volatile("cp.async.bulk.wait_group 0;" ::: "memory"); }
__device__ __forceinline__ void l2_prefetch(const void* p, uint32_t bytes) { asm volatile("cp.async.bulk.prefetch.L2.global [%0], %1;" :: "l"(p), "r"(bytes) : "memory"); }
__device__ __forceinline__ void prefetch_tmap(const CUtensorMap* tm) { asm volatile("prefetch.tensormap [%0];" :: "l"(tm) : "memory"); }
__device__ __forceinline__ void fence_async_smem() { asm volatile("fence.proxy.async.shared::cta;" ::: "memory"); }
__device__ __forceinline__ void wg_fence() { asm volatile("wgmma.fence.sync.aligned;" ::: "memory"); }
__device__ __forceinline__ void wg_commit() { asm volatile("wgmma.commit_group.sync.aligned;" ::: "memory"); }
template<int N> __device__ __forceinline__ void wg_wait() { asm volatile("wgmma.wait_group.sync.aligned %0;" :: "n"(N) : "memory"); }
__device__ __forceinline__ void bar_sync(int id, int n) { asm volatile("bar.sync %0, %1;" :: "r"(id), "r"(n) : "memory"); }
__device__ __forceinline__ void bar_arrive(int id, int n) { asm volatile("bar.arrive %0, %1;" :: "r"(id), "r"(n) : "memory"); }
__device__ __forceinline__ void pdl_wait() { asm volatile("griddepcontrol.wait;" ::: "memory"); }
__device__ __forceinline__ void pdl_launch() { asm volatile("griddepcontrol.launch_dependents;" ::: "memory"); }
__device__ __forceinline__ float ex2(float x) { float y; asm("ex2.approx.ftz.f32 %0, %1;" : "=f"(y) : "f"(x)); return y; }
__device__ __forceinline__ float tanh_fast(float x) { float y; asm("tanh.approx.f32 %0, %1;" : "=f"(y) : "f"(x)); return y; }
__device__ __forceinline__ uint32_t pack_bf16(float lo, float hi) { uint32_t r; asm("cvt.rn.bf16x2.f32 %0, %1, %2;" : "=r"(r) : "f"(hi), "f"(lo)); return r; }
__device__ __forceinline__ float bf_lo(uint32_t u) { return __uint_as_float(u << 16); }
__device__ __forceinline__ float bf_hi(uint32_t u) { return __uint_as_float(u & 0xffff0000u); }
__device__ __forceinline__ void ldsm_x4(uint32_t addr, uint32_t& r0, uint32_t& r1, uint32_t& r2, uint32_t& r3) {
  asm volatile("ldmatrix.sync.aligned.m8n8.x4.shared.b16 {%0,%1,%2,%3}, [%4];" : "=r"(r0), "=r"(r1), "=r"(r2), "=r"(r3) : "r"(addr) : "memory");
}
__device__ __forceinline__ void stsm_x4(uint32_t addr, uint32_t r0, uint32_t r1, uint32_t r2, uint32_t r3) {
  asm volatile("stmatrix.sync.aligned.m8n8.x4.shared.b16 [%0], {%1,%2,%3,%4};" :: "r"(addr), "r"(r0), "r"(r1), "r"(r2), "r"(r3) : "memory");
}
__device__ __forceinline__ void sts128(uint32_t addr, uint4 v) { asm volatile("st.shared.v4.b32 [%0], {%1,%2,%3,%4};" :: "r"(addr), "r"(v.x), "r"(v.y), "r"(v.z), "r"(v.w) : "memory"); }
__device__ __forceinline__ uint4 lds128(uint32_t addr) { uint4 v; asm volatile("ld.shared.v4.b32 {%0,%1,%2,%3}, [%4];" : "=r"(v.x), "=r"(v.y), "=r"(v.z), "=r"(v.w) : "r"(addr) : "memory"); return v; }
__device__ __forceinline__ void sts64f(uint32_t addr, float a, float b) { asm volatile("st.shared.v2.f32 [%0], {%1,%2};" :: "r"(addr), "f"(a), "f"(b) : "memory"); }
__device__ __forceinline__ float2 lds64f(uint32_t addr) { float2 v; asm volatile("ld.shared.v2.f32 {%0,%1}, [%2];" : "=f"(v.x), "=f"(v.y) : "r"(addr) : "memory"); return v; }
__device__ __forceinline__ uint32_t dlo(uint32_t addr, uint32_t lbo) { return ((addr & 0x3FFFF) >> 4) | ((lbo >> 4) << 16); }

template<int SD> __device__ __forceinline__ void wg_ss_n128_tb1(float (&d)[64], uint32_t da, uint32_t db) {
  asm volatile("{\n.reg .b64 da, db;\nmov.b64 da, {%64, 0x40000040};\nmov.b64 db, {%65, 0x40000040};\n"
    "wgmma.mma_async.sync.aligned.m64n128k16.f32.bf16.bf16 {%0, %1, %2, %3, %4, %5, %6, %7, %8, %9, %10, %11, %12, %13, %14, %15, %16, %17, %18, %19, %20, %21, %22, %23, %24, %25, %26, %27, %28, %29, %30, %31, %32, %33, %34, %35, %36, %37, %38, %39, %40, %41, %42, %43, %44, %45, %46, %47, %48, %49, %50, %51, %52, %53, %54, %55, %56, %57, %58, %59, %60, %61, %62, %63}, da, db, %66, 1, 1, 0, 1;\n}\n"
    : "+f"(d[0]), "+f"(d[1]), "+f"(d[2]), "+f"(d[3]), "+f"(d[4]), "+f"(d[5]), "+f"(d[6]), "+f"(d[7]), "+f"(d[8]), "+f"(d[9]), "+f"(d[10]), "+f"(d[11]), "+f"(d[12]), "+f"(d[13]), "+f"(d[14]), "+f"(d[15]), "+f"(d[16]), "+f"(d[17]), "+f"(d[18]), "+f"(d[19]), "+f"(d[20]), "+f"(d[21]), "+f"(d[22]), "+f"(d[23]), "+f"(d[24]), "+f"(d[25]), "+f"(d[26]), "+f"(d[27]), "+f"(d[28]), "+f"(d[29]), "+f"(d[30]), "+f"(d[31]), "+f"(d[32]), "+f"(d[33]), "+f"(d[34]), "+f"(d[35]), "+f"(d[36]), "+f"(d[37]), "+f"(d[38]), "+f"(d[39]), "+f"(d[40]), "+f"(d[41]), "+f"(d[42]), "+f"(d[43]), "+f"(d[44]), "+f"(d[45]), "+f"(d[46]), "+f"(d[47]), "+f"(d[48]), "+f"(d[49]), "+f"(d[50]), "+f"(d[51]), "+f"(d[52]), "+f"(d[53]), "+f"(d[54]), "+f"(d[55]), "+f"(d[56]), "+f"(d[57]), "+f"(d[58]), "+f"(d[59]), "+f"(d[60]), "+f"(d[61]), "+f"(d[62]), "+f"(d[63])
    : "r"(da), "r"(db), "n"(SD));
}
template<int SD> __device__ __forceinline__ void wg_rs_n128_tb1(float (&d)[64], uint32_t a0, uint32_t a1, uint32_t a2, uint32_t a3, uint32_t db) {
  asm volatile("{\n.reg .b64 db;\nmov.b64 db, {%68, 0x40000040};\n"
    "wgmma.mma_async.sync.aligned.m64n128k16.f32.bf16.bf16 {%0, %1, %2, %3, %4, %5, %6, %7, %8, %9, %10, %11, %12, %13, %14, %15, %16, %17, %18, %19, %20, %21, %22, %23, %24, %25, %26, %27, %28, %29, %30, %31, %32, %33, %34, %35, %36, %37, %38, %39, %40, %41, %42, %43, %44, %45, %46, %47, %48, %49, %50, %51, %52, %53, %54, %55, %56, %57, %58, %59, %60, %61, %62, %63}, {%64, %65, %66, %67}, db, %69, 1, 1, 1;\n}\n"
    : "+f"(d[0]), "+f"(d[1]), "+f"(d[2]), "+f"(d[3]), "+f"(d[4]), "+f"(d[5]), "+f"(d[6]), "+f"(d[7]), "+f"(d[8]), "+f"(d[9]), "+f"(d[10]), "+f"(d[11]), "+f"(d[12]), "+f"(d[13]), "+f"(d[14]), "+f"(d[15]), "+f"(d[16]), "+f"(d[17]), "+f"(d[18]), "+f"(d[19]), "+f"(d[20]), "+f"(d[21]), "+f"(d[22]), "+f"(d[23]), "+f"(d[24]), "+f"(d[25]), "+f"(d[26]), "+f"(d[27]), "+f"(d[28]), "+f"(d[29]), "+f"(d[30]), "+f"(d[31]), "+f"(d[32]), "+f"(d[33]), "+f"(d[34]), "+f"(d[35]), "+f"(d[36]), "+f"(d[37]), "+f"(d[38]), "+f"(d[39]), "+f"(d[40]), "+f"(d[41]), "+f"(d[42]), "+f"(d[43]), "+f"(d[44]), "+f"(d[45]), "+f"(d[46]), "+f"(d[47]), "+f"(d[48]), "+f"(d[49]), "+f"(d[50]), "+f"(d[51]), "+f"(d[52]), "+f"(d[53]), "+f"(d[54]), "+f"(d[55]), "+f"(d[56]), "+f"(d[57]), "+f"(d[58]), "+f"(d[59]), "+f"(d[60]), "+f"(d[61]), "+f"(d[62]), "+f"(d[63])
    : "r"(a0), "r"(a1), "r"(a2), "r"(a3), "r"(db), "n"(SD));
}
template<int SD> __device__ __forceinline__ void wg_ss_n64_tb1(float (&d)[32], uint32_t da, uint32_t db) {
  asm volatile("{\n.reg .b64 da, db;\nmov.b64 da, {%32, 0x40000040};\nmov.b64 db, {%33, 0x40000040};\n"
    "wgmma.mma_async.sync.aligned.m64n64k16.f32.bf16.bf16 {%0, %1, %2, %3, %4, %5, %6, %7, %8, %9, %10, %11, %12, %13, %14, %15, %16, %17, %18, %19, %20, %21, %22, %23, %24, %25, %26, %27, %28, %29, %30, %31}, da, db, %34, 1, 1, 0, 1;\n}\n"
    : "+f"(d[0]), "+f"(d[1]), "+f"(d[2]), "+f"(d[3]), "+f"(d[4]), "+f"(d[5]), "+f"(d[6]), "+f"(d[7]), "+f"(d[8]), "+f"(d[9]), "+f"(d[10]), "+f"(d[11]), "+f"(d[12]), "+f"(d[13]), "+f"(d[14]), "+f"(d[15]), "+f"(d[16]), "+f"(d[17]), "+f"(d[18]), "+f"(d[19]), "+f"(d[20]), "+f"(d[21]), "+f"(d[22]), "+f"(d[23]), "+f"(d[24]), "+f"(d[25]), "+f"(d[26]), "+f"(d[27]), "+f"(d[28]), "+f"(d[29]), "+f"(d[30]), "+f"(d[31])
    : "r"(da), "r"(db), "n"(SD));
}
template<int SD> __device__ __forceinline__ void wg_ss_n80_tb0(float (&d)[40], uint32_t da, uint32_t db) {
  asm volatile("{\n.reg .b64 da, db;\nmov.b64 da, {%40, 0x40000040};\nmov.b64 db, {%41, 0x40000040};\n"
    "wgmma.mma_async.sync.aligned.m64n80k16.f32.bf16.bf16 {%0, %1, %2, %3, %4, %5, %6, %7, %8, %9, %10, %11, %12, %13, %14, %15, %16, %17, %18, %19, %20, %21, %22, %23, %24, %25, %26, %27, %28, %29, %30, %31, %32, %33, %34, %35, %36, %37, %38, %39}, da, db, %42, 1, 1, 0, 0;\n}\n"
    : "+f"(d[0]), "+f"(d[1]), "+f"(d[2]), "+f"(d[3]), "+f"(d[4]), "+f"(d[5]), "+f"(d[6]), "+f"(d[7]), "+f"(d[8]), "+f"(d[9]), "+f"(d[10]), "+f"(d[11]), "+f"(d[12]), "+f"(d[13]), "+f"(d[14]), "+f"(d[15]), "+f"(d[16]), "+f"(d[17]), "+f"(d[18]), "+f"(d[19]), "+f"(d[20]), "+f"(d[21]), "+f"(d[22]), "+f"(d[23]), "+f"(d[24]), "+f"(d[25]), "+f"(d[26]), "+f"(d[27]), "+f"(d[28]), "+f"(d[29]), "+f"(d[30]), "+f"(d[31]), "+f"(d[32]), "+f"(d[33]), "+f"(d[34]), "+f"(d[35]), "+f"(d[36]), "+f"(d[37]), "+f"(d[38]), "+f"(d[39])
    : "r"(da), "r"(db), "n"(SD));
}
template<int SD> __device__ __forceinline__ void wg_rs_n64_tb1(float (&d)[32], uint32_t a0, uint32_t a1, uint32_t a2, uint32_t a3, uint32_t db) {
  asm volatile("{\n.reg .b64 db;\nmov.b64 db, {%36, 0x40000040};\n"
    "wgmma.mma_async.sync.aligned.m64n64k16.f32.bf16.bf16 {%0, %1, %2, %3, %4, %5, %6, %7, %8, %9, %10, %11, %12, %13, %14, %15, %16, %17, %18, %19, %20, %21, %22, %23, %24, %25, %26, %27, %28, %29, %30, %31}, {%32, %33, %34, %35}, db, %37, 1, 1, 1;\n}\n"
    : "+f"(d[0]), "+f"(d[1]), "+f"(d[2]), "+f"(d[3]), "+f"(d[4]), "+f"(d[5]), "+f"(d[6]), "+f"(d[7]), "+f"(d[8]), "+f"(d[9]), "+f"(d[10]), "+f"(d[11]), "+f"(d[12]), "+f"(d[13]), "+f"(d[14]), "+f"(d[15]), "+f"(d[16]), "+f"(d[17]), "+f"(d[18]), "+f"(d[19]), "+f"(d[20]), "+f"(d[21]), "+f"(d[22]), "+f"(d[23]), "+f"(d[24]), "+f"(d[25]), "+f"(d[26]), "+f"(d[27]), "+f"(d[28]), "+f"(d[29]), "+f"(d[30]), "+f"(d[31])
    : "r"(a0), "r"(a1), "r"(a2), "r"(a3), "r"(db), "n"(SD));
}


constexpr int RING = 5;
constexpr uint32_t STAGE = 32768;
constexpr uint32_t OFF_X = 32768, OFF_W = 65536, OFF_MISC = OFF_W + RING * STAGE;
constexpr int ROW_SMEM = OFF_MISC + 256 + 1024 + 1024;

struct Ctx {
  uint32_t sA, sX, sW, full, empty, stats;
  uint32_t frag;
  uint32_t rsw;
  uint32_t hi;
  int wg, tid, lane;
};
__device__ __forceinline__ uint32_t stage_wait(const Ctx& c, int n) {
  const int q = n / RING, s = n - q * RING;
  mbar_wait(c.full + 8 * s, q & 1);
  return dlo(c.sW + s * STAGE, 0);
}
__device__ __forceinline__ void stage_release(const Ctx& c, int n) {
  const int s = n % RING;
  if (c.tid == 0) mbar_arrive(c.empty + 8 * s);
}
template<int FIRST> __device__ __forceinline__ void piece_ss(float (&acc)[64], uint32_t dA, uint32_t dB) {
  dB += (16384 >> 4) << 16;
  wg_ss_n128_tb1<FIRST ? 0 : 1>(acc, dA, dB);
#pragma unroll
  for (int kk = 1; kk < 8; kk++) wg_ss_n128_tb1<1>(acc, dA + (kk >> 2) * 512 + (kk & 3) * 2, dB + kk * 128);
}
__device__ __forceinline__ void ff_g1(float (&h)[32], uint32_t dA, uint32_t dB) {
  wg_ss_n64_tb1<0>(h, dA, dB);
#pragma unroll
  for (int kk = 1; kk < 16; kk++) wg_ss_n64_tb1<1>(h, dA + (kk >> 2) * 512 + (kk & 3) * 2, dB + kk * 128);
}
__device__ __forceinline__ void ff_g2(float (&acc)[64], const uint32_t (&P)[16], uint32_t dB, int half) {
  dB += ((8192 >> 4) << 16) + half * 1024;
#pragma unroll
  for (int kk = 0; kk < 4; kk++) wg_rs_n128_tb1<1>(acc, P[4 * kk], P[4 * kk + 1], P[4 * kk + 2], P[4 * kk + 3], dB + kk * 128);
}
template<int FIRST> __device__ __forceinline__ void gemm256(const Ctx& c, float (&acc)[64], int n) {
  const uint32_t dA = dlo(c.sA, 16);
  uint32_t b = stage_wait(c, n);
  wg_fence(); piece_ss<FIRST>(acc, dA, b); wg_commit();
  b = stage_wait(c, n + 1);
  wg_fence(); piece_ss<0>(acc, dA + 1024, b); wg_commit();
  wg_wait<1>(); stage_release(c, n);
  wg_wait<0>(); stage_release(c, n + 1);
}
__device__ __forceinline__ uint32_t frag_addr(const Ctx& c, uint32_t tile, int j) {
  return tile + (2 * c.wg + (j >> 2)) * 8192 + c.frag + ((((j & 3) * 2 + c.hi) ^ c.rsw) << 4);
}
__device__ __forceinline__ void load_half(const Ctx& c, uint32_t tile, float (&v)[64]) {
#pragma unroll
  for (int j = 0; j < 8; j++) {
    uint32_t r0, r1, r2, r3;
    ldsm_x4(frag_addr(c, tile, j), r0, r1, r2, r3);
    v[8 * j] = bf_lo(r0); v[8 * j + 1] = bf_hi(r0); v[8 * j + 2] = bf_lo(r1); v[8 * j + 3] = bf_hi(r1);
    v[8 * j + 4] = bf_lo(r2); v[8 * j + 5] = bf_hi(r2); v[8 * j + 6] = bf_lo(r3); v[8 * j + 7] = bf_hi(r3);
  }
}
__device__ __forceinline__ void store_half(const Ctx& c, uint32_t tile, const float (&v)[64], float a0, float b0, float a1, float b1) {
#pragma unroll
  for (int j = 0; j < 8; j++)
    stsm_x4(frag_addr(c, tile, j),
            pack_bf16(fmaf(v[8 * j], a0, b0), fmaf(v[8 * j + 1], a0, b0)), pack_bf16(fmaf(v[8 * j + 2], a1, b1), fmaf(v[8 * j + 3], a1, b1)),
            pack_bf16(fmaf(v[8 * j + 4], a0, b0), fmaf(v[8 * j + 5], a0, b0)), pack_bf16(fmaf(v[8 * j + 6], a1, b1), fmaf(v[8 * j + 7], a1, b1)));
}
__device__ __forceinline__ void store_half_raw(const Ctx& c, uint32_t tile, const float (&v)[64]) {
#pragma unroll
  for (int j = 0; j < 8; j++)
    stsm_x4(frag_addr(c, tile, j), pack_bf16(v[8 * j], v[8 * j + 1]), pack_bf16(v[8 * j + 2], v[8 * j + 3]),
            pack_bf16(v[8 * j + 4], v[8 * j + 5]), pack_bf16(v[8 * j + 6], v[8 * j + 7]));
}
__device__ __forceinline__ void ln_stats(const Ctx& c, const float (&v)[64], float scale, float& a0, float& b0, float& a1, float& b1) {
  float s0 = 0.f, s1 = 0.f, q0 = 0.f, q1 = 0.f, s2 = 0.f, s3 = 0.f, q2 = 0.f, q3 = 0.f;
#pragma unroll
  for (int i = 0; i < 16; i++) {
    s0 += v[4 * i]; q0 = fmaf(v[4 * i], v[4 * i], q0);
    s2 += v[4 * i + 1]; q2 = fmaf(v[4 * i + 1], v[4 * i + 1], q2);
    s1 += v[4 * i + 2]; q1 = fmaf(v[4 * i + 2], v[4 * i + 2], q1);
    s3 += v[4 * i + 3]; q3 = fmaf(v[4 * i + 3], v[4 * i + 3], q3);
  }
  s0 += s2; q0 += q2; s1 += s3; q1 += q3;
  s0 += __shfl_xor_sync(0xffffffff, s0, 1); q0 += __shfl_xor_sync(0xffffffff, q0, 1);
  s1 += __shfl_xor_sync(0xffffffff, s1, 1); q1 += __shfl_xor_sync(0xffffffff, q1, 1);
  s0 += __shfl_xor_sync(0xffffffff, s0, 2); q0 += __shfl_xor_sync(0xffffffff, q0, 2);
  s1 += __shfl_xor_sync(0xffffffff, s1, 2); q1 += __shfl_xor_sync(0xffffffff, q1, 2);
  const uint32_t row = (c.tid >> 5) * 16 + (c.lane >> 2);
  if ((c.lane & 3) == 0) {
    sts64f(c.stats + c.wg * 512 + row * 8, s0, q0);
    sts64f(c.stats + c.wg * 512 + (row + 8) * 8, s1, q1);
  }
  bar_sync(1, 256);
  const float2 o0 = lds64f(c.stats + (c.wg ^ 1) * 512 + row * 8), o1 = lds64f(c.stats + (c.wg ^ 1) * 512 + (row + 8) * 8);
  const float m0 = (s0 + o0.x) * (1.f / 256.f), m1 = (s1 + o1.x) * (1.f / 256.f);
  const float var0 = fmaxf(fmaf(-m0, m0, (q0 + o0.y) * (1.f / 256.f)), 0.f), var1 = fmaxf(fmaf(-m1, m1, (q1 + o1.y) * (1.f / 256.f)), 0.f);
  a0 = rsqrtf(var0 + 1e-5f) * scale; a1 = rsqrtf(var1 + 1e-5f) * scale;
  b0 = -m0 * a0; b1 = -m1 * a1;
}
__device__ __forceinline__ float silu_half(float h) { return fmaf(h, tanh_fast(h), h); }
__device__ __forceinline__ void silu_pack(const float (&acc)[32], uint32_t (&P)[16]) {
#pragma unroll
  for (int i = 0; i < 16; i++) P[i] = pack_bf16(silu_half(acc[2 * i]), silu_half(acc[2 * i + 1]));
}
__device__ __forceinline__ void ff_block(const Ctx& c, int n0, float (&own)[64]) {
  float oth[64], h[32];
  uint32_t P[16];
#pragma unroll
  for (int i = 0; i < 64; i++) oth[i] = 0.f;
  const uint32_t dA = dlo(c.sA, 16);
  {
    const uint32_t b = stage_wait(c, n0 + c.wg);
    wg_fence(); ff_g1(h, dA, b); wg_commit();
    wg_wait<0>(); stage_release(c, n0 + c.wg);
    silu_pack(h, P);
  }
#pragma unroll 1
  for (int it = 1; it < 8; it++) {
    const int n = n0 + 4 * it - 2 + 2 * c.wg;
    uint32_t b = stage_wait(c, n);
    wg_fence(); ff_g2(own, P, b, c.wg); ff_g2(oth, P, b, c.wg ^ 1); wg_commit();
    b = stage_wait(c, n + 1);
    wg_fence(); ff_g1(h, dA, b); wg_commit();
    wg_wait<1>(); stage_release(c, n);
    wg_wait<0>(); stage_release(c, n + 1);
    silu_pack(h, P);
  }
  if (c.wg == 0) bar_arrive(2, 256);
  {
    const int n = n0 + 30 + c.wg;
    const uint32_t b = stage_wait(c, n);
    wg_fence(); ff_g2(oth, P, b, c.wg ^ 1); wg_commit();
    ff_g2(own, P, b, c.wg); wg_commit();
    wg_wait<1>();
    if (c.wg == 1) bar_sync(2, 256);
    const uint32_t e = (c.wg == 0 ? c.sX : c.sA) + c.tid * 16;
#pragma unroll
    for (int i = 0; i < 16; i++)
      sts128(e + i * 2048, make_uint4(__float_as_uint(oth[4 * i]), __float_as_uint(oth[4 * i + 1]), __float_as_uint(oth[4 * i + 2]), __float_as_uint(oth[4 * i + 3])));
    wg_wait<0>(); stage_release(c, n);
  }
  bar_sync(1, 256);
  const uint32_t e = (c.wg == 0 ? c.sA : c.sX) + c.tid * 16;
#pragma unroll
  for (int i = 0; i < 16; i++) {
    const uint4 u = lds128(e + i * 2048);
    own[4 * i] += __uint_as_float(u.x); own[4 * i + 1] += __uint_as_float(u.y);
    own[4 * i + 2] += __uint_as_float(u.z); own[4 * i + 3] += __uint_as_float(u.w);
  }
}
__device__ __forceinline__ void produce(uint32_t sW, uint32_t full, uint32_t empty, int n, const CUtensorMap* tm, int k0, int nblk, int c0 = 0) {
  const int q = n / RING, s = n - q * RING;
  mbar_wait(empty + 8 * s, (q & 1) ^ 1);
  mbar_expect_tx(full + 8 * s, STAGE);
  tma_load_3d(sW + s * STAGE, tm, full + 8 * s, c0, k0, nblk);
}
__device__ __forceinline__ void produce_ff(uint32_t sW, uint32_t full, uint32_t empty, int n0, const CUtensorMap* tmA, const CUtensorMap* tmB) {
#pragma unroll 1
  for (int m = 0; m < 32; m++) {
    int is2, j;
    if (m < 2) { is2 = 0; j = m; }
    else if (m == 31) { is2 = 1; j = 15; }
    else { const int q = m - 2; is2 = !(q & 1); j = (q >> 1) + (is2 ? 0 : 2); }
    if (is2) produce(sW, full, empty, n0 + m, tmB, 64 * j, 0);
    else produce(sW, full, empty, n0 + m, tmA, 0, j);
  }
}
__device__ __forceinline__ Ctx make_ctx(uint32_t base) {
  Ctx c;
  c.sA = base; c.sX = base + OFF_X; c.sW = base + OFF_W;
  c.full = base + OFF_MISC; c.empty = c.full + 8 * RING; c.stats = base + OFF_MISC + 256;
  c.wg = __shfl_sync(0xffffffff, (int)(threadIdx.x >> 7), 0);
  c.tid = threadIdx.x & 127; c.lane = threadIdx.x & 31;
  const uint32_t r = (c.tid >> 5) * 16 + (c.lane & 7) + ((c.lane >> 3) & 1) * 8;
  c.frag = r * 128; c.rsw = r & 7; c.hi = c.lane >> 4;
  return c;
}
__device__ __forceinline__ void row_init(uint32_t base) {
  if (threadIdx.x == 0) {
    const uint32_t full = base + OFF_MISC;
    for (int i = 0; i < RING; i++) { mbar_init(full + 8 * i, 1); mbar_init(full + 8 * RING + 8 * i, 1); }
    mbar_init(full + 16 * RING, 1);
    mbar_init(full + 16 * RING + 8, 1);
    asm volatile("fence.mbarrier_init.release.cluster;" ::: "memory");
  }
  __syncthreads();
}
struct Wptrs { const void* p[8]; uint32_t bytes[8]; };

__global__ void __launch_bounds__(384, 1) k1_ff1_qkv(const __grid_constant__ CUtensorMap tmX, const __grid_constant__ CUtensorMap tmW1a,
    const __grid_constant__ CUtensorMap tmW1b, const __grid_constant__ CUtensorMap tmWqkv, const __grid_constant__ CUtensorMap tmX1st,
    const __grid_constant__ CUtensorMap tmQKVst, const __grid_constant__ Wptrs wp) {
  extern __shared__ uint8_t smem_raw[];
  const uint32_t base = (smem_u32(smem_raw) + 1023) & ~1023u;
  const int tile = blockIdx.x;
  row_init(base);
  pdl_launch();
  if (threadIdx.x >= 256) {
    asm volatile("setmaxnreg.dec.sync.aligned.u32 24;");
    const uint32_t sW = base + OFF_W, full = base + OFF_MISC, empty = full + 8 * RING, inbar = full + 16 * RING;
    if (threadIdx.x == 256) {
      mbar_expect_tx(inbar, 32768);
      tma_load_3d(base + OFF_X, &tmX, inbar, 0, tile * 64, 0);
      produce_ff(sW, full, empty, 0, &tmW1a, &tmW1b);
#pragma unroll 1
      for (int m = 0; m < 12; m++) produce(sW, full, empty, 32 + m, &tmWqkv, 128 * (m & 1), 2 * (m >> 1));
    } else if (threadIdx.x >= 288 && threadIdx.x < 296) {
      const int w = threadIdx.x - 288;
      const uint32_t bytes = wp.bytes[w], per = ((bytes / NTILE) + 127) & ~127u, off = per * tile;
      if (off < bytes) l2_prefetch((const uint8_t*)wp.p[w] + off, min(per, bytes - off));
    } else if (threadIdx.x == 320) {
      g_flag[tile * 2] = 0; g_flag[tile * 2 + 1] = 0;
    }
  } else {
    asm volatile("setmaxnreg.inc.sync.aligned.u32 240;");
    const Ctx c = make_ctx(base);
    float own[64];
    float a0, b0, a1, b1;
    mbar_wait(c.full + 16 * RING, 0);
    load_half(c, c.sX, own);
    ln_stats(c, own, 0.5f, a0, b0, a1, b1);
    store_half(c, c.sA, own, a0, b0, a1, b1);
    fence_async_smem();
#pragma unroll
    for (int i = 0; i < 64; i++) own[i] *= 2.f;
    bar_sync(1, 256);
    ff_block(c, 0, own);
#pragma unroll
    for (int i = 0; i < 64; i++) own[i] *= 0.5f;
    ln_stats(c, own, 1.f, a0, b0, a1, b1);
    store_half(c, c.sA, own, a0, b0, a1, b1);
    store_half_raw(c, c.sX, own);
    fence_async_smem();
    bar_sync(1, 256);
    if (c.tid == 0) { tma_store_3d(&tmX1st, c.sX + c.wg * 16384, 0, tile * 64, 2 * c.wg); bulk_commit(); }
#pragma unroll 1
    for (int cc = 0; cc < 3; cc++) {
      const int j = 2 * cc + c.wg;
      gemm256<1>(c, own, 32 + 2 * j);
      const float sc = (cc == 0) ? 0.125f * 1.4426950408889634f : 1.f;
      if (c.tid == 0) bulk_wait_read();
      bar_sync(3 + c.wg, 128);
      store_half(c, c.sX, own, sc, 0.f, sc, 0.f);
      fence_async_smem();
      bar_sync(3 + c.wg, 128);
      if (c.tid == 0) { tma_store_3d(&tmQKVst, c.sX + c.wg * 16384, 0, tile * 64, 2 * j); bulk_commit(); }
    }
    if (c.tid == 0) bulk_wait_all();
  }
}

__global__ void __launch_bounds__(384, 1) k3_tail(const __grid_constant__ CUtensorMap tmAtt, const __grid_constant__ CUtensorMap tmX1,
    const __grid_constant__ CUtensorMap tmWo, const __grid_constant__ CUtensorMap tmPw1, const __grid_constant__ CUtensorMap tmPw2,
    const __grid_constant__ CUtensorMap tmW2a, const __grid_constant__ CUtensorMap tmW2b, const __grid_constant__ CUtensorMap tmOut,
    const uint4* __restrict__ dw) {
  extern __shared__ uint8_t smem_raw[];
  const uint32_t base = (smem_u32(smem_raw) + 1023) & ~1023u;
  const int tile = blockIdx.x;
  row_init(base);
  if (threadIdx.x >= 256) {
    asm volatile("setmaxnreg.dec.sync.aligned.u32 24;");
    const uint32_t sW = base + OFF_W, full = base + OFF_MISC, empty = full + 8 * RING, inbar = full + 16 * RING;
    if (threadIdx.x == 256) {
#pragma unroll 1
      for (int m = 0; m < 4; m++) produce(sW, full, empty, m, &tmWo, 128 * (m & 1), 2 * (m >> 1));
#pragma unroll 1
      for (int m = 0; m < 8; m++) produce(sW, full, empty, 4 + m, &tmPw1, 128 * (m & 1), 0, 64 * (2 * ((m >> 1) & 1) + (m >> 2)));
#pragma unroll 1
      for (int m = 0; m < 4; m++) produce(sW, full, empty, 12 + m, &tmPw2, 128 * (m & 1), 2 * (m >> 1));
      produce_ff(sW, full, empty, 16, &tmW2a, &tmW2b);
    } else if (threadIdx.x == 288) {
      pdl_wait();
      mbar_expect_tx(inbar + 8, 32768);
      tma_load_3d(base, &tmAtt, inbar + 8, 0, tile * 64, 0);
      mbar_expect_tx(inbar, 32768);
      tma_load_3d(base + OFF_X, &tmX1, inbar, 0, tile * 64, 0);
    }
  } else {
    asm volatile("setmaxnreg.inc.sync.aligned.u32 240;");
    const Ctx c = make_ctx(base);
    float own[64];
    float a0, b0, a1, b1;
    pdl_wait();
    mbar_wait(c.full + 16 * RING, 0);
    load_half(c, c.sX, own);
    mbar_wait(c.full + 16 * RING + 8, 0);
    gemm256<0>(c, own, 2 * c.wg);
    ln_stats(c, own, 0.5f, a0, b0, a1, b1);
    store_half(c, c.sA, own, a0, b0, a1, b1);
    fence_async_smem();
    bar_sync(1, 256);
    uint4 dwr[5];
#pragma unroll
    for (int i = 0; i < 5; i++) dwr[i] = __ldg(dw + i * 32 + c.lane);
#pragma unroll 1
    for (int q = 0; q < 2; q++) {
      float ab[64];
      gemm256<1>(c, ab, 4 + 4 * q + 2 * c.wg);
#pragma unroll
      for (int j = 0; j < 4; j++) {
        float g[8];
#pragma unroll
        for (int i = 0; i < 8; i++) g[i] = fmaf(ab[8 * j + i], tanh_fast(ab[32 + 8 * j + i]), ab[8 * j + i]);
        stsm_x4(c.sX + (2 * c.wg + q) * 8192 + c.frag + (((j * 2 + c.hi) ^ c.rsw) << 4),
                pack_bf16(g[0], g[1]), pack_bf16(g[2], g[3]), pack_bf16(g[4], g[5]), pack_bf16(g[6], g[7]));
      }
    }
    bar_sync(1, 256);
    {
      const int wi = threadIdx.x >> 5;
      const uint32_t col = (c.lane >> 3) * 8192, ch = c.lane & 7;
      uint4 r[12];
#pragma unroll
      for (int i = 0; i < 12; i++) {
        const int row = (wi * 8 - 2 + i) & 63;
        r[i] = lds128(c.sX + col + row * 128 + ((ch ^ (row & 7)) << 4));
      }
      const int R0 = tile * 64 + wi * 8;
      const bool prev_ok = (R0 % T_) != 0, next_ok = ((R0 + 8) % T_) != 0;
      if (wi == 0 || wi == 7) {
        const int side = wi == 0 ? 0 : 1;
        uint4* hp = g_halo + (tile * 4 + side * 2) * 32 + c.lane;
        hp[0] = side ? r[8] : r[2]; hp[32] = side ? r[9] : r[3];
        __threadfence();
        __syncwarp();
        if (c.lane == 0) asm volatile("st.release.gpu.global.u32 [%0], %1;" :: "l"(g_flag + tile * 2 + side), "r"(1u) : "memory");
        if (side ? next_ok : prev_ok) {
          const int nb = side ? tile + 1 : tile - 1;
          const uint32_t* fl = g_flag + nb * 2 + (side ^ 1);
          flag_wait(fl);
          const uint4* sp = g_halo + (nb * 4 + (side ^ 1) * 2) * 32 + c.lane;
          uint4 h0, h1;
          asm volatile("ld.relaxed.gpu.global.v4.u32 {%0,%1,%2,%3}, [%4];" : "=r"(h0.x), "=r"(h0.y), "=r"(h0.z), "=r"(h0.w) : "l"(sp) : "memory");
          asm volatile("ld.relaxed.gpu.global.v4.u32 {%0,%1,%2,%3}, [%4];" : "=r"(h1.x), "=r"(h1.y), "=r"(h1.z), "=r"(h1.w) : "l"(sp + 32) : "memory");
          if (side) { r[10] = h0; r[11] = h1; } else { r[0] = h0; r[1] = h1; }
        }
      }
      if (!prev_ok) { r[0] = make_uint4(0, 0, 0, 0); r[1] = r[0]; }
      if (!next_ok) { r[10] = make_uint4(0, 0, 0, 0); r[11] = r[10]; }
      uint32_t o[8][4];
#pragma unroll
      for (int q = 0; q < 4; q++) {
        float wl[5], wh[5], xl[12], xh[12];
#pragma unroll
        for (int k = 0; k < 5; k++) {
          const uint32_t u = q == 0 ? dwr[k].x : q == 1 ? dwr[k].y : q == 2 ? dwr[k].z : dwr[k].w;
          wl[k] = bf_lo(u) * 0.5f; wh[k] = bf_hi(u) * 0.5f;
        }
#pragma unroll
        for (int i = 0; i < 12; i++) {
          const uint32_t u = q == 0 ? r[i].x : q == 1 ? r[i].y : q == 2 ? r[i].z : r[i].w;
          xl[i] = bf_lo(u); xh[i] = bf_hi(u);
        }
#pragma unroll
        for (int i = 0; i < 8; i++) {
          float cl = xl[i] * wl[0], chh = xh[i] * wh[0];
#pragma unroll
          for (int k = 1; k < 5; k++) { cl = fmaf(xl[i + k], wl[k], cl); chh = fmaf(xh[i + k], wh[k], chh); }
          o[i][q] = pack_bf16(silu_half(cl), silu_half(chh));
        }
      }
#pragma unroll
      for (int i = 0; i < 8; i++)
        sts128(c.sA + col + (wi * 8 + i) * 128 + ((ch ^ i) << 4), make_uint4(o[i][0], o[i][1], o[i][2], o[i][3]));
    }
    fence_async_smem();
    bar_sync(1, 256);
    gemm256<0>(c, own, 12 + 2 * c.wg);
    ln_stats(c, own, 0.5f, a0, b0, a1, b1);
    store_half(c, c.sA, own, a0, b0, a1, b1);
    fence_async_smem();
#pragma unroll
    for (int i = 0; i < 64; i++) own[i] *= 2.f;
    bar_sync(1, 256);
    ff_block(c, 16, own);
#pragma unroll
    for (int i = 0; i < 64; i++) own[i] *= 0.5f;
    ln_stats(c, own, 1.f, a0, b0, a1, b1);
    store_half(c, c.sX, own, a0, b0, a1, b1);
    fence_async_smem();
    bar_sync(3 + c.wg, 128);
    if (c.tid == 0) { tma_store_3d(&tmOut, c.sX + c.wg * 16384, 0, tile * 64, 2 * c.wg); bulk_commit(); bulk_wait_all(); }
  }
}

constexpr int NSTG = 4;
constexpr int KVB = 160 * 128;
constexpr int NKV = T_ / 160;
constexpr int ATT_SMEM = 32768 + NSTG * 2 * KVB + 256 + 1024;

struct AttCtx { uint32_t sKV, full, empty; const CUtensorMap* tmKV; int h, b, wg; };
__device__ __forceinline__ void att_load_stage(const AttCtx& a, int i) {
  const int s = i & (NSTG - 1);
  mbar_expect_tx(a.full + 8 * s, 2 * KVB);
  tma_load_3d(a.sKV + s * 2 * KVB, a.tmKV, a.full + 8 * s, 256 + a.h * 64, i * 160, a.b);
  tma_load_3d(a.sKV + s * 2 * KVB + KVB, a.tmKV, a.full + 8 * s, 512 + a.h * 64, i * 160, a.b);
}
__device__ __forceinline__ void att_qk(float (&S)[40], uint32_t dQ, uint32_t kd) {
  wg_ss_n80_tb0<0>(S, dQ, kd);
#pragma unroll
  for (int kk = 1; kk < 4; kk++) wg_ss_n80_tb0<1>(S, dQ + kk * 2, kd + kk * 2);
}
__device__ __forceinline__ void att_pv(float (&O)[32], const uint32_t (&P)[20], uint32_t vd) {
#pragma unroll
  for (int kk = 0; kk < 5; kk++) wg_rs_n64_tb1<1>(O, P[kk * 4], P[kk * 4 + 1], P[kk * 4 + 2], P[kk * 4 + 3], vd + kk * 128);
}
template<bool SAFE>
__device__ __forceinline__ void att_softmax(const float (&S)[40], uint32_t (&P)[20], float (&O)[32], float& m0, float& m1, float& l0, float& l1) {
  if (SAFE) {
    float x0 = fmaxf(S[0], S[1]), x1 = fmaxf(S[2], S[3]);
#pragma unroll
    for (int i = 1; i < 10; i++) { x0 = fmaxf(x0, fmaxf(S[4 * i], S[4 * i + 1])); x1 = fmaxf(x1, fmaxf(S[4 * i + 2], S[4 * i + 3])); }
    x0 = fmaxf(x0, __shfl_xor_sync(0xffffffff, x0, 1)); x1 = fmaxf(x1, __shfl_xor_sync(0xffffffff, x1, 1));
    x0 = fmaxf(x0, __shfl_xor_sync(0xffffffff, x0, 2)); x1 = fmaxf(x1, __shfl_xor_sync(0xffffffff, x1, 2));
    const float n0 = fmaxf(m0, x0), n1 = fmaxf(m1, x1);
    const float f0 = ex2(m0 - n0), f1 = ex2(m1 - n1);
    m0 = n0; m1 = n1; l0 *= f0; l1 *= f1;
#pragma unroll
    for (int i = 0; i < 8; i++) { O[4 * i] *= f0; O[4 * i + 1] *= f0; O[4 * i + 2] *= f1; O[4 * i + 3] *= f1; }
  }
#pragma unroll
  for (int i = 0; i < 10; i++) {
    float p0, p1, p2, p3;
    if (SAFE) { p0 = ex2(S[4 * i] - m0); p1 = ex2(S[4 * i + 1] - m0); p2 = ex2(S[4 * i + 2] - m1); p3 = ex2(S[4 * i + 3] - m1); }
    else { p0 = ex2(S[4 * i]); p1 = ex2(S[4 * i + 1]); p2 = ex2(S[4 * i + 2]); p3 = ex2(S[4 * i + 3]); }
    l0 += p0 + p1; l1 += p2 + p3;
    P[2 * i] = pack_bf16(p0, p1); P[2 * i + 1] = pack_bf16(p2, p3);
  }
}
template<bool SAFE>
__device__ __forceinline__ void att_pass(const AttCtx& a, uint32_t dQ, float (&O)[32], float& l0, float& l1) {
  float S[40];
  uint32_t P[20];
  float m0 = -INFINITY, m1 = -INFINITY;
  l0 = 0.f; l1 = 0.f;
#pragma unroll
  for (int i = 0; i < 32; i++) O[i] = 0.f;
  const uint32_t dKV = dlo(a.sKV, 16);
  constexpr uint32_t STG = 2 * KVB / 16, VOFF = KVB / 16, HALF = 80 * 128 / 16;
  constexpr int UNR = SAFE ? 1 : 4;
  mbar_wait(a.full, 0);
  wg_fence(); att_qk(S, dQ, dKV); wg_commit(); wg_wait<0>();
  att_softmax<SAFE>(S, P, O, m0, m1, l0, l1);
  wg_fence(); att_pv(O, P, dKV + VOFF); att_qk(S, dQ, dKV + HALF); wg_commit(); wg_wait<0>();
#pragma unroll 1
  for (int it0 = 0; it0 < NKV - 1; it0 += UNR) {
#pragma unroll
    for (int u = 0; u < UNR; u++) {
      const int it = it0 + u;
      const int s = SAFE ? (it & 3) : u, sn = (s + 1) & 3, sp = (s + 3) & 3;
      const uint32_t kb = dKV + s * STG, kn = dKV + sn * STG;
      att_softmax<SAFE>(S, P, O, m0, m1, l0, l1);
      mbar_wait(a.full + 8 * sn, ((it + 1) >> 2) & 1);
      wg_fence(); att_pv(O, P, kb + VOFF + HALF); att_qk(S, dQ, kn); wg_commit(); wg_wait<0>();
      if ((threadIdx.x & 127) == 0) {
        mbar_arrive(a.empty + 8 * s);
        if (a.wg == s && it >= 1 && it - 1 + NSTG < NKV) {
          mbar_wait(a.empty + 8 * sp, ((it - 1) >> 2) & 1);
          att_load_stage(a, it - 1 + NSTG);
        }
      }
      __syncwarp();
      att_softmax<SAFE>(S, P, O, m0, m1, l0, l1);
      wg_fence(); att_pv(O, P, kn + VOFF); att_qk(S, dQ, kn + HALF); wg_commit(); wg_wait<0>();
    }
  }
  att_softmax<SAFE>(S, P, O, m0, m1, l0, l1);
  wg_fence(); att_pv(O, P, dKV + ((NKV - 1) & 3) * STG + VOFF + HALF); wg_commit(); wg_wait<0>();
  l0 += __shfl_xor_sync(0xffffffff, l0, 1); l1 += __shfl_xor_sync(0xffffffff, l1, 1);
  l0 += __shfl_xor_sync(0xffffffff, l0, 2); l1 += __shfl_xor_sync(0xffffffff, l1, 2);
}

__global__ void __launch_bounds__(512, 1) k2_attn(const __grid_constant__ CUtensorMap tmQ, const __grid_constant__ CUtensorMap tmKV,
                                                  const __grid_constant__ CUtensorMap tmO) {
  extern __shared__ uint8_t smem_raw[];
  const uint32_t base = (smem_u32(smem_raw) + 1023) & ~1023u;
  const uint32_t sQ = base;
  AttCtx a;
  a.sKV = base + 32768; a.full = a.sKV + NSTG * 2 * KVB; a.empty = a.full + 8 * NSTG; a.tmKV = &tmKV;
  const uint32_t qbar = a.full + 16 * NSTG;
  const int qt = blockIdx.x & 15;
  a.h = (blockIdx.x >> 4) & 3; a.b = blockIdx.x >> 6;
  a.wg = __shfl_sync(0xffffffff, (int)(threadIdx.x >> 7), 0);
  const int lane = threadIdx.x & 31, wq = (threadIdx.x >> 5) & 3;
  if (threadIdx.x == 0) {
    prefetch_tmap(&tmQ); prefetch_tmap(&tmKV); prefetch_tmap(&tmO);
    for (int i = 0; i < NSTG; i++) { mbar_init(a.full + 8 * i, 1); mbar_init(a.empty + 8 * i, 4); }
    mbar_init(qbar, 1);
    asm volatile("fence.mbarrier_init.release.cluster;" ::: "memory");
    pdl_launch();
    pdl_wait();
    mbar_expect_tx(qbar, 32768);
    tma_load_3d(sQ, &tmQ, qbar, a.h * 64, qt * 256, a.b);
    for (int i = 0; i < NSTG; i++) att_load_stage(a, i);
  }
  __syncthreads();
  const uint32_t sQw = sQ + a.wg * 8192, dQ = dlo(sQw, 16);
  float O[32], l0, l1;
  mbar_wait(qbar, 0);
  att_pass<false>(a, dQ, O, l0, l1);
  {
    float z = 0.f;
#pragma unroll
    for (int i = 0; i < 32; i++) z = fmaf(O[i], 0.f, z);
    const bool ok = (l0 >= 0x1p-80f) && (l0 <= 0x1p100f) && (l1 >= 0x1p-80f) && (l1 <= 0x1p100f) && (z == 0.f);
    if (__syncthreads_or(!ok)) {
      if (threadIdx.x == 0) {
        for (int i = 0; i < NSTG; i++) { mbar_inval(a.full + 8 * i); mbar_inval(a.empty + 8 * i); }
        for (int i = 0; i < NSTG; i++) { mbar_init(a.full + 8 * i, 1); mbar_init(a.empty + 8 * i, 4); }
        asm volatile("fence.mbarrier_init.release.cluster;" ::: "memory");
        fence_async_smem();
        for (int i = 0; i < NSTG; i++) att_load_stage(a, i);
      }
      __syncthreads();
      att_pass<true>(a, dQ, O, l0, l1);
    }
  }
  const float i0 = 1.f / l0, i1 = 1.f / l1;
  const int r = wq * 16 + (lane & 7) + ((lane >> 3) & 1) * 8;
#pragma unroll
  for (int j = 0; j < 4; j++) {
    const int ch = j * 2 + (lane >> 4);
    stsm_x4(sQw + r * 128 + ((ch ^ (r & 7)) << 4),
            pack_bf16(O[8 * j] * i0, O[8 * j + 1] * i0), pack_bf16(O[8 * j + 2] * i1, O[8 * j + 3] * i1),
            pack_bf16(O[8 * j + 4] * i0, O[8 * j + 5] * i0), pack_bf16(O[8 * j + 6] * i1, O[8 * j + 7] * i1));
  }
  fence_async_smem();
  bar_sync(1 + a.wg, 128);
  if ((threadIdx.x & 127) == 0) {
    tma_store_3d(&tmO, sQw, a.h * 64, qt * 256 + a.wg * 64, a.b);
    bulk_commit();
    bulk_wait_all();
  }
}

typedef CUresult (*EncodeFn)(CUtensorMap*, CUtensorMapDataType, cuuint32_t, void*, const cuuint64_t*, const cuuint64_t*, const cuuint32_t*,
                             const cuuint32_t*, CUtensorMapInterleave, CUtensorMapSwizzle, CUtensorMapL2promotion, CUtensorMapFloatOOBfill);

CUtensorMap make_map(EncodeFn enc, const void* p, uint64_t d0, uint64_t d1, uint64_t d2, uint64_t s1, uint64_t s2, uint32_t b1, uint32_t b2) {
  CUtensorMap tm;
  cuuint64_t dims[3] = {d0, d1, d2};
  cuuint64_t strides[2] = {s1, s2};
  cuuint32_t box[3] = {64, b1, b2};
  cuuint32_t es[3] = {1, 1, 1};
  enc(&tm, CU_TENSOR_MAP_DATA_TYPE_BFLOAT16, 3, const_cast<void*>(p), dims, strides, box, es, CU_TENSOR_MAP_INTERLEAVE_NONE,
      CU_TENSOR_MAP_SWIZZLE_128B, CU_TENSOR_MAP_L2_PROMOTION_L2_256B, CU_TENSOR_MAP_FLOAT_OOB_FILL_NONE);
  return tm;
}
CUtensorMap blk_map(EncodeFn enc, const void* p, uint64_t rows, uint64_t cols, uint32_t boxrows, uint32_t boxblks) {
  return make_map(enc, p, 64, rows, cols / 64, cols * 2, 128, boxrows, boxblks);
}
CUtensorMap seq_map(EncodeFn enc, const void* p, uint64_t cols, uint32_t boxrows) {
  return make_map(enc, p, cols, T_, 2, cols * 2, cols * 2 * T_, boxrows, 1);
}

}

extern "C" void kernel_launch(void* const* d_in, const int* in_sizes, int n_in, void* d_out, int out_size) {
  (void)in_sizes; (void)n_in; (void)out_size;
  const void *x = d_in[0], *w1a = d_in[1], *w1b = d_in[2], *wqkv = d_in[3], *wo = d_in[4], *pw1 = d_in[5], *dw = d_in[6], *pw2 = d_in[7],
             *w2a = d_in[8], *w2b = d_in[9];
  void* fn = nullptr;
  cudaDriverEntryPointQueryResult qr;
  cudaGetDriverEntryPoint("cuTensorMapEncodeTiled", &fn, cudaEnableDefault, &qr);
  EncodeFn enc = (EncodeFn)fn;
  void *x1, *qkv, *att;
  cudaGetSymbolAddress(&x1, g_x1);
  cudaGetSymbolAddress(&qkv, g_qkv);
  cudaGetSymbolAddress(&att, g_att);
  cudaFuncSetAttribute(k1_ff1_qkv, cudaFuncAttributeMaxDynamicSharedMemorySize, ROW_SMEM);
  cudaFuncSetAttribute(k2_attn, cudaFuncAttributeMaxDynamicSharedMemorySize, ATT_SMEM);
  cudaFuncSetAttribute(k3_tail, cudaFuncAttributeMaxDynamicSharedMemorySize, ROW_SMEM);

  Wptrs wp;
  const void* ws[8] = {w1a, w1b, wqkv, wo, pw1, pw2, w2a, w2b};
  const uint32_t wb[8] = {524288, 524288, 393216, 131072, 262144, 131072, 524288, 524288};
  for (int i = 0; i < 8; i++) { wp.p[i] = ws[i]; wp.bytes[i] = wb[i]; }

  cudaLaunchAttribute pdl[1];
  pdl[0].id = cudaLaunchAttributeProgrammaticStreamSerialization;
  pdl[0].val.programmaticStreamSerializationAllowed = 1;
  cudaLaunchConfig_t cfg = {};
  cfg.stream = cudaStreamPerThread;

  cfg.gridDim = dim3(NTILE); cfg.blockDim = dim3(384); cfg.dynamicSmemBytes = ROW_SMEM; cfg.attrs = nullptr; cfg.numAttrs = 0;
  cudaLaunchKernelEx(&cfg, k1_ff1_qkv, blk_map(enc, x, ROWS, 256, 64, 4), blk_map(enc, w1a, 256, 1024, 256, 1), blk_map(enc, w1b, 1024, 256, 64, 4),
                     blk_map(enc, wqkv, 256, 768, 128, 2), blk_map(enc, x1, ROWS, 256, 64, 2), blk_map(enc, qkv, ROWS, 768, 64, 2), wp);

  cfg.gridDim = dim3(128); cfg.blockDim = dim3(512); cfg.dynamicSmemBytes = ATT_SMEM; cfg.attrs = pdl; cfg.numAttrs = 1;
  cudaLaunchKernelEx(&cfg, k2_attn, seq_map(enc, qkv, 768, 256), seq_map(enc, qkv, 768, 160), seq_map(enc, att, 256, 64));

  cfg.gridDim = dim3(NTILE); cfg.blockDim = dim3(384); cfg.dynamicSmemBytes = ROW_SMEM;
  cudaLaunchKernelEx(&cfg, k3_tail, blk_map(enc, att, ROWS, 256, 64, 4), blk_map(enc, x1, ROWS, 256, 64, 4), blk_map(enc, wo, 256, 256, 128, 2),
                     make_map(enc, pw1, 256, 256, 2, 1024, 512, 128, 2), blk_map(enc, pw2, 256, 256, 128, 2), blk_map(enc, w2a, 256, 1024, 256, 1),
                     blk_map(enc, w2b, 1024, 256, 64, 4), blk_map(enc, d_out, ROWS, 256, 64, 2), (const uint4*)dw);
}
```

```cpp
#include <cuda_runtime.h>
#include <cuda_bf16.h>
#include <cuda.h>
#include <stdint.h>

namespace {

constexpr int T_ = 4000;
constexpr int ROWS = 8000;
constexpr int NTILE = 125;

__device__ __nv_bfloat16 g_x1[ROWS * 256];
__device__ __nv_bfloat16 g_qkv[ROWS * 768];
__device__ __nv_bfloat16 g_att[ROWS * 256];
__device__ uint4 g_halo[NTILE * 4 * 32];

#define PROF_MARK(k, i) do {} while (0)
#define PROF_STG(n, i) do {} while (0)

__device__ __forceinline__ uint32_t smem_u32(const void* p) { return (uint32_t)__cvta_generic_to_shared(p); }
__device__ __forceinline__ void mbar_init(uint32_t bar, uint32_t cnt) { asm volatile("mbarrier.init.shared::cta.b64 [%0], %1;" :: "r"(bar), "r"(cnt) : "memory"); }
__device__ __forceinline__ void mbar_inval(uint32_t bar) { asm volatile("mbarrier.inval.shared::cta.b64 [%0];" :: "r"(bar) : "memory"); }
__device__ __forceinline__ void mbar_expect_tx(uint32_t bar, uint32_t bytes) { asm volatile("mbarrier.arrive.expect_tx.shared::cta.b64 _, [%0], %1;" :: "r"(bar), "r"(bytes) : "memory"); }
__device__ __forceinline__ void mbar_arrive(uint32_t bar) { asm volatile("mbarrier.arrive.shared::cta.b64 _, [%0];" :: "r"(bar) : "memory"); }
__device__ __forceinline__ void mbar_wait(uint32_t bar, uint32_t parity) {
  asm volatile("{\n.reg .pred p;\n.reg .u32 n;\n"
               "mbarrier.try_wait.parity.shared::cta.b64 p, [%0], %1;\n@p bra DONE_%=;\nmov.u32 n, 0;\n"
               "LOOP_%=:\nmbarrier.try_wait.parity.shared::cta.b64 p, [%0], %1;\n@p bra DONE_%=;\n"
               "add.u32 n, n, 1;\nsetp.lt.u32 p, n, 4194304;\n@p bra LOOP_%=;\ntrap;\nDONE_%=:\n}\n" :: "r"(bar), "r"(parity) : "memory");
}
__device__ __forceinline__ void halo_poll(const uint4* p, uint4& v) {
  asm volatile("{\n.reg .pred p;\n.reg .u32 n, t;\nmov.u32 n, 0;\n"
               "LOOP_%=:\nld.relaxed.gpu.global.v4.u32 {%0,%1,%2,%3}, [%4];\n"
               "max.u32 t, %0, %1;\nmax.u32 t, t, %2;\nmax.u32 t, t, %3;\nsetp.ne.u32 p, t, 0xFFFFFFFF;\n@p bra DONE_%=;\n"
               "add.u32 n, n, 1;\nsetp.lt.u32 p, n, 16777216;\n@p bra LOOP_%=;\ntrap;\nDONE_%=:\n}\n"
               : "=&r"(v.x), "=&r"(v.y), "=&r"(v.z), "=&r"(v.w) : "l"(p) : "memory");
}
__device__ __forceinline__ void tma_load_3d(uint32_t dst, const CUtensorMap* tm, uint32_t bar, int c0, int c1, int c2) {
  asm volatile("cp.async.bulk.tensor.3d.shared::cluster.global.mbarrier::complete_tx::bytes [%0], [%1, {%3, %4, %5}], [%2];"
    :: "r"(dst), "l"(tm), "r"(bar), "r"(c0), "r"(c1), "r"(c2) : "memory");
}
__device__ __forceinline__ void tma_store_3d(const CUtensorMap* tm, uint32_t src, int c0, int c1, int c2) {
  asm volatile("cp.async.bulk.tensor.3d.global.shared::cta.bulk_group [%0, {%2, %3, %4}], [%1];" :: "l"(tm), "r"(src), "r"(c0), "r"(c1), "r"(c2) : "memory");
}
__device__ __forceinline__ void bulk_commit() { asm volatile("cp.async.bulk.commit_group;" ::: "memory"); }
__device__ __forceinline__ void bulk_wait_read() { asm volatile("cp.async.bulk.wait_group.read 0;" ::: "memory"); }
__device__ __forceinline__ void bulk_wait_all() { asm volatile("cp.async.bulk.wait_group 0;" ::: "memory"); }
__device__ __forceinline__ void l2_prefetch(const void* p, uint32_t bytes) { asm volatile("cp.async.bulk.prefetch.L2.global [%0], %1;" :: "l"(p), "r"(bytes) : "memory"); }
__device__ __forceinline__ void prefetch_tmap(const CUtensorMap* tm) { asm volatile("prefetch.tensormap [%0];" :: "l"(tm) : "memory"); }
__device__ __forceinline__ void fence_async_smem() { asm volatile("fence.proxy.async.shared::cta;" ::: "memory"); }
__device__ __forceinline__ void wg_fence() { asm volatile("wgmma.fence.sync.aligned;" ::: "memory"); }
__device__ __forceinline__ void wg_commit() { asm volatile("wgmma.commit_group.sync.aligned;" ::: "memory"); }
template<int N> __device__ __forceinline__ void wg_wait() { asm volatile("wgmma.wait_group.sync.aligned %0;" :: "n"(N) : "memory"); }
__device__ __forceinline__ void bar_sync(int id, int n) { asm volatile("bar.sync %0, %1;" :: "r"(id), "r"(n) : "memory"); }
__device__ __forceinline__ void bar_arrive(int id, int n) { asm volatile("bar.arrive %0, %1;" :: "r"(id), "r"(n) : "memory"); }
__device__ __forceinline__ void pdl_wait() { asm volatile("griddepcontrol.wait;" ::: "memory"); }
__device__ __forceinline__ void pdl_launch() { asm volatile("griddepcontrol.launch_dependents;" ::: "memory"); }
__device__ __forceinline__ float ex2(float x) { float y; asm("ex2.approx.ftz.f32 %0, %1;" : "=f"(y) : "f"(x)); return y; }
__device__ __forceinline__ float tanh_fast(float x) { float y; asm("tanh.approx.f32 %0, %1;" : "=f"(y) : "f"(x)); return y; }
__device__ __forceinline__ uint32_t pack_bf16(float lo, float hi) { uint32_t r; asm("cvt.rn.bf16x2.f32 %0, %1, %2;" : "=r"(r) : "f"(hi), "f"(lo)); return r; }
__device__ __forceinline__ uint32_t bmul2(uint32_t a, uint32_t b) { uint32_t d; asm("mul.rn.bf16x2 %0, %1, %2;" : "=r"(d) : "r"(a), "r"(b)); return d; }
__device__ __forceinline__ uint32_t bfma2(uint32_t a, uint32_t b, uint32_t c) { uint32_t d; asm("fma.rn.bf16x2 %0, %1, %2, %3;" : "=r"(d) : "r"(a), "r"(b), "r"(c)); return d; }
__device__ __forceinline__ float bf_lo(uint32_t u) { return __uint_as_float(u << 16); }
__device__ __forceinline__ float bf_hi(uint32_t u) { return __uint_as_float(u & 0xffff0000u); }
__device__ __forceinline__ void ldsm_x4(uint32_t addr, uint32_t& r0, uint32_t& r1, uint32_t& r2, uint32_t& r3) {
  asm volatile("ldmatrix.sync.aligned.m8n8.x4.shared.b16 {%0,%1,%2,%3}, [%4];" : "=r"(r0), "=r"(r1), "=r"(r2), "=r"(r3) : "r"(addr) : "memory");
}
__device__ __forceinline__ void stsm_x4(uint32_t addr, uint32_t r0, uint32_t r1, uint32_t r2, uint32_t r3) {
  asm volatile("stmatrix.sync.aligned.m8n8.x4.shared.b16 [%0], {%1,%2,%3,%4};" :: "r"(addr), "r"(r0), "r"(r1), "r"(r2), "r"(r3) : "memory");
}
__device__ __forceinline__ void sts128(uint32_t addr, uint4 v) { asm volatile("st.shared.v4.b32 [%0], {%1,%2,%3,%4};" :: "r"(addr), "r"(v.x), "r"(v.y), "r"(v.z), "r"(v.w) : "memory"); }
__device__ __forceinline__ uint4 lds128(uint32_t addr) { uint4 v; asm volatile("ld.shared.v4.b32 {%0,%1,%2,%3}, [%4];" : "=r"(v.x), "=r"(v.y), "=r"(v.z), "=r"(v.w) : "r"(addr) : "memory"); return v; }
__device__ __forceinline__ void sts64f(uint32_t addr, float a, float b) { asm volatile("st.shared.v2.f32 [%0], {%1,%2};" :: "r"(addr), "f"(a), "f"(b) : "memory"); }
__device__ __forceinline__ float2 lds64f(uint32_t addr) { float2 v; asm volatile("ld.shared.v2.f32 {%0,%1}, [%2];" : "=f"(v.x), "=f"(v.y) : "r"(addr) : "memory"); return v; }
__device__ __forceinline__ uint32_t dlo(uint32_t addr, uint32_t lbo) { return ((addr & 0x3FFFF) >> 4) | ((lbo >> 4) << 16); }

template<int SD> __device__ __forceinline__ void wg_ss_n128_tb1(float (&d)[64], uint32_t da, uint32_t db) {
  asm volatile("{\n.reg .b64 da, db;\nmov.b64 da, {%64, 0x40000040};\nmov.b64 db, {%65, 0x40000040};\n"
    "wgmma.mma_async.sync.aligned.m64n128k16.f32.bf16.bf16 {%0, %1, %2, %3, %4, %5, %6, %7, %8, %9, %10, %11, %12, %13, %14, %15, %16, %17, %18, %19, %20, %21, %22, %23, %24, %25, %26, %27, %28, %29, %30, %31, %32, %33, %34, %35, %36, %37, %38, %39, %40, %41, %42, %43, %44, %45, %46, %47, %48, %49, %50, %51, %52, %53, %54, %55, %56, %57, %58, %59, %60, %61, %62, %63}, da, db, %66, 1, 1, 0, 1;\n}\n"
    : "+f"(d[0]), "+f"(d[1]), "+f"(d[2]), "+f"(d[3]), "+f"(d[4]), "+f"(d[5]), "+f"(d[6]), "+f"(d[7]), "+f"(d[8]), "+f"(d[9]), "+f"(d[10]), "+f"(d[11]), "+f"(d[12]), "+f"(d[13]), "+f"(d[14]), "+f"(d[15]), "+f"(d[16]), "+f"(d[17]), "+f"(d[18]), "+f"(d[19]), "+f"(d[20]), "+f"(d[21]), "+f"(d[22]), "+f"(d[23]), "+f"(d[24]), "+f"(d[25]), "+f"(d[26]), "+f"(d[27]), "+f"(d[28]), "+f"(d[29]), "+f"(d[30]), "+f"(d[31]), "+f"(d[32]), "+f"(d[33]), "+f"(d[34]), "+f"(d[35]), "+f"(d[36]), "+f"(d[37]), "+f"(d[38]), "+f"(d[39]), "+f"(d[40]), "+f"(d[41]), "+f"(d[42]), "+f"(d[43]), "+f"(d[44]), "+f"(d[45]), "+f"(d[46]), "+f"(d[47]), "+f"(d[48]), "+f"(d[49]), "+f"(d[50]), "+f"(d[51]), "+f"(d[52]), "+f"(d[53]), "+f"(d[54]), "+f"(d[55]), "+f"(d[56]), "+f"(d[57]), "+f"(d[58]), "+f"(d[59]), "+f"(d[60]), "+f"(d[61]), "+f"(d[62]), "+f"(d[63])
    : "r"(da), "r"(db), "n"(SD));
}
template<int SD> __device__ __forceinline__ void wg_rs_n128_tb1(float (&d)[64], uint32_t a0, uint32_t a1, uint32_t a2, uint32_t a3, uint32_t db) {
  asm volatile("{\n.reg .b64 db;\nmov.b64 db, {%68, 0x40000040};\n"
    "wgmma.mma_async.sync.aligned.m64n128k16.f32.bf16.bf16 {%0, %1, %2, %3, %4, %5, %6, %7, %8, %9, %10, %11, %12, %13, %14, %15, %16, %17, %18, %19, %20, %21, %22, %23, %24, %25, %26, %27, %28, %29, %30, %31, %32, %33, %34, %35, %36, %37, %38, %39, %40, %41, %42, %43, %44, %45, %46, %47, %48, %49, %50, %51, %52, %53, %54, %55, %56, %57, %58, %59, %60, %61, %62, %63}, {%64, %65, %66, %67}, db, %69, 1, 1, 1;\n}\n"
    : "+f"(d[0]), "+f"(d[1]), "+f"(d[2]), "+f"(d[3]), "+f"(d[4]), "+f"(d[5]), "+f"(d[6]), "+f"(d[7]), "+f"(d[8]), "+f"(d[9]), "+f"(d[10]), "+f"(d[11]), "+f"(d[12]), "+f"(d[13]), "+f"(d[14]), "+f"(d[15]), "+f"(d[16]), "+f"(d[17]), "+f"(d[18]), "+f"(d[19]), "+f"(d[20]), "+f"(d[21]), "+f"(d[22]), "+f"(d[23]), "+f"(d[24]), "+f"(d[25]), "+f"(d[26]), "+f"(d[27]), "+f"(d[28]), "+f"(d[29]), "+f"(d[30]), "+f"(d[31]), "+f"(d[32]), "+f"(d[33]), "+f"(d[34]), "+f"(d[35]), "+f"(d[36]), "+f"(d[37]), "+f"(d[38]), "+f"(d[39]), "+f"(d[40]), "+f"(d[41]), "+f"(d[42]), "+f"(d[43]), "+f"(d[44]), "+f"(d[45]), "+f"(d[46]), "+f"(d[47]), "+f"(d[48]), "+f"(d[49]), "+f"(d[50]), "+f"(d[51]), "+f"(d[52]), "+f"(d[53]), "+f"(d[54]), "+f"(d[55]), "+f"(d[56]), "+f"(d[57]), "+f"(d[58]), "+f"(d[59]), "+f"(d[60]), "+f"(d[61]), "+f"(d[62]), "+f"(d[63])
    : "r"(a0), "r"(a1), "r"(a2), "r"(a3), "r"(db), "n"(SD));
}
template<int SD> __device__ __forceinline__ void wg_ss_n64_tb1(float (&d)[32], uint32_t da, uint32_t db) {
  asm volatile("{\n.reg .b64 da, db;\nmov.b64 da, {%32, 0x40000040};\nmov.b64 db, {%33, 0x40000040};\n"
    "wgmma.mma_async.sync.aligned.m64n64k16.f32.bf16.bf16 {%0, %1, %2, %3, %4, %5, %6, %7, %8, %9, %10, %11, %12, %13, %14, %15, %16, %17, %18, %19, %20, %21, %22, %23, %24, %25, %26, %27, %28, %29, %30, %31}, da, db, %34, 1, 1, 0, 1;\n}\n"
    : "+f"(d[0]), "+f"(d[1]), "+f"(d[2]), "+f"(d[3]), "+f"(d[4]), "+f"(d[5]), "+f"(d[6]), "+f"(d[7]), "+f"(d[8]), "+f"(d[9]), "+f"(d[10]), "+f"(d[11]), "+f"(d[12]), "+f"(d[13]), "+f"(d[14]), "+f"(d[15]), "+f"(d[16]), "+f"(d[17]), "+f"(d[18]), "+f"(d[19]), "+f"(d[20]), "+f"(d[21]), "+f"(d[22]), "+f"(d[23]), "+f"(d[24]), "+f"(d[25]), "+f"(d[26]), "+f"(d[27]), "+f"(d[28]), "+f"(d[29]), "+f"(d[30]), "+f"(d[31])
    : "r"(da), "r"(db), "n"(SD));
}
template<int SD> __device__ __forceinline__ void wg_ss_n80_tb0(float (&d)[40], uint32_t da, uint32_t db) {
  asm volatile("{\n.reg .b64 da, db;\nmov.b64 da, {%40, 0x40000040};\nmov.b64 db, {%41, 0x40000040};\n"
    "wgmma.mma_async.sync.aligned.m64n80k16.f32.bf16.bf16 {%0, %1, %2, %3, %4, %5, %6, %7, %8, %9, %10, %11, %12, %13, %14, %15, %16, %17, %18, %19, %20, %21, %22, %23, %24, %25, %26, %27, %28, %29, %30, %31, %32, %33, %34, %35, %36, %37, %38, %39}, da, db, %42, 1, 1, 0, 0;\n}\n"
    : "+f"(d[0]), "+f"(d[1]), "+f"(d[2]), "+f"(d[3]), "+f"(d[4]), "+f"(d[5]), "+f"(d[6]), "+f"(d[7]), "+f"(d[8]), "+f"(d[9]), "+f"(d[10]), "+f"(d[11]), "+f"(d[12]), "+f"(d[13]), "+f"(d[14]), "+f"(d[15]), "+f"(d[16]), "+f"(d[17]), "+f"(d[18]), "+f"(d[19]), "+f"(d[20]), "+f"(d[21]), "+f"(d[22]), "+f"(d[23]), "+f"(d[24]), "+f"(d[25]), "+f"(d[26]), "+f"(d[27]), "+f"(d[28]), "+f"(d[29]), "+f"(d[30]), "+f"(d[31]), "+f"(d[32]), "+f"(d[33]), "+f"(d[34]), "+f"(d[35]), "+f"(d[36]), "+f"(d[37]), "+f"(d[38]), "+f"(d[39])
    : "r"(da), "r"(db), "n"(SD));
}
template<int SD> __device__ __forceinline__ void wg_rs_n64_tb1(float (&d)[32], uint32_t a0, uint32_t a1, uint32_t a2, uint32_t a3, uint32_t db) {
  asm volatile("{\n.reg .b64 db;\nmov.b64 db, {%36, 0x40000040};\n"
    "wgmma.mma_async.sync.aligned.m64n64k16.f32.bf16.bf16 {%0, %1, %2, %3, %4, %5, %6, %7, %8, %9, %10, %11, %12, %13, %14, %15, %16, %17, %18, %19, %20, %21, %22, %23, %24, %25, %26, %27, %28, %29, %30, %31}, {%32, %33, %34, %35}, db, %37, 1, 1, 1;\n}\n"
    : "+f"(d[0]), "+f"(d[1]), "+f"(d[2]), "+f"(d[3]), "+f"(d[4]), "+f"(d[5]), "+f"(d[6]), "+f"(d[7]), "+f"(d[8]), "+f"(d[9]), "+f"(d[10]), "+f"(d[11]), "+f"(d[12]), "+f"(d[13]), "+f"(d[14]), "+f"(d[15]), "+f"(d[16]), "+f"(d[17]), "+f"(d[18]), "+f"(d[19]), "+f"(d[20]), "+f"(d[21]), "+f"(d[22]), "+f"(d[23]), "+f"(d[24]), "+f"(d[25]), "+f"(d[26]), "+f"(d[27]), "+f"(d[28]), "+f"(d[29]), "+f"(d[30]), "+f"(d[31])
    : "r"(a0), "r"(a1), "r"(a2), "r"(a3), "r"(db), "n"(SD));
}

constexpr int RING = 5;
constexpr uint32_t STAGE = 32768;
constexpr uint32_t OFF_X = 32768, OFF_W = 65536, OFF_MISC = OFF_W + RING * STAGE;
constexpr int ROW_SMEM = OFF_MISC + 256 + 1024 + 1024;

struct Ctx {
  uint32_t sA, sX, sW, full, empty, stats;
  uint32_t frag;
  uint32_t rsw;
  uint32_t hi;
  int wg, tid, lane;
  int pk;
};
__device__ __forceinline__ uint32_t stage_wait(const Ctx& c, int n) {
  const int q = n / RING, s = n - q * RING;
  if (c.tid == 0) PROF_STG(n + c.pk, 1);
  mbar_wait(c.full + 8 * s, q & 1);
  if (c.tid == 0) PROF_STG(n + c.pk, 2);
  return dlo(c.sW + s * STAGE, 0);
}
__device__ __forceinline__ void stage_release(const Ctx& c, int n) {
  const int s = n % RING;
  if (c.tid == 0) { mbar_arrive(c.empty + 8 * s); PROF_STG(n + c.pk, 3); }
}
__device__ __forceinline__ void turn_begin(const Ctx& c) { bar_sync(5 + c.wg, 256); }
__device__ __forceinline__ void turn_end(const Ctx& c) { bar_arrive(5 + (c.wg ^ 1), 256); }
template<int FIRST> __device__ __forceinline__ void piece_ss(float (&acc)[64], uint32_t dA, uint32_t dB) {
  dB += (16384 >> 4) << 16;
  wg_ss_n128_tb1<FIRST ? 0 : 1>(acc, dA, dB);
#pragma unroll
  for (int kk = 1; kk < 8; kk++) wg_ss_n128_tb1<1>(acc, dA + (kk >> 2) * 512 + (kk & 3) * 2, dB + kk * 128);
}
__device__ __forceinline__ void ff_g1(float (&h)[32], uint32_t dA, uint32_t dB) {
  wg_ss_n64_tb1<0>(h, dA, dB);
#pragma unroll
  for (int kk = 1; kk < 16; kk++) wg_ss_n64_tb1<1>(h, dA + (kk >> 2) * 512 + (kk & 3) * 2, dB + kk * 128);
}
__device__ __forceinline__ void ff_g2(float (&acc)[64], const uint32_t (&P)[16], uint32_t dB, int half) {
  dB += ((8192 >> 4) << 16) + half * 1024;
#pragma unroll
  for (int kk = 0; kk < 4; kk++) wg_rs_n128_tb1<1>(acc, P[4 * kk], P[4 * kk + 1], P[4 * kk + 2], P[4 * kk + 3], dB + kk * 128);
}
template<int FIRST> __device__ __forceinline__ void gemm256(const Ctx& c, float (&acc)[64], int n) {
  const uint32_t dA = dlo(c.sA, 16);
  uint32_t b = stage_wait(c, n);
  turn_begin(c);
  wg_fence(); piece_ss<FIRST>(acc, dA, b); wg_commit();
  b = stage_wait(c, n + 1);
  wg_fence(); piece_ss<0>(acc, dA + 1024, b); wg_commit();
  turn_end(c);
  wg_wait<1>(); stage_release(c, n);
  wg_wait<0>(); stage_release(c, n + 1);
}
__device__ __forceinline__ uint32_t frag_addr(const Ctx& c, uint32_t tile, int j) {
  return tile + (2 * c.wg + (j >> 2)) * 8192 + c.frag + ((((j & 3) * 2 + c.hi) ^ c.rsw) << 4);
}
__device__ __forceinline__ void load_half(const Ctx& c, uint32_t tile, float (&v)[64]) {
#pragma unroll
  for (int j = 0; j < 8; j++) {
    uint32_t r0, r1, r2, r3;
    ldsm_x4(frag_addr(c, tile, j), r0, r1, r2, r3);
    v[8 * j] = bf_lo(r0); v[8 * j + 1] = bf_hi(r0); v[8 * j + 2] = bf_lo(r1); v[8 * j + 3] = bf_hi(r1);
    v[8 * j + 4] = bf_lo(r2); v[8 * j + 5] = bf_hi(r2); v[8 * j + 6] = bf_lo(r3); v[8 * j + 7] = bf_hi(r3);
  }
}
__device__ __forceinline__ void store_half(const Ctx& c, uint32_t tile, const float (&v)[64], float a0, float b0, float a1, float b1) {
#pragma unroll
  for (int j = 0; j < 8; j++)
    stsm_x4(frag_addr(c, tile, j),
            pack_bf16(fmaf(v[8 * j], a0, b0), fmaf(v[8 * j + 1], a0, b0)), pack_bf16(fmaf(v[8 * j + 2], a1, b1), fmaf(v[8 * j + 3], a1, b1)),
            pack_bf16(fmaf(v[8 * j + 4], a0, b0), fmaf(v[8 * j + 5], a0, b0)), pack_bf16(fmaf(v[8 * j + 6], a1, b1), fmaf(v[8 * j + 7], a1, b1)));
}
__device__ __forceinline__ void store_half_raw(const Ctx& c, uint32_t tile, const float (&v)[64]) {
#pragma unroll
  for (int j = 0; j < 8; j++)
    stsm_x4(frag_addr(c, tile, j), pack_bf16(v[8 * j], v[8 * j + 1]), pack_bf16(v[8 * j + 2], v[8 * j + 3]),
            pack_bf16(v[8 * j + 4], v[8 * j + 5]), pack_bf16(v[8 * j + 6], v[8 * j + 7]));
}
__device__ __forceinline__ void ln_stats(const Ctx& c, const float (&v)[64], float scale, float& a0, float& b0, float& a1, float& b1) {
  float s0 = 0.f, s1 = 0.f, q0 = 0.f, q1 = 0.f, s2 = 0.f, s3 = 0.f, q2 = 0.f, q3 = 0.f;
#pragma unroll
  for (int i = 0; i < 16; i++) {
    s0 += v[4 * i]; q0 = fmaf(v[4 * i], v[4 * i], q0);
    s2 += v[4 * i + 1]; q2 = fmaf(v[4 * i + 1], v[4 * i + 1], q2);
    s1 += v[4 * i + 2]; q1 = fmaf(v[4 * i + 2], v[4 * i + 2], q1);
    s3 += v[4 * i + 3]; q3 = fmaf(v[4 * i + 3], v[4 * i + 3], q3);
  }
  s0 += s2; q0 += q2; s1 += s3; q1 += q3;
  s0 += __shfl_xor_sync(0xffffffff, s0, 1); q0 += __shfl_xor_sync(0xffffffff, q0, 1);
  s1 += __shfl_xor_sync(0xffffffff, s1, 1); q1 += __shfl_xor_sync(0xffffffff, q1, 1);
  s0 += __shfl_xor_sync(0xffffffff, s0, 2); q0 += __shfl_xor_sync(0xffffffff, q0, 2);
  s1 += __shfl_xor_sync(0xffffffff, s1, 2); q1 += __shfl_xor_sync(0xffffffff, q1, 2);
  const uint32_t row = (c.tid >> 5) * 16 + (c.lane >> 2);
  if ((c.lane & 3) == 0) {
    sts64f(c.stats + c.wg * 512 + row * 8, s0, q0);
    sts64f(c.stats + c.wg * 512 + (row + 8) * 8, s1, q1);
  }
  bar_sync(1, 256);
  const float2 o0 = lds64f(c.stats + (c.wg ^ 1) * 512 + row * 8), o1 = lds64f(c.stats + (c.wg ^ 1) * 512 + (row + 8) * 8);
  const float m0 = (s0 + o0.x) * (1.f / 256.f), m1 = (s1 + o1.x) * (1.f / 256.f);
  const float var0 = fmaxf(fmaf(-m0, m0, (q0 + o0.y) * (1.f / 256.f)), 0.f), var1 = fmaxf(fmaf(-m1, m1, (q1 + o1.y) * (1.f / 256.f)), 0.f);
  a0 = rsqrtf(var0 + 1e-5f) * scale; a1 = rsqrtf(var1 + 1e-5f) * scale;
  b0 = -m0 * a0; b1 = -m1 * a1;
}
__device__ __forceinline__ float silu_half(float h) { return fmaf(h, tanh_fast(h), h); }
__device__ __forceinline__ float silu_quarter(float h) { const float q = 0.5f * h; return fmaf(q, tanh_fast(h), q); }
__device__ __forceinline__ void silu_pack(const float (&acc)[32], uint32_t (&P)[16]) {
#pragma unroll
  for (int i = 0; i < 16; i++) P[i] = pack_bf16(silu_quarter(acc[2 * i]), silu_quarter(acc[2 * i + 1]));
}
__device__ __forceinline__ void ff_block(const Ctx& c, int n0, float (&own)[64]) {
  float oth[64], h[32];
  uint32_t P[16];
#pragma unroll
  for (int i = 0; i < 64; i++) oth[i] = 0.f;
  const uint32_t dA = dlo(c.sA, 16);
  {
    const uint32_t b = stage_wait(c, n0 + c.wg);
    turn_begin(c);
    wg_fence(); ff_g1(h, dA, b); wg_commit();
    turn_end(c);
    wg_wait<0>(); stage_release(c, n0 + c.wg);
    silu_pack(h, P);
  }
#pragma unroll 1
  for (int it = 1; it < 8; it++) {
    const int n = n0 + 4 * it - 2 + 2 * c.wg;
    uint32_t b = stage_wait(c, n);
    turn_begin(c);
    wg_fence(); ff_g2(own, P, b, c.wg); ff_g2(oth, P, b, c.wg ^ 1); wg_commit();
    b = stage_wait(c, n + 1);
    wg_fence(); ff_g1(h, dA, b); wg_commit();
    turn_end(c);
    wg_wait<1>(); stage_release(c, n);
    wg_wait<0>(); stage_release(c, n + 1);
    silu_pack(h, P);
  }
  if (c.wg == 0) bar_arrive(2, 256);
  {
    const int n = n0 + 30 + c.wg;
    const uint32_t b = stage_wait(c, n);
    turn_begin(c);
    wg_fence(); ff_g2(oth, P, b, c.wg ^ 1); wg_commit();
    ff_g2(own, P, b, c.wg); wg_commit();
    turn_end(c);
    wg_wait<1>();
    if (c.wg == 1) bar_sync(2, 256);
    const uint32_t e = (c.wg == 0 ? c.sX : c.sA) + c.tid * 16;
#pragma unroll
    for (int i = 0; i < 16; i++)
      sts128(e + i * 2048, make_uint4(__float_as_uint(oth[4 * i]), __float_as_uint(oth[4 * i + 1]), __float_as_uint(oth[4 * i + 2]), __float_as_uint(oth[4 * i + 3])));
    wg_wait<0>(); stage_release(c, n);
  }
  bar_sync(1, 256);
  const uint32_t e = (c.wg == 0 ? c.sA : c.sX) + c.tid * 16;
#pragma unroll
  for (int i = 0; i < 16; i++) {
    const uint4 u = lds128(e + i * 2048);
    own[4 * i] += __uint_as_float(u.x); own[4 * i + 1] += __uint_as_float(u.y);
    own[4 * i + 2] += __uint_as_float(u.z); own[4 * i + 3] += __uint_as_float(u.w);
  }
}
__device__ __forceinline__ void produce(uint32_t sW, uint32_t full, uint32_t empty, int n, const CUtensorMap* tm, int k0, int nblk, int c0 = 0) {
  const int q = n / RING, s = n - q * RING;
  mbar_wait(empty + 8 * s, (q & 1) ^ 1);
  PROF_STG(n + ((sW & 1) ? 132 * 64 : 0), 0);
  sW &= ~1u;
  mbar_expect_tx(full + 8 * s, STAGE);
  tma_load_3d(sW + s * STAGE, tm, full + 8 * s, c0, k0, nblk);
}
__device__ __forceinline__ void produce_ff(uint32_t sW, uint32_t full, uint32_t empty, int n0, const CUtensorMap* tmA, const CUtensorMap* tmB) {
#pragma unroll 1
  for (int m = 0; m < 32; m++) {
    int is2, j;
    if (m < 2) { is2 = 0; j = m; }
    else if (m == 31) { is2 = 1; j = 15; }
    else { const int q = m - 2; is2 = !(q & 1); j = (q >> 1) + (is2 ? 0 : 2); }
    if (is2) produce(sW, full, empty, n0 + m, tmB, 64 * j, 0);
    else produce(sW, full, empty, n0 + m, tmA, 0, j);
  }
}
__device__ __forceinline__ Ctx make_ctx(uint32_t base, int pk = 0) {
  Ctx c; c.pk = pk;
  c.sA = base; c.sX = base + OFF_X; c.sW = base + OFF_W;
  c.full = base + OFF_MISC; c.empty = c.full + 8 * RING; c.stats = base + OFF_MISC + 256;
  c.wg = __shfl_sync(0xffffffff, (int)(threadIdx.x >> 7), 0);
  c.tid = threadIdx.x & 127; c.lane = threadIdx.x & 31;
  const uint32_t r = (c.tid >> 5) * 16 + (c.lane & 7) + ((c.lane >> 3) & 1) * 8;
  c.frag = r * 128; c.rsw = r & 7; c.hi = c.lane >> 4;
  return c;
}
__device__ __forceinline__ void row_init(uint32_t base) {
  if (threadIdx.x == 0) {
    const uint32_t full = base + OFF_MISC;
    for (int i = 0; i < RING; i++) { mbar_init(full + 8 * i, 1); mbar_init(full + 8 * RING + 8 * i, 1); }
    mbar_init(full + 16 * RING, 1);
    mbar_init(full + 16 * RING + 8, 1);
    asm volatile("fence.mbarrier_init.release.cluster;" ::: "memory");
  }
  __syncthreads();
}
struct Wptrs { const void* p[8]; uint32_t bytes[8]; };

__global__ void __launch_bounds__(384, 1) k1_ff1_qkv(const __grid_constant__ CUtensorMap tmX, const __grid_constant__ CUtensorMap tmW1a,
    const __grid_constant__ CUtensorMap tmW1b, const __grid_constant__ CUtensorMap tmWqkv, const __grid_constant__ CUtensorMap tmX1st,
    const __grid_constant__ CUtensorMap tmQKVst, const __grid_constant__ Wptrs wp) {
  extern __shared__ uint8_t smem_raw[];
  const uint32_t base = (smem_u32(smem_raw) + 1023) & ~1023u;
  const int tile = blockIdx.x;
  if (threadIdx.x == 256) { prefetch_tmap(&tmX); prefetch_tmap(&tmW1a); prefetch_tmap(&tmW1b); prefetch_tmap(&tmWqkv); prefetch_tmap(&tmX1st); prefetch_tmap(&tmQKVst); }
  row_init(base);
  pdl_launch();
  if (threadIdx.x >= 256) {
    asm volatile("setmaxnreg.dec.sync.aligned.u32 24;");
    const uint32_t sW = base + OFF_W, full = base + OFF_MISC, empty = full + 8 * RING, inbar = full + 16 * RING;
    if (threadIdx.x == 256) {
      mbar_expect_tx(inbar, 32768);
      tma_load_3d(base + OFF_X, &tmX, inbar, 0, tile * 64, 0);
      produce_ff(sW, full, empty, 0, &tmW1a, &tmW1b);
#pragma unroll 1
      for (int m = 0; m < 12; m++) produce(sW, full, empty, 32 + m, &tmWqkv, 128 * (m & 1), 2 * (m >> 1));
    } else if (threadIdx.x >= 288 && threadIdx.x < 296) {
      const int w = threadIdx.x - 288;
      if (w >= 2) mbar_wait(inbar, 0);
      const uint32_t bytes = wp.bytes[w], per = ((bytes / NTILE) + 127) & ~127u, off = per * tile;
      if (off < bytes) l2_prefetch((const uint8_t*)wp.p[w] + off, min(per, bytes - off));
    } else if (threadIdx.x >= 320) {
      g_halo[tile * 128 + (threadIdx.x - 320)] = make_uint4(~0u, ~0u, ~0u, ~0u);
      g_halo[tile * 128 + 64 + (threadIdx.x - 320)] = make_uint4(~0u, ~0u, ~0u, ~0u);
    }
  } else {
    asm volatile("setmaxnreg.inc.sync.aligned.u32 240;");
    const Ctx c = make_ctx(base);
    if (c.wg == 1) turn_end(c);
    float own[64];
    float a0, b0, a1, b1;
    PROF_MARK(0, 0);
    mbar_wait(c.full + 16 * RING, 0);
    PROF_MARK(0, 1);
    load_half(c, c.sX, own);
    ln_stats(c, own, 0.5f, a0, b0, a1, b1);
    store_half(c, c.sA, own, a0, b0, a1, b1);
    fence_async_smem();
    bar_sync(1, 256);
    PROF_MARK(0, 2);
    ff_block(c, 0, own);
    PROF_MARK(0, 3);
    ln_stats(c, own, 1.f, a0, b0, a1, b1);
    store_half(c, c.sA, own, a0, b0, a1, b1);
    store_half_raw(c, c.sX, own);
    fence_async_smem();
    bar_sync(1, 256);
    PROF_MARK(0, 4);
    if (c.tid == 0) { tma_store_3d(&tmX1st, c.sX + c.wg * 16384, 0, tile * 64, 2 * c.wg); bulk_commit(); }
#pragma unroll 1
    for (int cc = 0; cc < 3; cc++) {
      const int j = 2 * cc + c.wg;
      gemm256<1>(c, own, 32 + 2 * j);
      const float sc = (cc == 0) ? 0.125f * 1.4426950408889634f : 1.f;
      if (c.tid == 0) bulk_wait_read();
      bar_sync(3 + c.wg, 128);
      store_half(c, c.sX, own, sc, 0.f, sc, 0.f);
      fence_async_smem();
      bar_sync(3 + c.wg, 128);
      if (c.tid == 0) { tma_store_3d(&tmQKVst, c.sX + c.wg * 16384, 0, tile * 64, 2 * j); bulk_commit(); }
    }
    PROF_MARK(0, 5);
    if (c.tid == 0) bulk_wait_all();
    PROF_MARK(0, 6);
  }
}

__global__ void __launch_bounds__(384, 1) k3_tail(const __grid_constant__ CUtensorMap tmAtt, const __grid_constant__ CUtensorMap tmX1,
    const __grid_constant__ CUtensorMap tmWo, const __grid_constant__ CUtensorMap tmPw1, const __grid_constant__ CUtensorMap tmPw2,
    const __grid_constant__ CUtensorMap tmW2a, const __grid_constant__ CUtensorMap tmW2b, const __grid_constant__ CUtensorMap tmOut,
    const uint4* __restrict__ dw) {
  extern __shared__ uint8_t smem_raw[];
  const uint32_t base = (smem_u32(smem_raw) + 1023) & ~1023u;
  const int tile = blockIdx.x;
  if (threadIdx.x == 256) {
    prefetch_tmap(&tmWo); prefetch_tmap(&tmAtt); prefetch_tmap(&tmX1); prefetch_tmap(&tmPw1); prefetch_tmap(&tmPw2);
    prefetch_tmap(&tmW2a); prefetch_tmap(&tmW2b); prefetch_tmap(&tmOut);
  }
  row_init(base);
  if (threadIdx.x >= 256) {
    asm volatile("setmaxnreg.dec.sync.aligned.u32 24;");
    const uint32_t sW = (base + OFF_W) | 1, full = base + OFF_MISC, empty = full + 8 * RING, inbar = full + 16 * RING;
    if (threadIdx.x == 256) {
#pragma unroll 1
      for (int m = 0; m < 4; m++) produce(sW, full, empty, m, &tmWo, 128 * (m & 1), 2 * (m >> 1));
#pragma unroll 1
      for (int m = 0; m < 8; m++) produce(sW, full, empty, 4 + m, &tmPw1, 128 * (m & 1), 0, 64 * (2 * ((m >> 1) & 1) + (m >> 2)));
#pragma unroll 1
      for (int m = 0; m < 4; m++) produce(sW, full, empty, 12 + m, &tmPw2, 128 * (m & 1), 2 * (m >> 1));
      produce_ff(sW, full, empty, 16, &tmW2a, &tmW2b);
    } else if (threadIdx.x == 288) {
      pdl_wait();
      mbar_expect_tx(inbar + 8, 32768);
      tma_load_3d(base, &tmAtt, inbar + 8, 0, tile * 64, 0);
      mbar_expect_tx(inbar, 32768);
      tma_load_3d(base + OFF_X, &tmX1, inbar, 0, tile * 64, 0);
    }
  } else {
    asm volatile("setmaxnreg.inc.sync.aligned.u32 240;");
    const Ctx c = make_ctx(base, 132 * 64);
    if (c.wg == 1) turn_end(c);
    float own[64];
    float a0, b0, a1, b1;
    PROF_MARK(2, 0);
    pdl_wait();
    PROF_MARK(2, 1);
    mbar_wait(c.full + 16 * RING, 0);
    load_half(c, c.sX, own);
    mbar_wait(c.full + 16 * RING + 8, 0);
    PROF_MARK(2, 2);
    gemm256<0>(c, own, 2 * c.wg);
    PROF_MARK(2, 3);
    ln_stats(c, own, 0.5f, a0, b0, a1, b1);
    store_half(c, c.sA, own, a0, b0, a1, b1);
    fence_async_smem();
    bar_sync(1, 256);
    PROF_MARK(2, 4);
    uint4 dwr[5];
#pragma unroll
    for (int i = 0; i < 5; i++) dwr[i] = __ldg(dw + i * 32 + c.lane);
    const bool top = c.tid < 8, pub = top || c.tid >= 120;
    uint32_t* halo_out = (uint32_t*)g_halo + (tile * 4 + (top ? (c.tid >> 2) : ((c.tid >> 2) - 28))) * 128 + c.wg * 64 + (c.lane & 3);
#pragma unroll 1
    for (int q = 0; q < 2; q++) {
      float ab[64];
      gemm256<1>(c, ab, 4 + 4 * q + 2 * c.wg);
#pragma unroll
      for (int j = 0; j < 4; j++) {
        float g[8];
#pragma unroll
        for (int i = 0; i < 8; i++) g[i] = fmaf(ab[8 * j + i], tanh_fast(ab[32 + 8 * j + i]), ab[8 * j + i]);
        const uint32_t p0 = pack_bf16(g[0], g[1]), p1 = pack_bf16(g[2], g[3]), p2 = pack_bf16(g[4], g[5]), p3 = pack_bf16(g[6], g[7]);
        if (pub) {
          uint32_t* hp = halo_out + q * 32 + j * 8;
          asm volatile("st.relaxed.gpu.global.u32 [%0], %1;" :: "l"(hp), "r"(top ? p0 : p1) : "memory");
          asm volatile("st.relaxed.gpu.global.u32 [%0], %1;" :: "l"(hp + 4), "r"(top ? p2 : p3) : "memory");
        }
        stsm_x4(c.sX + (2 * c.wg + q) * 8192 + c.frag + (((j * 2 + c.hi) ^ c.rsw) << 4), p0, p1, p2, p3);
      }
    }
    bar_sync(1, 256);
    PROF_MARK(2, 5);
    {
      const int wi = threadIdx.x >> 5;
      const uint32_t col = (c.lane >> 3) * 8192, ch = c.lane & 7;
      uint4 r[12];
#pragma unroll
      for (int i = 0; i < 12; i++) {
        const int row = (wi * 8 - 2 + i) & 63;
        r[i] = lds128(c.sX + col + row * 128 + ((ch ^ (row & 7)) << 4));
      }
      uint32_t w[5][4];
#pragma unroll
      for (int k = 0; k < 5; k++) {
        w[k][0] = bmul2(dwr[k].x, 0x3F003F00u); w[k][1] = bmul2(dwr[k].y, 0x3F003F00u);
        w[k][2] = bmul2(dwr[k].z, 0x3F003F00u); w[k][3] = bmul2(dwr[k].w, 0x3F003F00u);
      }
      auto conv_row = [&](int i) {
        uint32_t o[4];
#pragma unroll
        for (int q = 0; q < 4; q++) {
          uint32_t acc = bmul2(q == 0 ? r[i].x : q == 1 ? r[i].y : q == 2 ? r[i].z : r[i].w, w[0][q]);
#pragma unroll
          for (int k = 1; k < 5; k++) acc = bfma2(q == 0 ? r[i + k].x : q == 1 ? r[i + k].y : q == 2 ? r[i + k].z : r[i + k].w, w[k][q], acc);
          o[q] = pack_bf16(silu_half(bf_lo(acc)), silu_half(bf_hi(acc)));
        }
        sts128(c.sA + col + (wi * 8 + i) * 128 + ((ch ^ i) << 4), make_uint4(o[0], o[1], o[2], o[3]));
      };
      conv_row(2); conv_row(3); conv_row(4); conv_row(5);
      const int R0 = tile * 64 + wi * 8;
      if ((R0 % T_) == 0) { r[0] = make_uint4(0, 0, 0, 0); r[1] = r[0]; }
      else if (wi == 0) { const uint4* sp = g_halo + ((tile - 1) * 4 + 2) * 32 + c.lane; halo_poll(sp, r[0]); halo_poll(sp + 32, r[1]); }
      if (((R0 + 8) % T_) == 0) { r[10] = make_uint4(0, 0, 0, 0); r[11] = r[10]; }
      else if (wi == 7) { const uint4* sp = g_halo + ((tile + 1) * 4) * 32 + c.lane; halo_poll(sp, r[10]); halo_poll(sp + 32, r[11]); }
      conv_row(0); conv_row(1); conv_row(6); conv_row(7);
    }
    fence_async_smem();
    bar_sync(1, 256);
    PROF_MARK(2, 6);
    gemm256<0>(c, own, 12 + 2 * c.wg);
    PROF_MARK(2, 7);
    ln_stats(c, own, 0.5f, a0, b0, a1, b1);
    store_half(c, c.sA, own, a0, b0, a1, b1);
    fence_async_smem();
    bar_sync(1, 256);
    PROF_MARK(2, 8);
    ff_block(c, 16, own);
    PROF_MARK(2, 9);
    ln_stats(c, own, 1.f, a0, b0, a1, b1);
    store_half(c, c.sX, own, a0, b0, a1, b1);
    fence_async_smem();
    bar_sync(3 + c.wg, 128);
    if (c.tid == 0) { tma_store_3d(&tmOut, c.sX + c.wg * 16384, 0, tile * 64, 2 * c.wg); bulk_commit(); PROF_MARK(2, 10); bulk_wait_all(); }
    PROF_MARK(2, 11);
  }
}

constexpr int NSTG = 4;
constexpr int KVB = 160 * 128;
constexpr int NKV = T_ / 160;
constexpr int ATT_SMEM = 32768 + NSTG * 2 * KVB + 256 + 1024;

struct AttCtx { uint32_t sKV, full, empty; const CUtensorMap* tmKV; int h, b, wg; };
__device__ __forceinline__ void att_load_stage(const AttCtx& a, int i) {
  const int s = i & (NSTG - 1);
  mbar_expect_tx(a.full + 8 * s, 2 * KVB);
  tma_load_3d(a.sKV + s * 2 * KVB, a.tmKV, a.full + 8 * s, 256 + a.h * 64, i * 160, a.b);
  tma_load_3d(a.sKV + s * 2 * KVB + KVB, a.tmKV, a.full + 8 * s, 512 + a.h * 64, i * 160, a.b);
}
__device__ __forceinline__ void att_qk(float (&S)[40], uint32_t dQ, uint32_t kd) {
  wg_ss_n80_tb0<0>(S, dQ, kd);
#pragma unroll
  for (int kk = 1; kk < 4; kk++) wg_ss_n80_tb0<1>(S, dQ + kk * 2, kd + kk * 2);
}
__device__ __forceinline__ void att_pv(float (&O)[32], const uint32_t (&P)[20], uint32_t vd) {
#pragma unroll
  for (int kk = 0; kk < 5; kk++) wg_rs_n64_tb1<1>(O, P[kk * 4], P[kk * 4 + 1], P[kk * 4 + 2], P[kk * 4 + 3], vd + kk * 128);
}
template<bool SAFE>
__device__ __forceinline__ void att_softmax(const float (&S)[40], uint32_t (&P)[20], float (&O)[32], float& m0, float& m1, float& l0, float& l1) {
  if (SAFE) {
    float x0 = fmaxf(S[0], S[1]), x1 = fmaxf(S[2], S[3]);
#pragma unroll
    for (int i = 1; i < 10; i++) { x0 = fmaxf(x0, fmaxf(S[4 * i], S[4 * i + 1])); x1 = fmaxf(x1, fmaxf(S[4 * i + 2], S[4 * i + 3])); }
    x0 = fmaxf(x0, __shfl_xor_sync(0xffffffff, x0, 1)); x1 = fmaxf(x1, __shfl_xor_sync(0xffffffff, x1, 1));
    x0 = fmaxf(x0, __shfl_xor_sync(0xffffffff, x0, 2)); x1 = fmaxf(x1, __shfl_xor_sync(0xffffffff, x1, 2));
    const float n0 = fmaxf(m0, x0), n1 = fmaxf(m1, x1);
    const float f0 = ex2(m0 - n0), f1 = ex2(m1 - n1);
    m0 = n0; m1 = n1; l0 *= f0; l1 *= f1;
#pragma unroll
    for (int i = 0; i < 8; i++) { O[4 * i] *= f0; O[4 * i + 1] *= f0; O[4 * i + 2] *= f1; O[4 * i + 3] *= f1; }
  }
#pragma unroll
  for (int i = 0; i < 10; i++) {
    float p0, p1, p2, p3;
    if (SAFE) { p0 = ex2(S[4 * i] - m0); p1 = ex2(S[4 * i + 1] - m0); p2 = ex2(S[4 * i + 2] - m1); p3 = ex2(S[4 * i + 3] - m1); }
    else { p0 = ex2(S[4 * i]); p1 = ex2(S[4 * i + 1]); p2 = ex2(S[4 * i + 2]); p3 = ex2(S[4 * i + 3]); }
    l0 += p0 + p1; l1 += p2 + p3;
    P[2 * i] = pack_bf16(p0, p1); P[2 * i + 1] = pack_bf16(p2, p3);
  }
}
template<bool SAFE>
__device__ __forceinline__ void att_pass(const AttCtx& a, uint32_t dQ, float (&O)[32], float& l0, float& l1) {
  float S[40];
  uint32_t P[20];
  float m0 = -INFINITY, m1 = -INFINITY;
  l0 = 0.f; l1 = 0.f;
#pragma unroll
  for (int i = 0; i < 32; i++) O[i] = 0.f;
  const uint32_t dKV = dlo(a.sKV, 16);
  constexpr uint32_t STG = 2 * KVB / 16, VOFF = KVB / 16, HALF = 80 * 128 / 16;
  constexpr int UNR = SAFE ? 1 : 4;
  mbar_wait(a.full, 0);
  wg_fence(); att_qk(S, dQ, dKV); wg_commit(); wg_wait<0>();
  att_softmax<SAFE>(S, P, O, m0, m1, l0, l1);
  wg_fence(); att_pv(O, P, dKV + VOFF); att_qk(S, dQ, dKV + HALF); wg_commit(); wg_wait<0>();
#pragma unroll 1
  for (int it0 = 0; it0 < NKV - 1; it0 += UNR) {
#pragma unroll
    for (int u = 0; u < UNR; u++) {
      const int it = it0 + u;
      const int s = SAFE ? (it & 3) : u, sn = (s + 1) & 3, sp = (s + 3) & 3;
      const uint32_t kb = dKV + s * STG, kn = dKV + sn * STG;
      att_softmax<SAFE>(S, P, O, m0, m1, l0, l1);
      mbar_wait(a.full + 8 * sn, ((it + 1) >> 2) & 1);
      wg_fence(); att_pv(O, P, kb + VOFF + HALF); att_qk(S, dQ, kn); wg_commit(); wg_wait<0>();
      if ((threadIdx.x & 127) == 0) {
        mbar_arrive(a.empty + 8 * s);
        if (a.wg == s && it >= 1 && it - 1 + NSTG < NKV) {
          mbar_wait(a.empty + 8 * sp, ((it - 1) >> 2) & 1);
          att_load_stage(a, it - 1 + NSTG);
        }
      }
      __syncwarp();
      att_softmax<SAFE>(S, P, O, m0, m1, l0, l1);
      wg_fence(); att_pv(O, P, kn + VOFF); att_qk(S, dQ, kn + HALF); wg_commit(); wg_wait<0>();
    }
  }
  att_softmax<SAFE>(S, P, O, m0, m1, l0, l1);
  wg_fence(); att_pv(O, P, dKV + ((NKV - 1) & 3) * STG + VOFF + HALF); wg_commit(); wg_wait<0>();
  l0 += __shfl_xor_sync(0xffffffff, l0, 1); l1 += __shfl_xor_sync(0xffffffff, l1, 1);
  l0 += __shfl_xor_sync(0xffffffff, l0, 2); l1 += __shfl_xor_sync(0xffffffff, l1, 2);
}

__global__ void __launch_bounds__(512, 1) k2_attn(const __grid_constant__ CUtensorMap tmQ, const __grid_constant__ CUtensorMap tmKV,
                                                  const __grid_constant__ CUtensorMap tmO) {
  extern __shared__ uint8_t smem_raw[];
  const uint32_t base = (smem_u32(smem_raw) + 1023) & ~1023u;
  const uint32_t sQ = base;
  AttCtx a;
  a.sKV = base + 32768; a.full = a.sKV + NSTG * 2 * KVB; a.empty = a.full + 8 * NSTG; a.tmKV = &tmKV;
  const uint32_t qbar = a.full + 16 * NSTG;
  const int qt = blockIdx.x & 15;
  a.h = (blockIdx.x >> 4) & 3; a.b = blockIdx.x >> 6;
  a.wg = __shfl_sync(0xffffffff, (int)(threadIdx.x >> 7), 0);
  const int lane = threadIdx.x & 31, wq = (threadIdx.x >> 5) & 3;
  PROF_MARK(1, 0);
  if (threadIdx.x == 0) {
    prefetch_tmap(&tmQ); prefetch_tmap(&tmKV); prefetch_tmap(&tmO);
    for (int i = 0; i < NSTG; i++) { mbar_init(a.full + 8 * i, 1); mbar_init(a.empty + 8 * i, 4); }
    mbar_init(qbar, 1);
    asm volatile("fence.mbarrier_init.release.cluster;" ::: "memory");
    pdl_launch();
    pdl_wait();
    mbar_expect_tx(qbar, 32768);
    tma_load_3d(sQ, &tmQ, qbar, a.h * 64, qt * 256, a.b);
    for (int i = 0; i < NSTG; i++) att_load_stage(a, i);
  }
  __syncthreads();
  const uint32_t sQw = sQ + a.wg * 8192, dQ = dlo(sQw, 16);
  float O[32], l0, l1;
  PROF_MARK(1, 1);
  mbar_wait(qbar, 0);
  PROF_MARK(1, 2);
  att_pass<false>(a, dQ, O, l0, l1);
  PROF_MARK(1, 3);
  {
    float z = 0.f;
#pragma unroll
    for (int i = 0; i < 32; i++) z = fmaf(O[i], 0.f, z);
    const bool ok = (l0 >= 0x1p-80f) && (l0 <= 0x1p100f) && (l1 >= 0x1p-80f) && (l1 <= 0x1p100f) && (z == 0.f);
    if (__syncthreads_or(!ok)) {
      if (threadIdx.x == 0) {
        for (int i = 0; i < NSTG; i++) { mbar_inval(a.full + 8 * i); mbar_inval(a.empty + 8 * i); }
        for (int i = 0; i < NSTG; i++) { mbar_init(a.full + 8 * i, 1); mbar_init(a.empty + 8 * i, 4); }
        asm volatile("fence.mbarrier_init.release.cluster;" ::: "memory");
        fence_async_smem();
        for (int i = 0; i < NSTG; i++) att_load_stage(a, i);
      }
      __syncthreads();
      att_pass<true>(a, dQ, O, l0, l1);
    }
  }
  const float i0 = 1.f / l0, i1 = 1.f / l1;
  const int r = wq * 16 + (lane & 7) + ((lane >> 3) & 1) * 8;
#pragma unroll
  for (int j = 0; j < 4; j++) {
    const int ch = j * 2 + (lane >> 4);
    stsm_x4(sQw + r * 128 + ((ch ^ (r & 7)) << 4),
            pack_bf16(O[8 * j] * i0, O[8 * j + 1] * i0), pack_bf16(O[8 * j + 2] * i1, O[8 * j + 3] * i1),
            pack_bf16(O[8 * j + 4] * i0, O[8 * j + 5] * i0), pack_bf16(O[8 * j + 6] * i1, O[8 * j + 7] * i1));
  }
  fence_async_smem();
  bar_sync(1 + a.wg, 128);
  if ((threadIdx.x & 127) == 0) {
    tma_store_3d(&tmO, sQw, a.h * 64, qt * 256 + a.wg * 64, a.b);
    bulk_commit();
    PROF_MARK(1, 4);
    bulk_wait_all();
  }
  PROF_MARK(1, 5);
}

typedef CUresult (*EncodeFn)(CUtensorMap*, CUtensorMapDataType, cuuint32_t, void*, const cuuint64_t*, const cuuint64_t*, const cuuint32_t*,
                             const cuuint32_t*, CUtensorMapInterleave, CUtensorMapSwizzle, CUtensorMapL2promotion, CUtensorMapFloatOOBfill);

CUtensorMap make_map(EncodeFn enc, const void* p, uint64_t d0, uint64_t d1, uint64_t d2, uint64_t s1, uint64_t s2, uint32_t b1, uint32_t b2) {
  CUtensorMap tm;
  cuuint64_t dims[3] = {d0, d1, d2};
  cuuint64_t strides[2] = {s1, s2};
  cuuint32_t box[3] = {64, b1, b2};
  cuuint32_t es[3] = {1, 1, 1};
  enc(&tm, CU_TENSOR_MAP_DATA_TYPE_BFLOAT16, 3, const_cast<void*>(p), dims, strides, box, es, CU_TENSOR_MAP_INTERLEAVE_NONE,
      CU_TENSOR_MAP_SWIZZLE_128B, CU_TENSOR_MAP_L2_PROMOTION_L2_256B, CU_TENSOR_MAP_FLOAT_OOB_FILL_NONE);
  return tm;
}
CUtensorMap blk_map(EncodeFn enc, const void* p, uint64_t rows, uint64_t cols, uint32_t boxrows, uint32_t boxblks) {
  return make_map(enc, p, 64, rows, cols / 64, cols * 2, 128, boxrows, boxblks);
}
CUtensorMap seq_map(EncodeFn enc, const void* p, uint64_t cols, uint32_t boxrows) {
  return make_map(enc, p, cols, T_, 2, cols * 2, cols * 2 * T_, boxrows, 1);
}

}

extern "C" void kernel_launch(void* const* d_in, const int* in_sizes, int n_in, void* d_out, int out_size) {
  (void)in_sizes; (void)n_in; (void)out_size;
  const void *x = d_in[0], *w1a = d_in[1], *w1b = d_in[2], *wqkv = d_in[3], *wo = d_in[4], *pw1 = d_in[5], *dw = d_in[6], *pw2 = d_in[7],
             *w2a = d_in[8], *w2b = d_in[9];
  void* fn = nullptr;
  cudaDriverEntryPointQueryResult qr;
  cudaGetDriverEntryPoint("cuTensorMapEncodeTiled", &fn, cudaEnableDefault, &qr);
  EncodeFn enc = (EncodeFn)fn;
  void *x1, *qkv, *att;
  cudaGetSymbolAddress(&x1, g_x1);
  cudaGetSymbolAddress(&qkv, g_qkv);
  cudaGetSymbolAddress(&att, g_att);
  cudaFuncSetAttribute(k1_ff1_qkv, cudaFuncAttributeMaxDynamicSharedMemorySize, ROW_SMEM);
  cudaFuncSetAttribute(k2_attn, cudaFuncAttributeMaxDynamicSharedMemorySize, ATT_SMEM);
  cudaFuncSetAttribute(k3_tail, cudaFuncAttributeMaxDynamicSharedMemorySize, ROW_SMEM);

  Wptrs wp;
  const void* ws[8] = {w1a, w1b, wqkv, wo, pw1, pw2, w2a, w2b};
  const uint32_t wb[8] = {524288, 524288, 393216, 131072, 262144, 131072, 524288, 524288};
  for (int i = 0; i < 8; i++) { wp.p[i] = ws[i]; wp.bytes[i] = wb[i]; }

  cudaLaunchAttribute pdl[1];
  pdl[0].id = cudaLaunchAttributeProgrammaticStreamSerialization;
  pdl[0].val.programmaticStreamSerializationAllowed = 1;
  cudaLaunchConfig_t cfg = {};
  cfg.stream = cudaStreamPerThread;

  cfg.gridDim = dim3(NTILE); cfg.blockDim = dim3(384); cfg.dynamicSmemBytes = ROW_SMEM; cfg.attrs = nullptr; cfg.numAttrs = 0;
  cudaLaunchKernelEx(&cfg, k1_ff1_qkv, blk_map(enc, x, ROWS, 256, 64, 4), blk_map(enc, w1a, 256, 1024, 256, 1), blk_map(enc, w1b, 1024, 256, 64, 4),
                     blk_map(enc, wqkv, 256, 768, 128, 2), blk_map(enc, x1, ROWS, 256, 64, 2), blk_map(enc, qkv, ROWS, 768, 64, 2), wp);

  cfg.gridDim = dim3(128); cfg.blockDim = dim3(512); cfg.dynamicSmemBytes = ATT_SMEM; cfg.attrs = pdl; cfg.numAttrs = 1;
  cudaLaunchKernelEx(&cfg, k2_attn, seq_map(enc, qkv, 768, 256), seq_map(enc, qkv, 768, 160), seq_map(enc, att, 256, 64));

  cfg.gridDim = dim3(NTILE); cfg.blockDim = dim3(384); cfg.dynamicSmemBytes = ROW_SMEM;
  cudaLaunchKernelEx(&cfg, k3_tail, blk_map(enc, att, ROWS, 256, 64, 4), blk_map(enc, x1, ROWS, 256, 64, 4), blk_map(enc, wo, 256, 256, 128, 2),
                     make_map(enc, pw1, 256, 256, 2, 1024, 512, 128, 2), blk_map(enc, pw2, 256, 256, 128, 2), blk_map(enc, w2a, 256, 1024, 256, 1),
                     blk_map(enc, w2b, 1024, 256, 64, 4), blk_map(enc, d_out, ROWS, 256, 64, 2), (const uint4*)dw);
}
```

```cpp
#include <cuda_runtime.h>
#include <cuda_bf16.h>
#include <cuda.h>
#include <stdint.h>

namespace {

constexpr int T_ = 4000;
constexpr int ROWS = 8000;
constexpr int NTILE = 125;

__device__ __nv_bfloat16 g_x1[ROWS * 256];
__device__ __nv_bfloat16 g_qkv[ROWS * 768];
__device__ __nv_bfloat16 g_att[ROWS * 256];
__device__ uint4 g_halo[NTILE * 4 * 32];
__device__ uint32_t g_cnt1[2 * 32];
__device__ uint32_t g_cnt2[2 * 64];

#define PROF_MARK(k, i) do {} while (0)
#define PROF_STG(n, i) do {} while (0)

__device__ __forceinline__ uint32_t smem_u32(const void* p) { return (uint32_t)__cvta_generic_to_shared(p); }
__device__ __forceinline__ void mbar_init(uint32_t bar, uint32_t cnt) { asm volatile("mbarrier.init.shared::cta.b64 [%0], %1;" :: "r"(bar), "r"(cnt) : "memory"); }
__device__ __forceinline__ void mbar_inval(uint32_t bar) { asm volatile("mbarrier.inval.shared::cta.b64 [%0];" :: "r"(bar) : "memory"); }
__device__ __forceinline__ void mbar_expect_tx(uint32_t bar, uint32_t bytes) { asm volatile("mbarrier.arrive.expect_tx.shared::cta.b64 _, [%0], %1;" :: "r"(bar), "r"(bytes) : "memory"); }
__device__ __forceinline__ void mbar_arrive(uint32_t bar) { asm volatile("mbarrier.arrive.shared::cta.b64 _, [%0];" :: "r"(bar) : "memory"); }
__device__ __forceinline__ void mbar_wait(uint32_t bar, uint32_t parity) {
  asm volatile("{\n.reg .pred p;\n.reg .u32 n;\n"
               "mbarrier.try_wait.parity.shared::cta.b64 p, [%0], %1;\n@p bra DONE_%=;\nmov.u32 n, 0;\n"
               "LOOP_%=:\nmbarrier.try_wait.parity.shared::cta.b64 p, [%0], %1;\n@p bra DONE_%=;\n"
               "add.u32 n, n, 1;\nsetp.lt.u32 p, n, 4194304;\n@p bra LOOP_%=;\ntrap;\nDONE_%=:\n}\n" :: "r"(bar), "r"(parity) : "memory");
}
__device__ __forceinline__ void halo_poll(const uint4* p, uint4& v) {
  asm volatile("{\n.reg .pred p;\n.reg .u32 n, t;\nmov.u32 n, 0;\n"
               "LOOP_%=:\nld.relaxed.gpu.global.v4.u32 {%0,%1,%2,%3}, [%4];\n"
               "max.u32 t, %0, %1;\nmax.u32 t, t, %2;\nmax.u32 t, t, %3;\nsetp.ne.u32 p, t, 0xFFFFFFFF;\n@p bra DONE_%=;\n"
               "add.u32 n, n, 1;\nsetp.lt.u32 p, n, 16777216;\n@p bra LOOP_%=;\ntrap;\nDONE_%=:\n}\n"
               : "=&r"(v.x), "=&r"(v.y), "=&r"(v.z), "=&r"(v.w) : "l"(p) : "memory");
}
__device__ __forceinline__ void cnt_wait(const uint32_t* p, uint32_t target) {
  asm volatile("{\n.reg .pred p;\n.reg .u32 n, v;\nmov.u32 n, 0;\n"
               "LOOP_%=:\nld.acquire.gpu.global.u32 v, [%0];\nsetp.ge.u32 p, v, %1;\n@p bra DONE_%=;\n"
               "nanosleep.u32 20;\nadd.u32 n, n, 1;\nsetp.lt.u32 p, n, 16777216;\n@p bra LOOP_%=;\ntrap;\nDONE_%=:\n"
               "fence.proxy.async.global;\n}\n" :: "l"(p), "r"(target) : "memory");
}
__device__ __forceinline__ void cnt_signal(uint32_t* p) {
  asm volatile("fence.proxy.async.global;\nred.release.gpu.global.add.u32 [%0], 1;" :: "l"(p) : "memory");
}
__device__ __forceinline__ void tma_load_3d(uint32_t dst, const CUtensorMap* tm, uint32_t bar, int c0, int c1, int c2) {
  asm volatile("cp.async.bulk.tensor.3d.shared::cluster.global.mbarrier::complete_tx::bytes [%0], [%1, {%3, %4, %5}], [%2];"
    :: "r"(dst), "l"(tm), "r"(bar), "r"(c0), "r"(c1), "r"(c2) : "memory");
}
__device__ __forceinline__ void tma_store_3d(const CUtensorMap* tm, uint32_t src, int c0, int c1, int c2) {
  asm volatile("cp.async.bulk.tensor.3d.global.shared::cta.bulk_group [%0, {%2, %3, %4}], [%1];" :: "l"(tm), "r"(src), "r"(c0), "r"(c1), "r"(c2) : "memory");
}
__device__ __forceinline__ void bulk_commit() { asm volatile("cp.async.bulk.commit_group;" ::: "memory"); }
__device__ __forceinline__ void bulk_wait_read() { asm volatile("cp.async.bulk.wait_group.read 0;" ::: "memory"); }
__device__ __forceinline__ void bulk_wait_all() { asm volatile("cp.async.bulk.wait_group 0;" ::: "memory"); }
__device__ __forceinline__ void l2_prefetch(const void* p, uint32_t bytes) { asm volatile("cp.async.bulk.prefetch.L2.global [%0], %1;" :: "l"(p), "r"(bytes) : "memory"); }
__device__ __forceinline__ void prefetch_tmap(const CUtensorMap* tm) { asm volatile("prefetch.tensormap [%0];" :: "l"(tm) : "memory"); }
__device__ __forceinline__ void fence_async_smem() { asm volatile("fence.proxy.async.shared::cta;" ::: "memory"); }
__device__ __forceinline__ void wg_fence() { asm volatile("wgmma.fence.sync.aligned;" ::: "memory"); }
__device__ __forceinline__ void wg_commit() { asm volatile("wgmma.commit_group.sync.aligned;" ::: "memory"); }
template<int N> __device__ __forceinline__ void wg_wait() { asm volatile("wgmma.wait_group.sync.aligned %0;" :: "n"(N) : "memory"); }
__device__ __forceinline__ void bar_sync(int id, int n) { asm volatile("bar.sync %0, %1;" :: "r"(id), "r"(n) : "memory"); }
__device__ __forceinline__ void bar_arrive(int id, int n) { asm volatile("bar.arrive %0, %1;" :: "r"(id), "r"(n) : "memory"); }
__device__ __forceinline__ void pdl_wait() { asm volatile("griddepcontrol.wait;" ::: "memory"); }
__device__ __forceinline__ void pdl_launch() { asm volatile("griddepcontrol.launch_dependents;" ::: "memory"); }
__device__ __forceinline__ float ex2(float x) { float y; asm("ex2.approx.ftz.f32 %0, %1;" : "=f"(y) : "f"(x)); return y; }
__device__ __forceinline__ float tanh_fast(float x) { float y; asm("tanh.approx.f32 %0, %1;" : "=f"(y) : "f"(x)); return y; }
__device__ __forceinline__ uint32_t pack_bf16(float lo, float hi) { uint32_t r; asm("cvt.rn.bf16x2.f32 %0, %1, %2;" : "=r"(r) : "f"(hi), "f"(lo)); return r; }
__device__ __forceinline__ uint32_t bmul2(uint32_t a, uint32_t b) { uint32_t d; asm("mul.rn.bf16x2 %0, %1, %2;" : "=r"(d) : "r"(a), "r"(b)); return d; }
__device__ __forceinline__ uint32_t bfma2(uint32_t a, uint32_t b, uint32_t c) { uint32_t d; asm("fma.rn.bf16x2 %0, %1, %2, %3;" : "=r"(d) : "r"(a), "r"(b), "r"(c)); return d; }
__device__ __forceinline__ float bf_lo(uint32_t u) { return __uint_as_float(u << 16); }
__device__ __forceinline__ float bf_hi(uint32_t u) { return __uint_as_float(u & 0xffff0000u); }
__device__ __forceinline__ void ldsm_x4(uint32_t addr, uint32_t& r0, uint32_t& r1, uint32_t& r2, uint32_t& r3) {
  asm volatile("ldmatrix.sync.aligned.m8n8.x4.shared.b16 {%0,%1,%2,%3}, [%4];" : "=r"(r0), "=r"(r1), "=r"(r2), "=r"(r3) : "r"(addr) : "memory");
}
__device__ __forceinline__ void stsm_x4(uint32_t addr, uint32_t r0, uint32_t r1, uint32_t r2, uint32_t r3) {
  asm volatile("stmatrix.sync.aligned.m8n8.x4.shared.b16 [%0], {%1,%2,%3,%4};" :: "r"(addr), "r"(r0), "r"(r1), "r"(r2), "r"(r3) : "memory");
}
__device__ __forceinline__ void sts128(uint32_t addr, uint4 v) { asm volatile("st.shared.v4.b32 [%0], {%1,%2,%3,%4};" :: "r"(addr), "r"(v.x), "r"(v.y), "r"(v.z), "r"(v.w) : "memory"); }
__device__ __forceinline__ uint4 lds128(uint32_t addr) { uint4 v; asm volatile("ld.shared.v4.b32 {%0,%1,%2,%3}, [%4];" : "=r"(v.x), "=r"(v.y), "=r"(v.z), "=r"(v.w) : "r"(addr) : "memory"); return v; }
__device__ __forceinline__ void sts64f(uint32_t addr, float a, float b) { asm volatile("st.shared.v2.f32 [%0], {%1,%2};" :: "r"(addr), "f"(a), "f"(b) : "memory"); }
__device__ __forceinline__ float2 lds64f(uint32_t addr) { float2 v; asm volatile("ld.shared.v2.f32 {%0,%1}, [%2];" : "=f"(v.x), "=f"(v.y) : "r"(addr) : "memory"); return v; }
__device__ __forceinline__ uint32_t dlo(uint32_t addr, uint32_t lbo) { return ((addr & 0x3FFFF) >> 4) | ((lbo >> 4) << 16); }

template<int SD> __device__ __forceinline__ void wg_ss_n128_tb1(float (&d)[64], uint32_t da, uint32_t db) {
  asm volatile("{\n.reg .b64 da, db;\nmov.b64 da, {%64, 0x40000040};\nmov.b64 db, {%65, 0x40000040};\n"
    "wgmma.mma_async.sync.aligned.m64n128k16.f32.bf16.bf16 {%0, %1, %2, %3, %4, %5, %6, %7, %8, %9, %10, %11, %12, %13, %14, %15, %16, %17, %18, %19, %20, %21, %22, %23, %24, %25, %26, %27, %28, %29, %30, %31, %32, %33, %34, %35, %36, %37, %38, %39, %40, %41, %42, %43, %44, %45, %46, %47, %48, %49, %50, %51, %52, %53, %54, %55, %56, %57, %58, %59, %60, %61, %62, %63}, da, db, %66, 1, 1, 0, 1;\n}\n"
    : "+f"(d[0]), "+f"(d[1]), "+f"(d[2]), "+f"(d[3]), "+f"(d[4]), "+f"(d[5]), "+f"(d[6]), "+f"(d[7]), "+f"(d[8]), "+f"(d[9]), "+f"(d[10]), "+f"(d[11]), "+f"(d[12]), "+f"(d[13]), "+f"(d[14]), "+f"(d[15]), "+f"(d[16]), "+f"(d[17]), "+f"(d[18]), "+f"(d[19]), "+f"(d[20]), "+f"(d[21]), "+f"(d[22]), "+f"(d[23]), "+f"(d[24]), "+f"(d[25]), "+f"(d[26]), "+f"(d[27]), "+f"(d[28]), "+f"(d[29]), "+f"(d[30]), "+f"(d[31]), "+f"(d[32]), "+f"(d[33]), "+f"(d[34]), "+f"(d[35]), "+f"(d[36]), "+f"(d[37]), "+f"(d[38]), "+f"(d[39]), "+f"(d[40]), "+f"(d[41]), "+f"(d[42]), "+f"(d[43]), "+f"(d[44]), "+f"(d[45]), "+f"(d[46]), "+f"(d[47]), "+f"(d[48]), "+f"(d[49]), "+f"(d[50]), "+f"(d[51]), "+f"(d[52]), "+f"(d[53]), "+f"(d[54]), "+f"(d[55]), "+f"(d[56]), "+f"(d[57]), "+f"(d[58]), "+f"(d[59]), "+f"(d[60]), "+f"(d[61]), "+f"(d[62]), "+f"(d[63])
    : "r"(da), "r"(db), "n"(SD));
}
template<int SD> __device__ __forceinline__ void wg_rs_n128_tb1(float (&d)[64], uint32_t a0, uint32_t a1, uint32_t a2, uint32_t a3, uint32_t db) {
  asm volatile("{\n.reg .b64 db;\nmov.b64 db, {%68, 0x40000040};\n"
    "wgmma.mma_async.sync.aligned.m64n128k16.f32.bf16.bf16 {%0, %1, %2, %3, %4, %5, %6, %7, %8, %9, %10, %11, %12, %13, %14, %15, %16, %17, %18, %19, %20, %21, %22, %23, %24, %25, %26, %27, %28, %29, %30, %31, %32, %33, %34, %35, %36, %37, %38, %39, %40, %41, %42, %43, %44, %45, %46, %47, %48, %49, %50, %51, %52, %53, %54, %55, %56, %57, %58, %59, %60, %61, %62, %63}, {%64, %65, %66, %67}, db, %69, 1, 1, 1;\n}\n"
    : "+f"(d[0]), "+f"(d[1]), "+f"(d[2]), "+f"(d[3]), "+f"(d[4]), "+f"(d[5]), "+f"(d[6]), "+f"(d[7]), "+f"(d[8]), "+f"(d[9]), "+f"(d[10]), "+f"(d[11]), "+f"(d[12]), "+f"(d[13]), "+f"(d[14]), "+f"(d[15]), "+f"(d[16]), "+f"(d[17]), "+f"(d[18]), "+f"(d[19]), "+f"(d[20]), "+f"(d[21]), "+f"(d[22]), "+f"(d[23]), "+f"(d[24]), "+f"(d[25]), "+f"(d[26]), "+f"(d[27]), "+f"(d[28]), "+f"(d[29]), "+f"(d[30]), "+f"(d[31]), "+f"(d[32]), "+f"(d[33]), "+f"(d[34]), "+f"(d[35]), "+f"(d[36]), "+f"(d[37]), "+f"(d[38]), "+f"(d[39]), "+f"(d[40]), "+f"(d[41]), "+f"(d[42]), "+f"(d[43]), "+f"(d[44]), "+f"(d[45]), "+f"(d[46]), "+f"(d[47]), "+f"(d[48]), "+f"(d[49]), "+f"(d[50]), "+f"(d[51]), "+f"(d[52]), "+f"(d[53]), "+f"(d[54]), "+f"(d[55]), "+f"(d[56]), "+f"(d[57]), "+f"(d[58]), "+f"(d[59]), "+f"(d[60]), "+f"(d[61]), "+f"(d[62]), "+f"(d[63])
    : "r"(a0), "r"(a1), "r"(a2), "r"(a3), "r"(db), "n"(SD));
}
template<int SD> __device__ __forceinline__ void wg_ss_n64_tb1(float (&d)[32], uint32_t da, uint32_t db) {
  asm volatile("{\n.reg .b64 da, db;\nmov.b64 da, {%32, 0x40000040};\nmov.b64 db, {%33, 0x40000040};\n"
    "wgmma.mma_async.sync.aligned.m64n64k16.f32.bf16.bf16 {%0, %1, %2, %3, %4, %5, %6, %7, %8, %9, %10, %11, %12, %13, %14, %15, %16, %17, %18, %19, %20, %21, %22, %23, %24, %25, %26, %27, %28, %29, %30, %31}, da, db, %34, 1, 1, 0, 1;\n}\n"
    : "+f"(d[0]), "+f"(d[1]), "+f"(d[2]), "+f"(d[3]), "+f"(d[4]), "+f"(d[5]), "+f"(d[6]), "+f"(d[7]), "+f"(d[8]), "+f"(d[9]), "+f"(d[10]), "+f"(d[11]), "+f"(d[12]), "+f"(d[13]), "+f"(d[14]), "+f"(d[15]), "+f"(d[16]), "+f"(d[17]), "+f"(d[18]), "+f"(d[19]), "+f"(d[20]), "+f"(d[21]), "+f"(d[22]), "+f"(d[23]), "+f"(d[24]), "+f"(d[25]), "+f"(d[26]), "+f"(d[27]), "+f"(d[28]), "+f"(d[29]), "+f"(d[30]), "+f"(d[31])
    : "r"(da), "r"(db), "n"(SD));
}
template<int SD> __device__ __forceinline__ void wg_ss_n80_tb0(float (&d)[40], uint32_t da, uint32_t db) {
  asm volatile("{\n.reg .b64 da, db;\nmov.b64 da, {%40, 0x40000040};\nmov.b64 db, {%41, 0x40000040};\n"
    "wgmma.mma_async.sync.aligned.m64n80k16.f32.bf16.bf16 {%0, %1, %2, %3, %4, %5, %6, %7, %8, %9, %10, %11, %12, %13, %14, %15, %16, %17, %18, %19, %20, %21, %22, %23, %24, %25, %26, %27, %28, %29, %30, %31, %32, %33, %34, %35, %36, %37, %38, %39}, da, db, %42, 1, 1, 0, 0;\n}\n"
    : "+f"(d[0]), "+f"(d[1]), "+f"(d[2]), "+f"(d[3]), "+f"(d[4]), "+f"(d[5]), "+f"(d[6]), "+f"(d[7]), "+f"(d[8]), "+f"(d[9]), "+f"(d[10]), "+f"(d[11]), "+f"(d[12]), "+f"(d[13]), "+f"(d[14]), "+f"(d[15]), "+f"(d[16]), "+f"(d[17]), "+f"(d[18]), "+f"(d[19]), "+f"(d[20]), "+f"(d[21]), "+f"(d[22]), "+f"(d[23]), "+f"(d[24]), "+f"(d[25]), "+f"(d[26]), "+f"(d[27]), "+f"(d[28]), "+f"(d[29]), "+f"(d[30]), "+f"(d[31]), "+f"(d[32]), "+f"(d[33]), "+f"(d[34]), "+f"(d[35]), "+f"(d[36]), "+f"(d[37]), "+f"(d[38]), "+f"(d[39])
    : "r"(da), "r"(db), "n"(SD));
}
template<int SD> __device__ __forceinline__ void wg_rs_n64_tb1(float (&d)[32], uint32_t a0, uint32_t a1, uint32_t a2, uint32_t a3, uint32_t db) {
  asm volatile("{\n.reg .b64 db;\nmov.b64 db, {%36, 0x40000040};\n"
    "wgmma.mma_async.sync.aligned.m64n64k16.f32.bf16.bf16 {%0, %1, %2, %3, %4, %5, %6, %7, %8, %9, %10, %11, %12, %13, %14, %15, %16, %17, %18, %19, %20, %21, %22, %23, %24, %25, %26, %27, %28, %29, %30, %31}, {%32, %33, %34, %35}, db, %37, 1, 1, 1;\n}\n"
    : "+f"(d[0]), "+f"(d[1]), "+f"(d[2]), "+f"(d[3]), "+f"(d[4]), "+f"(d[5]), "+f"(d[6]), "+f"(d[7]), "+f"(d[8]), "+f"(d[9]), "+f"(d[10]), "+f"(d[11]), "+f"(d[12]), "+f"(d[13]), "+f"(d[14]), "+f"(d[15]), "+f"(d[16]), "+f"(d[17]), "+f"(d[18]), "+f"(d[19]), "+f"(d[20]), "+f"(d[21]), "+f"(d[22]), "+f"(d[23]), "+f"(d[24]), "+f"(d[25]), "+f"(d[26]), "+f"(d[27]), "+f"(d[28]), "+f"(d[29]), "+f"(d[30]), "+f"(d[31])
    : "r"(a0), "r"(a1), "r"(a2), "r"(a3), "r"(db), "n"(SD));
}

constexpr int RING = 5;
constexpr uint32_t STAGE = 32768;
constexpr uint32_t OFF_X = 32768, OFF_W = 65536, OFF_MISC = OFF_W + RING * STAGE;
constexpr int ROW_SMEM = OFF_MISC + 256 + 1024 + 1024;

struct Ctx {
  uint32_t sA, sX, sW, full, empty, stats;
  uint32_t frag;
  uint32_t rsw;
  uint32_t hi;
  int wg, tid, lane;
  int pk;
};
__device__ __forceinline__ uint32_t stage_wait(const Ctx& c, int n) {
  const int q = n / RING, s = n - q * RING;
  if (c.tid == 0) PROF_STG(n + c.pk, 1);
  mbar_wait(c.full + 8 * s, q & 1);
  if (c.tid == 0) PROF_STG(n + c.pk, 2);
  return dlo(c.sW + s * STAGE, 0);
}
__device__ __forceinline__ void stage_release(const Ctx& c, int n) {
  const int s = n % RING;
  if (c.tid == 0) { mbar_arrive(c.empty + 8 * s); PROF_STG(n + c.pk, 3); }
}
__device__ __forceinline__ void turn_begin(const Ctx& c) { bar_sync(5 + c.wg, 256); }
__device__ __forceinline__ void turn_end(const Ctx& c) { bar_arrive(5 + (c.wg ^ 1), 256); }
template<int FIRST> __device__ __forceinline__ void piece_ss(float (&acc)[64], uint32_t dA, uint32_t dB) {
  dB += (16384 >> 4) << 16;
  wg_ss_n128_tb1<FIRST ? 0 : 1>(acc, dA, dB);
#pragma unroll
  for (int kk = 1; kk < 8; kk++) wg_ss_n128_tb1<1>(acc, dA + (kk >> 2) * 512 + (kk & 3) * 2, dB + kk * 128);
}
__device__ __forceinline__ void ff_g1(float (&h)[32], uint32_t dA, uint32_t dB) {
  wg_ss_n64_tb1<0>(h, dA, dB);
#pragma unroll
  for (int kk = 1; kk < 16; kk++) wg_ss_n64_tb1<1>(h, dA + (kk >> 2) * 512 + (kk & 3) * 2, dB + kk * 128);
}
__device__ __forceinline__ void ff_g2(float (&acc)[64], const uint32_t (&P)[16], uint32_t dB, int half) {
  dB += ((8192 >> 4) << 16) + half * 1024;
#pragma unroll
  for (int kk = 0; kk < 4; kk++) wg_rs_n128_tb1<1>(acc, P[4 * kk], P[4 * kk + 1], P[4 * kk + 2], P[4 * kk + 3], dB + kk * 128);
}
template<int FIRST> __device__ __forceinline__ void gemm256(const Ctx& c, float (&acc)[64], int n) {
  const uint32_t dA = dlo(c.sA, 16);
  uint32_t b = stage_wait(c, n);
  turn_begin(c);
  wg_fence(); piece_ss<FIRST>(acc, dA, b); wg_commit();
  b = stage_wait(c, n + 1);
  wg_fence(); piece_ss<0>(acc, dA + 1024, b); wg_commit();
  turn_end(c);
  wg_wait<1>(); stage_release(c, n);
  wg_wait<0>(); stage_release(c, n + 1);
}
__device__ __forceinline__ uint32_t frag_addr(const Ctx& c, uint32_t tile, int j) {
  return tile + (2 * c.wg + (j >> 2)) * 8192 + c.frag + ((((j & 3) * 2 + c.hi) ^ c.rsw) << 4);
}
__device__ __forceinline__ void load_half(const Ctx& c, uint32_t tile, float (&v)[64]) {
#pragma unroll
  for (int j = 0; j < 8; j++) {
    uint32_t r0, r1, r2, r3;
    ldsm_x4(frag_addr(c, tile, j), r0, r1, r2, r3);
    v[8 * j] = bf_lo(r0); v[8 * j + 1] = bf_hi(r0); v[8 * j + 2] = bf_lo(r1); v[8 * j + 3] = bf_hi(r1);
    v[8 * j + 4] = bf_lo(r2); v[8 * j + 5] = bf_hi(r2); v[8 * j + 6] = bf_lo(r3); v[8 * j + 7] = bf_hi(r3);
  }
}
__device__ __forceinline__ void store_half(const Ctx& c, uint32_t tile, const float (&v)[64], float a0, float b0, float a1, float b1) {
#pragma unroll
  for (int j = 0; j < 8; j++)
    stsm_x4(frag_addr(c, tile, j),
            pack_bf16(fmaf(v[8 * j], a0, b0), fmaf(v[8 * j + 1], a0, b0)), pack_bf16(fmaf(v[8 * j + 2], a1, b1), fmaf(v[8 * j + 3], a1, b1)),
            pack_bf16(fmaf(v[8 * j + 4], a0, b0), fmaf(v[8 * j + 5], a0, b0)), pack_bf16(fmaf(v[8 * j + 6], a1, b1), fmaf(v[8 * j + 7], a1, b1)));
}
__device__ __forceinline__ void store_half_raw(const Ctx& c, uint32_t tile, const float (&v)[64]) {
#pragma unroll
  for (int j = 0; j < 8; j++)
    stsm_x4(frag_addr(c, tile, j), pack_bf16(v[8 * j], v[8 * j + 1]), pack_bf16(v[8 * j + 2], v[8 * j + 3]),
            pack_bf16(v[8 * j + 4], v[8 * j + 5]), pack_bf16(v[8 * j + 6], v[8 * j + 7]));
}
__device__ __forceinline__ void ln_stats(const Ctx& c, const float (&v)[64], float scale, float& a0, float& b0, float& a1, float& b1) {
  float s0 = 0.f, s1 = 0.f, q0 = 0.f, q1 = 0.f, s2 = 0.f, s3 = 0.f, q2 = 0.f, q3 = 0.f;
#pragma unroll
  for (int i = 0; i < 16; i++) {
    s0 += v[4 * i]; q0 = fmaf(v[4 * i], v[4 * i], q0);
    s2 += v[4 * i + 1]; q2 = fmaf(v[4 * i + 1], v[4 * i + 1], q2);
    s1 += v[4 * i + 2]; q1 = fmaf(v[4 * i + 2], v[4 * i + 2], q1);
    s3 += v[4 * i + 3]; q3 = fmaf(v[4 * i + 3], v[4 * i + 3], q3);
  }
  s0 += s2; q0 += q2; s1 += s3; q1 += q3;
  s0 += __shfl_xor_sync(0xffffffff, s0, 1); q0 += __shfl_xor_sync(0xffffffff, q0, 1);
  s1 += __shfl_xor_sync(0xffffffff, s1, 1); q1 += __shfl_xor_sync(0xffffffff, q1, 1);
  s0 += __shfl_xor_sync(0xffffffff, s0, 2); q0 += __shfl_xor_sync(0xffffffff, q0, 2);
  s1 += __shfl_xor_sync(0xffffffff, s1, 2); q1 += __shfl_xor_sync(0xffffffff, q1, 2);
  const uint32_t row = (c.tid >> 5) * 16 + (c.lane >> 2);
  if ((c.lane & 3) == 0) {
    sts64f(c.stats + c.wg * 512 + row * 8, s0, q0);
    sts64f(c.stats + c.wg * 512 + (row + 8) * 8, s1, q1);
  }
  bar_sync(1, 256);
  const float2 o0 = lds64f(c.stats + (c.wg ^ 1) * 512 + row * 8), o1 = lds64f(c.stats + (c.wg ^ 1) * 512 + (row + 8) * 8);
  const float m0 = (s0 + o0.x) * (1.f / 256.f), m1 = (s1 + o1.x) * (1.f / 256.f);
  const float var0 = fmaxf(fmaf(-m0, m0, (q0 + o0.y) * (1.f / 256.f)), 0.f), var1 = fmaxf(fmaf(-m1, m1, (q1 + o1.y) * (1.f / 256.f)), 0.f);
  a0 = rsqrtf(var0 + 1e-5f) * scale; a1 = rsqrtf(var1 + 1e-5f) * scale;
  b0 = -m0 * a0; b1 = -m1 * a1;
}
__device__ __forceinline__ float silu_half(float h) { return fmaf(h, tanh_fast(h), h); }
__device__ __forceinline__ float silu_quarter(float h) { const float q = 0.5f * h; return fmaf(q, tanh_fast(h), q); }
__device__ __forceinline__ void silu_pack(const float (&acc)[32], uint32_t (&P)[16]) {
#pragma unroll
  for (int i = 0; i < 16; i++) P[i] = pack_bf16(silu_quarter(acc[2 * i]), silu_quarter(acc[2 * i + 1]));
}
__device__ __forceinline__ void ff_block(const Ctx& c, int n0, float (&own)[64]) {
  float oth[64], h[32];
  uint32_t P[16];
#pragma unroll
  for (int i = 0; i < 64; i++) oth[i] = 0.f;
  const uint32_t dA = dlo(c.sA, 16);
  {
    const uint32_t b = stage_wait(c, n0 + c.wg);
    turn_begin(c);
    wg_fence(); ff_g1(h, dA, b); wg_commit();
    turn_end(c);
    wg_wait<0>(); stage_release(c, n0 + c.wg);
    silu_pack(h, P);
  }
#pragma unroll 1
  for (int it = 1; it < 8; it++) {
    const int n = n0 + 4 * it - 2 + 2 * c.wg;
    uint32_t b = stage_wait(c, n);
    turn_begin(c);
    wg_fence(); ff_g2(own, P, b, c.wg); ff_g2(oth, P, b, c.wg ^ 1); wg_commit();
    b = stage_wait(c, n + 1);
    wg_fence(); ff_g1(h, dA, b); wg_commit();
    turn_end(c);
    wg_wait<1>(); stage_release(c, n);
    wg_wait<0>(); stage_release(c, n + 1);
    silu_pack(h, P);
  }
  if (c.wg == 0) bar_arrive(2, 256);
  {
    const int n = n0 + 30 + c.wg;
    const uint32_t b = stage_wait(c, n);
    turn_begin(c);
    wg_fence(); ff_g2(oth, P, b, c.wg ^ 1); wg_commit();
    ff_g2(own, P, b, c.wg); wg_commit();
    turn_end(c);
    wg_wait<1>();
    if (c.wg == 1) bar_sync(2, 256);
    const uint32_t e = (c.wg == 0 ? c.sX : c.sA) + c.tid * 16;
#pragma unroll
    for (int i = 0; i < 16; i++)
      sts128(e + i * 2048, make_uint4(__float_as_uint(oth[4 * i]), __float_as_uint(oth[4 * i + 1]), __float_as_uint(oth[4 * i + 2]), __float_as_uint(oth[4 * i + 3])));
    wg_wait<0>(); stage_release(c, n);
  }
  bar_sync(1, 256);
  const uint32_t e = (c.wg == 0 ? c.sA : c.sX) + c.tid * 16;
#pragma unroll
  for (int i = 0; i < 16; i++) {
    const uint4 u = lds128(e + i * 2048);
    own[4 * i] += __uint_as_float(u.x); own[4 * i + 1] += __uint_as_float(u.y);
    own[4 * i + 2] += __uint_as_float(u.z); own[4 * i + 3] += __uint_as_float(u.w);
  }
}
__device__ __forceinline__ void produce(uint32_t sW, uint32_t full, uint32_t empty, int n, const CUtensorMap* tm, int k0, int nblk, int c0 = 0) {
  const int q = n / RING, s = n - q * RING;
  mbar_wait(empty + 8 * s, (q & 1) ^ 1);
  PROF_STG(n + ((sW & 1) ? 132 * 64 : 0), 0);
  sW &= ~1u;
  mbar_expect_tx(full + 8 * s, STAGE);
  tma_load_3d(sW + s * STAGE, tm, full + 8 * s, c0, k0, nblk);
}
__device__ __forceinline__ void produce_ff(uint32_t sW, uint32_t full, uint32_t empty, int n0, const CUtensorMap* tmA, const CUtensorMap* tmB) {
#pragma unroll 1
  for (int m = 0; m < 32; m++) {
    int is2, j;
    if (m < 2) { is2 = 0; j = m; }
    else if (m == 31) { is2 = 1; j = 15; }
    else { const int q = m - 2; is2 = !(q & 1); j = (q >> 1) + (is2 ? 0 : 2); }
    if (is2) produce(sW, full, empty, n0 + m, tmB, 64 * j, 0);
    else produce(sW, full, empty, n0 + m, tmA, 0, j);
  }
}
__device__ __forceinline__ Ctx make_ctx(uint32_t base, int pk = 0) {
  Ctx c; c.pk = pk;
  c.sA = base; c.sX = base + OFF_X; c.sW = base + OFF_W;
  c.full = base + OFF_MISC; c.empty = c.full + 8 * RING; c.stats = base + OFF_MISC + 256;
  c.wg = __shfl_sync(0xffffffff, (int)(threadIdx.x >> 7), 0);
  c.tid = threadIdx.x & 127; c.lane = threadIdx.x & 31;
  const uint32_t r = (c.tid >> 5) * 16 + (c.lane & 7) + ((c.lane >> 3) & 1) * 8;
  c.frag = r * 128; c.rsw = r & 7; c.hi = c.lane >> 4;
  return c;
}
__device__ __forceinline__ void row_init(uint32_t base) {
  if (threadIdx.x == 0) {
    const uint32_t full = base + OFF_MISC;
    for (int i = 0; i < RING; i++) { mbar_init(full + 8 * i, 1); mbar_init(full + 8 * RING + 8 * i, 1); }
    mbar_init(full + 16 * RING, 1);
    mbar_init(full + 16 * RING + 8, 1);
    asm volatile("fence.mbarrier_init.release.cluster;" ::: "memory");
  }
  __syncthreads();
}
struct Wptrs { const void* p[8]; uint32_t bytes[8]; };

__global__ void __launch_bounds__(384, 1) k1_ff1_qkv(const __grid_constant__ CUtensorMap tmX, const __grid_constant__ CUtensorMap tmW1a,
    const __grid_constant__ CUtensorMap tmW1b, const __grid_constant__ CUtensorMap tmWqkv, const __grid_constant__ CUtensorMap tmX1st,
    const __grid_constant__ CUtensorMap tmQKVst, const __grid_constant__ Wptrs wp) {
  extern __shared__ uint8_t smem_raw[];
  const uint32_t base = (smem_u32(smem_raw) + 1023) & ~1023u;
  const int tile = blockIdx.x;
  if (threadIdx.x == 256) { prefetch_tmap(&tmX); prefetch_tmap(&tmW1a); prefetch_tmap(&tmW1b); prefetch_tmap(&tmWqkv); prefetch_tmap(&tmX1st); prefetch_tmap(&tmQKVst); }
  if (threadIdx.x >= 128 && threadIdx.x < 256) g_halo[tile * 128 + threadIdx.x - 128] = make_uint4(~0u, ~0u, ~0u, ~0u);
  if (tile == 0 && threadIdx.x >= 256) g_cnt2[threadIdx.x - 256] = 0;
  row_init(base);
  pdl_launch();
  if (threadIdx.x >= 256) {
    asm volatile("setmaxnreg.dec.sync.aligned.u32 24;");
    const uint32_t sW = base + OFF_W, full = base + OFF_MISC, empty = full + 8 * RING, inbar = full + 16 * RING;
    if (threadIdx.x == 256) {
      mbar_expect_tx(inbar, 32768);
      tma_load_3d(base + OFF_X, &tmX, inbar, 0, tile * 64, 0);
      produce_ff(sW, full, empty, 0, &tmW1a, &tmW1b);
#pragma unroll 1
      for (int m = 0; m < 12; m++) produce(sW, full, empty, 32 + m, &tmWqkv, 128 * (m & 1), 2 * (m >> 1));
    } else if (threadIdx.x >= 288 && threadIdx.x < 296) {
      const int w = threadIdx.x - 288;
      mbar_wait(inbar, 0);
      const uint32_t bytes = wp.bytes[w], per = ((bytes / NTILE) + 127) & ~127u, off = per * tile;
      if (off < bytes) l2_prefetch((const uint8_t*)wp.p[w] + off, min(per, bytes - off));
    }
  } else {
    asm volatile("setmaxnreg.inc.sync.aligned.u32 240;");
    const Ctx c = make_ctx(base);
    if (c.wg == 1) turn_end(c);
    float own[64];
    float a0, b0, a1, b1;
    PROF_MARK(0, 0);
    mbar_wait(c.full + 16 * RING, 0);
    PROF_MARK(0, 1);
    load_half(c, c.sX, own);
    ln_stats(c, own, 0.5f, a0, b0, a1, b1);
    store_half(c, c.sA, own, a0, b0, a1, b1);
    fence_async_smem();
    bar_sync(1, 256);
    PROF_MARK(0, 2);
    ff_block(c, 0, own);
    PROF_MARK(0, 3);
    ln_stats(c, own, 1.f, a0, b0, a1, b1);
    store_half(c, c.sA, own, a0, b0, a1, b1);
    store_half_raw(c, c.sX, own);
    fence_async_smem();
    bar_sync(1, 256);
    PROF_MARK(0, 4);
    if (c.tid == 0) { tma_store_3d(&tmX1st, c.sX + c.wg * 16384, 0, tile * 64, 2 * c.wg); bulk_commit(); }
#pragma unroll 1
    for (int cc = 0; cc < 3; cc++) {
      const int j = 2 * cc + c.wg;
      gemm256<1>(c, own, 32 + 2 * j);
      const float sc = (cc == 0) ? 0.125f * 1.4426950408889634f : 1.f;
      if (c.tid == 0) bulk_wait_read();
      bar_sync(3 + c.wg, 128);
      store_half(c, c.sX, own, sc, 0.f, sc, 0.f);
      fence_async_smem();
      bar_sync(3 + c.wg, 128);
      if (c.tid == 0) { tma_store_3d(&tmQKVst, c.sX + c.wg * 16384, 0, tile * 64, 2 * j); bulk_commit(); }
    }
    PROF_MARK(0, 5);
    if (c.tid == 0) {
      bulk_wait_all();
      if (tile <= 62) cnt_signal(g_cnt1);
      if (tile >= 62) cnt_signal(g_cnt1 + 32);
    }
    PROF_MARK(0, 6);
  }
}

__global__ void __launch_bounds__(384, 1) k3_tail(const __grid_constant__ CUtensorMap tmAtt, const __grid_constant__ CUtensorMap tmX1,
    const __grid_constant__ CUtensorMap tmWo, const __grid_constant__ CUtensorMap tmPw1, const __grid_constant__ CUtensorMap tmPw2,
    const __grid_constant__ CUtensorMap tmW2a, const __grid_constant__ CUtensorMap tmW2b, const __grid_constant__ CUtensorMap tmOut,
    const uint4* __restrict__ dw) {
  extern __shared__ uint8_t smem_raw[];
  const uint32_t base = (smem_u32(smem_raw) + 1023) & ~1023u;
  const int tile = blockIdx.x;
  if (threadIdx.x == 256) {
    prefetch_tmap(&tmWo); prefetch_tmap(&tmAtt); prefetch_tmap(&tmX1); prefetch_tmap(&tmPw1); prefetch_tmap(&tmPw2);
    prefetch_tmap(&tmW2a); prefetch_tmap(&tmW2b); prefetch_tmap(&tmOut);
  }
  row_init(base);
  if (threadIdx.x >= 256) {
    asm volatile("setmaxnreg.dec.sync.aligned.u32 24;");
    const uint32_t sW = (base + OFF_W) | 1, full = base + OFF_MISC, empty = full + 8 * RING, inbar = full + 16 * RING;
    if (threadIdx.x == 256) {
#pragma unroll 1
      for (int m = 0; m < 4; m++) produce(sW, full, empty, m, &tmWo, 128 * (m & 1), 2 * (m >> 1));
#pragma unroll 1
      for (int m = 0; m < 8; m++) produce(sW, full, empty, 4 + m, &tmPw1, 128 * (m & 1), 0, 64 * (2 * ((m >> 1) & 1) + (m >> 2)));
#pragma unroll 1
      for (int m = 0; m < 4; m++) produce(sW, full, empty, 12 + m, &tmPw2, 128 * (m & 1), 2 * (m >> 1));
      produce_ff(sW, full, empty, 16, &tmW2a, &tmW2b);
    } else if (threadIdx.x == 288) {
      mbar_expect_tx(inbar, 32768);
      tma_load_3d(base + OFF_X, &tmX1, inbar, 0, tile * 64, 0);
      if (tile == 0) { g_cnt1[0] = 0; g_cnt1[32] = 0; }
      const int r0 = tile * 64, r1 = r0 + 63;
      cnt_wait(g_cnt2 + (r0 / T_) * 64 + (r0 % T_) / 64, 4);
      cnt_wait(g_cnt2 + (r1 / T_) * 64 + (r1 % T_) / 64, 4);
      mbar_expect_tx(inbar + 8, 32768);
      tma_load_3d(base, &tmAtt, inbar + 8, 0, tile * 64, 0);
      pdl_wait();
    }
  } else {
    asm volatile("setmaxnreg.inc.sync.aligned.u32 240;");
    const Ctx c = make_ctx(base, 132 * 64);
    if (c.wg == 1) turn_end(c);
    float own[64];
    float a0, b0, a1, b1;
    PROF_MARK(2, 0);
    mbar_wait(c.full + 16 * RING, 0);
    PROF_MARK(2, 1);
    load_half(c, c.sX, own);
    mbar_wait(c.full + 16 * RING + 8, 0);
    PROF_MARK(2, 2);
    gemm256<0>(c, own, 2 * c.wg);
    PROF_MARK(2, 3);
    ln_stats(c, own, 0.5f, a0, b0, a1, b1);
    store_half(c, c.sA, own, a0, b0, a1, b1);
    fence_async_smem();
    bar_sync(1, 256);
    PROF_MARK(2, 4);
    uint4 dwr[5];
#pragma unroll
    for (int i = 0; i < 5; i++) dwr[i] = __ldg(dw + i * 32 + c.lane);
    const bool top = c.tid < 8, pub = top || c.tid >= 120;
    uint32_t* halo_out = (uint32_t*)g_halo + (tile * 4 + (top ? (c.tid >> 2) : ((c.tid >> 2) - 28))) * 128 + c.wg * 64 + (c.lane & 3);
#pragma unroll 1
    for (int q = 0; q < 2; q++) {
      float ab[64];
      gemm256<1>(c, ab, 4 + 4 * q + 2 * c.wg);
#pragma unroll
      for (int j = 0; j < 4; j++) {
        float g[8];
#pragma unroll
        for (int i = 0; i < 8; i++) g[i] = fmaf(ab[8 * j + i], tanh_fast(ab[32 + 8 * j + i]), ab[8 * j + i]);
        const uint32_t p0 = pack_bf16(g[0], g[1]), p1 = pack_bf16(g[2], g[3]), p2 = pack_bf16(g[4], g[5]), p3 = pack_bf16(g[6], g[7]);
        if (pub) {
          uint32_t* hp = halo_out + q * 32 + j * 8;
          asm volatile("st.relaxed.gpu.global.u32 [%0], %1;" :: "l"(hp), "r"(top ? p0 : p1) : "memory");
          asm volatile("st.relaxed.gpu.global.u32 [%0], %1;" :: "l"(hp + 4), "r"(top ? p2 : p3) : "memory");
        }
        stsm_x4(c.sX + (2 * c.wg + q) * 8192 + c.frag + (((j * 2 + c.hi) ^ c.rsw) << 4), p0, p1, p2, p3);
      }
    }
    bar_sync(1, 256);
    PROF_MARK(2, 5);
    {
      const int wi = threadIdx.x >> 5;
      const uint32_t col = (c.lane >> 3) * 8192, ch = c.lane & 7;
      uint4 r[12];
#pragma unroll
      for (int i = 0; i < 12; i++) {
        const int row = (wi * 8 - 2 + i) & 63;
        r[i] = lds128(c.sX + col + row * 128 + ((ch ^ (row & 7)) << 4));
      }
      uint32_t w[5][4];
#pragma unroll
      for (int k = 0; k < 5; k++) {
        w[k][0] = bmul2(dwr[k].x, 0x3F003F00u); w[k][1] = bmul2(dwr[k].y, 0x3F003F00u);
        w[k][2] = bmul2(dwr[k].z, 0x3F003F00u); w[k][3] = bmul2(dwr[k].w, 0x3F003F00u);
      }
      auto conv_row = [&](int i) {
        uint32_t o[4];
#pragma unroll
        for (int q = 0; q < 4; q++) {
          uint32_t acc = bmul2(q == 0 ? r[i].x : q == 1 ? r[i].y : q == 2 ? r[i].z : r[i].w, w[0][q]);
#pragma unroll
          for (int k = 1; k < 5; k++) acc = bfma2(q == 0 ? r[i + k].x : q == 1 ? r[i + k].y : q == 2 ? r[i + k].z : r[i + k].w, w[k][q], acc);
          o[q] = pack_bf16(silu_half(bf_lo(acc)), silu_half(bf_hi(acc)));
        }
        sts128(c.sA + col + (wi * 8 + i) * 128 + ((ch ^ i) << 4), make_uint4(o[0], o[1], o[2], o[3]));
      };
      conv_row(2); conv_row(3); conv_row(4); conv_row(5);
      const int R0 = tile * 64 + wi * 8;
      if ((R0 % T_) == 0) { r[0] = make_uint4(0, 0, 0, 0); r[1] = r[0]; }
      else if (wi == 0) { const uint4* sp = g_halo + ((tile - 1) * 4 + 2) * 32 + c.lane; halo_poll(sp, r[0]); halo_poll(sp + 32, r[1]); }
      if (((R0 + 8) % T_) == 0) { r[10] = make_uint4(0, 0, 0, 0); r[11] = r[10]; }
      else if (wi == 7) { const uint4* sp = g_halo + ((tile + 1) * 4) * 32 + c.lane; halo_poll(sp, r[10]); halo_poll(sp + 32, r[11]); }
      conv_row(0); conv_row(1); conv_row(6); conv_row(7);
    }
    fence_async_smem();
    bar_sync(1, 256);
    PROF_MARK(2, 6);
    gemm256<0>(c, own, 12 + 2 * c.wg);
    PROF_MARK(2, 7);
    ln_stats(c, own, 0.5f, a0, b0, a1, b1);
    store_half(c, c.sA, own, a0, b0, a1, b1);
    fence_async_smem();
    bar_sync(1, 256);
    PROF_MARK(2, 8);
    ff_block(c, 16, own);
    PROF_MARK(2, 9);
    ln_stats(c, own, 1.f, a0, b0, a1, b1);
    store_half(c, c.sX, own, a0, b0, a1, b1);
    fence_async_smem();
    bar_sync(3 + c.wg, 128);
    if (c.tid == 0) { tma_store_3d(&tmOut, c.sX + c.wg * 16384, 0, tile * 64, 2 * c.wg); bulk_commit(); PROF_MARK(2, 10); bulk_wait_all(); }
    PROF_MARK(2, 11);
  }
}

constexpr int NSTG = 4;
constexpr int KVB = 160 * 128;
constexpr int NKV = T_ / 160;
constexpr int ATT_SMEM = 65536 + NSTG * 2 * KVB + 256 + 1024;

struct AttCtx { uint32_t sKV, full, empty; const CUtensorMap* tmKV; int h, b, wg; };
__device__ __forceinline__ void att_load_stage(const AttCtx& a, int i) {
  const int s = i & (NSTG - 1);
  mbar_expect_tx(a.full + 8 * s, 2 * KVB);
  tma_load_3d(a.sKV + s * 2 * KVB, a.tmKV, a.full + 8 * s, 256 + a.h * 64, i * 160, a.b);
  tma_load_3d(a.sKV + s * 2 * KVB + KVB, a.tmKV, a.full + 8 * s, 512 + a.h * 64, i * 160, a.b);
}
__device__ __forceinline__ void att_qk(float (&S)[40], uint32_t dQ, uint32_t kd) {
  wg_ss_n80_tb0<0>(S, dQ, kd);
#pragma unroll
  for (int kk = 1; kk < 4; kk++) wg_ss_n80_tb0<1>(S, dQ + kk * 2, kd + kk * 2);
}
__device__ __forceinline__ void att_pv(float (&O)[32], const uint32_t (&P)[20], uint32_t vd) {
#pragma unroll
  for (int kk = 0; kk < 5; kk++) wg_rs_n64_tb1<1>(O, P[kk * 4], P[kk * 4 + 1], P[kk * 4 + 2], P[kk * 4 + 3], vd + kk * 128);
}
template<bool SAFE>
__device__ __forceinline__ void att_softmax(const float (&S)[40], uint32_t (&P)[20], float (&O)[32], float& m0, float& m1, float& l0, float& l1) {
  if (SAFE) {
    float x0 = fmaxf(S[0], S[1]), x1 = fmaxf(S[2], S[3]);
#pragma unroll
    for (int i = 1; i < 10; i++) { x0 = fmaxf(x0, fmaxf(S[4 * i], S[4 * i + 1])); x1 = fmaxf(x1, fmaxf(S[4 * i + 2], S[4 * i + 3])); }
    x0 = fmaxf(x0, __shfl_xor_sync(0xffffffff, x0, 1)); x1 = fmaxf(x1, __shfl_xor_sync(0xffffffff, x1, 1));
    x0 = fmaxf(x0, __shfl_xor_sync(0xffffffff, x0, 2)); x1 = fmaxf(x1, __shfl_xor_sync(0xffffffff, x1, 2));
    const float n0 = fmaxf(m0, x0), n1 = fmaxf(m1, x1);
    const float f0 = ex2(m0 - n0), f1 = ex2(m1 - n1);
    m0 = n0; m1 = n1; l0 *= f0; l1 *= f1;
#pragma unroll
    for (int i = 0; i < 8; i++) { O[4 * i] *= f0; O[4 * i + 1] *= f0; O[4 * i + 2] *= f1; O[4 * i + 3] *= f1; }
  }
#pragma unroll
  for (int i = 0; i < 10; i++) {
    float p0, p1, p2, p3;
    if (SAFE) { p0 = ex2(S[4 * i] - m0); p1 = ex2(S[4 * i + 1] - m0); p2 = ex2(S[4 * i + 2] - m1); p3 = ex2(S[4 * i + 3] - m1); }
    else { p0 = ex2(S[4 * i]); p1 = ex2(S[4 * i + 1]); p2 = ex2(S[4 * i + 2]); p3 = ex2(S[4 * i + 3]); }
    l0 += p0 + p1; l1 += p2 + p3;
    P[2 * i] = pack_bf16(p0, p1); P[2 * i + 1] = pack_bf16(p2, p3);
  }
}
template<bool SAFE>
__device__ __forceinline__ void att_pass(const AttCtx& a, uint32_t dQ, float (&O)[32], float& l0, float& l1) {
  float S[40];
  uint32_t P[20];
  float m0 = -INFINITY, m1 = -INFINITY;
  l0 = 0.f; l1 = 0.f;
#pragma unroll
  for (int i = 0; i < 32; i++) O[i] = 0.f;
  const uint32_t dKV = dlo(a.sKV, 16);
  constexpr uint32_t STG = 2 * KVB / 16, VOFF = KVB / 16, HALF = 80 * 128 / 16;
  constexpr int UNR = SAFE ? 1 : 4;
  mbar_wait(a.full, 0);
  wg_fence(); att_qk(S, dQ, dKV); wg_commit(); wg_wait<0>();
  att_softmax<SAFE>(S, P, O, m0, m1, l0, l1);
  wg_fence(); att_pv(O, P, dKV + VOFF); att_qk(S, dQ, dKV + HALF); wg_commit(); wg_wait<0>();
#pragma unroll 1
  for (int it0 = 0; it0 < NKV - 1; it0 += UNR) {
#pragma unroll
    for (int u = 0; u < UNR; u++) {
      const int it = it0 + u;
      const int s = SAFE ? (it & 3) : u, sn = (s + 1) & 3, sp = (s + 3) & 3;
      const uint32_t kb = dKV + s * STG, kn = dKV + sn * STG;
      att_softmax<SAFE>(S, P, O, m0, m1, l0, l1);
      mbar_wait(a.full + 8 * sn, ((it + 1) >> 2) & 1);
      wg_fence(); att_pv(O, P, kb + VOFF + HALF); att_qk(S, dQ, kn); wg_commit(); wg_wait<0>();
      if ((threadIdx.x & 127) == 0) {
        mbar_arrive(a.empty + 8 * s);
        if (a.wg == s && it >= 1 && it - 1 + NSTG < NKV) {
          mbar_wait(a.empty + 8 * sp, ((it - 1) >> 2) & 1);
          att_load_stage(a, it - 1 + NSTG);
        }
      }
      __syncwarp();
      att_softmax<SAFE>(S, P, O, m0, m1, l0, l1);
      wg_fence(); att_pv(O, P, kn + VOFF); att_qk(S, dQ, kn + HALF); wg_commit(); wg_wait<0>();
    }
  }
  att_softmax<SAFE>(S, P, O, m0, m1, l0, l1);
  wg_fence(); att_pv(O, P, dKV + ((NKV - 1) & 3) * STG + VOFF + HALF); wg_commit(); wg_wait<0>();
  l0 += __shfl_xor_sync(0xffffffff, l0, 1); l1 += __shfl_xor_sync(0xffffffff, l1, 1);
  l0 += __shfl_xor_sync(0xffffffff, l0, 2); l1 += __shfl_xor_sync(0xffffffff, l1, 2);
}

__global__ void __launch_bounds__(512, 1) k2_attn(const __grid_constant__ CUtensorMap tmQ, const __grid_constant__ CUtensorMap tmKV,
                                                  const __grid_constant__ CUtensorMap tmO) {
  extern __shared__ uint8_t smem_raw[];
  const uint32_t base = (smem_u32(smem_raw) + 1023) & ~1023u;
  const uint32_t sQ = base;
  AttCtx a;
  a.sKV = base + 65536; a.full = a.sKV + NSTG * 2 * KVB; a.empty = a.full + 8 * NSTG; a.tmKV = &tmKV;
  const uint32_t qbar = a.full + 16 * NSTG;
  const int qt = blockIdx.x & 15;
  a.h = (blockIdx.x >> 4) & 3; a.b = blockIdx.x >> 6;
  a.wg = __shfl_sync(0xffffffff, (int)(threadIdx.x >> 7), 0);
  const int lane = threadIdx.x & 31, wq = (threadIdx.x >> 5) & 3;
  PROF_MARK(1, 0);
  if (threadIdx.x == 0) {
    prefetch_tmap(&tmQ); prefetch_tmap(&tmKV); prefetch_tmap(&tmO);
    for (int i = 0; i < NSTG; i++) { mbar_init(a.full + 8 * i, 1); mbar_init(a.empty + 8 * i, 4); }
    mbar_init(qbar, 1);
    asm volatile("fence.mbarrier_init.release.cluster;" ::: "memory");
    cnt_wait(g_cnt1 + a.b * 32, 126);
    __threadfence();
    pdl_launch();
    mbar_expect_tx(qbar, 32768);
    tma_load_3d(sQ, &tmQ, qbar, a.h * 64, qt * 256, a.b);
    for (int i = 0; i < NSTG; i++) att_load_stage(a, i);
  }
  __syncthreads();
  const uint32_t sQw = sQ + a.wg * 8192, dQ = dlo(sQw, 16);
  float O[32], l0, l1;
  PROF_MARK(1, 1);
  mbar_wait(qbar, 0);
  PROF_MARK(1, 2);
  att_pass<false>(a, dQ, O, l0, l1);
  PROF_MARK(1, 3);
  float z = 0.f;
#pragma unroll
  for (int i = 0; i < 32; i++) z = fmaf(O[i], 0.f, z);
  const bool ok = (l0 >= 0x1p-80f) && (l0 <= 0x1p100f) && (l1 >= 0x1p-80f) && (l1 <= 0x1p100f) && (z == 0.f);
  uint32_t wg_bad;
  asm volatile("{\n.reg .pred p, q;\nsetp.eq.u32 p, %1, 0;\nbar.red.or.pred q, %2, 128, p;\nselp.u32 %0, 1, 0, q;\n}\n"
               : "=r"(wg_bad) : "r"((uint32_t)ok), "r"(1 + a.wg) : "memory");
  auto store_out = [&]() {
    const float i0 = 1.f / l0, i1 = 1.f / l1;
    const int r = wq * 16 + (lane & 7) + ((lane >> 3) & 1) * 8;
    const uint32_t sOw = sQw + 32768;
#pragma unroll
    for (int j = 0; j < 4; j++) {
      const int ch = j * 2 + (lane >> 4);
      stsm_x4(sOw + r * 128 + ((ch ^ (r & 7)) << 4),
              pack_bf16(O[8 * j] * i0, O[8 * j + 1] * i0), pack_bf16(O[8 * j + 2] * i1, O[8 * j + 3] * i1),
              pack_bf16(O[8 * j + 4] * i0, O[8 * j + 5] * i0), pack_bf16(O[8 * j + 6] * i1, O[8 * j + 7] * i1));
    }
    fence_async_smem();
    bar_sync(1 + a.wg, 128);
    if ((threadIdx.x & 127) == 0) {
      tma_store_3d(&tmO, sOw, a.h * 64, qt * 256 + a.wg * 64, a.b);
      bulk_commit();
      PROF_MARK(1, 4);
      bulk_wait_all();
      cnt_signal(g_cnt2 + a.b * 64 + qt * 4 + a.wg);
    }
  };
  if (!wg_bad) store_out();
  if (__syncthreads_or(wg_bad)) {
    if (threadIdx.x == 0) {
      for (int i = 0; i < NSTG; i++) { mbar_inval(a.full + 8 * i); mbar_inval(a.empty + 8 * i); }
      for (int i = 0; i < NSTG; i++) { mbar_init(a.full + 8 * i, 1); mbar_init(a.empty + 8 * i, 4); }
      asm volatile("fence.mbarrier_init.release.cluster;" ::: "memory");
      fence_async_smem();
      for (int i = 0; i < NSTG; i++) att_load_stage(a, i);
    }
    __syncthreads();
    att_pass<true>(a, dQ, O, l0, l1);
    if (wg_bad) store_out();
  }
  if (threadIdx.x == 0) pdl_wait();
  PROF_MARK(1, 5);
}

typedef CUresult (*EncodeFn)(CUtensorMap*, CUtensorMapDataType, cuuint32_t, void*, const cuuint64_t*, const cuuint64_t*, const cuuint32_t*,
                             const cuuint32_t*, CUtensorMapInterleave, CUtensorMapSwizzle, CUtensorMapL2promotion, CUtensorMapFloatOOBfill);

CUtensorMap make_map(EncodeFn enc, const void* p, uint64_t d0, uint64_t d1, uint64_t d2, uint64_t s1, uint64_t s2, uint32_t b1, uint32_t b2) {
  CUtensorMap tm;
  cuuint64_t dims[3] = {d0, d1, d2};
  cuuint64_t strides[2] = {s1, s2};
  cuuint32_t box[3] = {64, b1, b2};
  cuuint32_t es[3] = {1, 1, 1};
  enc(&tm, CU_TENSOR_MAP_DATA_TYPE_BFLOAT16, 3, const_cast<void*>(p), dims, strides, box, es, CU_TENSOR_MAP_INTERLEAVE_NONE,
      CU_TENSOR_MAP_SWIZZLE_128B, CU_TENSOR_MAP_L2_PROMOTION_L2_256B, CU_TENSOR_MAP_FLOAT_OOB_FILL_NONE);
  return tm;
}
CUtensorMap blk_map(EncodeFn enc, const void* p, uint64_t rows, uint64_t cols, uint32_t boxrows, uint32_t boxblks) {
  return make_map(enc, p, 64, rows, cols / 64, cols * 2, 128, boxrows, boxblks);
}
CUtensorMap seq_map(EncodeFn enc, const void* p, uint64_t cols, uint32_t boxrows) {
  return make_map(enc, p, cols, T_, 2, cols * 2, cols * 2 * T_, boxrows, 1);
}

}

extern "C" void kernel_launch(void* const* d_in, const int* in_sizes, int n_in, void* d_out, int out_size) {
  (void)in_sizes; (void)n_in; (void)out_size;
  const void *x = d_in[0], *w1a = d_in[1], *w1b = d_in[2], *wqkv = d_in[3], *wo = d_in[4], *pw1 = d_in[5], *dw = d_in[6], *pw2 = d_in[7],
             *w2a = d_in[8], *w2b = d_in[9];
  void* fn = nullptr;
  cudaDriverEntryPointQueryResult qr;
  cudaGetDriverEntryPoint("cuTensorMapEncodeTiled", &fn, cudaEnableDefault, &qr);
  EncodeFn enc = (EncodeFn)fn;
  void *x1, *qkv, *att;
  cudaGetSymbolAddress(&x1, g_x1);
  cudaGetSymbolAddress(&qkv, g_qkv);
  cudaGetSymbolAddress(&att, g_att);
  cudaFuncSetAttribute(k1_ff1_qkv, cudaFuncAttributeMaxDynamicSharedMemorySize, ROW_SMEM);
  cudaFuncSetAttribute(k2_attn, cudaFuncAttributeMaxDynamicSharedMemorySize, ATT_SMEM);
  cudaFuncSetAttribute(k3_tail, cudaFuncAttributeMaxDynamicSharedMemorySize, ROW_SMEM);

  Wptrs wp;
  const void* ws[8] = {w1a, w1b, wqkv, wo, pw1, pw2, w2a, w2b};
  const uint32_t wb[8] = {524288, 524288, 393216, 131072, 262144, 131072, 524288, 524288};
  for (int i = 0; i < 8; i++) { wp.p[i] = ws[i]; wp.bytes[i] = wb[i]; }

  cudaLaunchAttribute pdl[1];
  pdl[0].id = cudaLaunchAttributeProgrammaticStreamSerialization;
  pdl[0].val.programmaticStreamSerializationAllowed = 1;
  cudaLaunchConfig_t cfg = {};
  cfg.stream = cudaStreamPerThread;

  cfg.gridDim = dim3(NTILE); cfg.blockDim = dim3(384); cfg.dynamicSmemBytes = ROW_SMEM; cfg.attrs = nullptr; cfg.numAttrs = 0;
  cudaLaunchKernelEx(&cfg, k1_ff1_qkv, blk_map(enc, x, ROWS, 256, 64, 4), blk_map(enc, w1a, 256, 1024, 256, 1), blk_map(enc, w1b, 1024, 256, 64, 4),
                     blk_map(enc, wqkv, 256, 768, 128, 2), blk_map(enc, x1, ROWS, 256, 64, 2), blk_map(enc, qkv, ROWS, 768, 64, 2), wp);

  cfg.gridDim = dim3(128); cfg.blockDim = dim3(512); cfg.dynamicSmemBytes = ATT_SMEM; cfg.attrs = pdl; cfg.numAttrs = 1;
  cudaLaunchKernelEx(&cfg, k2_attn, seq_map(enc, qkv, 768, 256), seq_map(enc, qkv, 768, 160), seq_map(enc, att, 256, 64));

  cfg.gridDim = dim3(NTILE); cfg.blockDim = dim3(384); cfg.dynamicSmemBytes = ROW_SMEM;
  cudaLaunchKernelEx(&cfg, k3_tail, blk_map(enc, att, ROWS, 256, 64, 4), blk_map(enc, x1, ROWS, 256, 64, 4), blk_map(enc, wo, 256, 256, 128, 2),
                     make_map(enc, pw1, 256, 256, 2, 1024, 512, 128, 2), blk_map(enc, pw2, 256, 256, 128, 2), blk_map(enc, w2a, 256, 1024, 256, 1),
                     blk_map(enc, w2b, 1024, 256, 64, 4), blk_map(enc, d_out, ROWS, 256, 64, 2), (const uint4*)dw);
}
```

```cpp
#include <cuda_runtime.h>
#include <cuda_bf16.h>
#include <cuda.h>
#include <stdint.h>

namespace {

constexpr int T_ = 4000;
constexpr int ROWS = 8000;
constexpr int NTILE = 125;

__device__ __nv_bfloat16 g_x1[ROWS * 256];
__device__ __nv_bfloat16 g_qkv[ROWS * 768];
__device__ uint4 g_att[(ROWS / 16) * 16 * 32];
__device__ uint4 g_halo[NTILE * 4 * 32];
__device__ uint32_t g_cnt1[4 * 32];

#define PROF_MARK(k, i) do {} while (0)
#define PROF_STG(n, i) do {} while (0)

__device__ __forceinline__ uint32_t smem_u32(const void* p) { return (uint32_t)__cvta_generic_to_shared(p); }
__device__ __forceinline__ void mbar_init(uint32_t bar, uint32_t cnt) { asm volatile("mbarrier.init.shared::cta.b64 [%0], %1;" :: "r"(bar), "r"(cnt) : "memory"); }
__device__ __forceinline__ void mbar_inval(uint32_t bar) { asm volatile("mbarrier.inval.shared::cta.b64 [%0];" :: "r"(bar) : "memory"); }
__device__ __forceinline__ void mbar_expect_tx(uint32_t bar, uint32_t bytes) { asm volatile("mbarrier.arrive.expect_tx.shared::cta.b64 _, [%0], %1;" :: "r"(bar), "r"(bytes) : "memory"); }
__device__ __forceinline__ void mbar_arrive(uint32_t bar) { asm volatile("mbarrier.arrive.shared::cta.b64 _, [%0];" :: "r"(bar) : "memory"); }
__device__ __forceinline__ void mbar_wait(uint32_t bar, uint32_t parity) {
  asm volatile("{\n.reg .pred p;\n.reg .u32 n;\n"
               "mbarrier.try_wait.parity.shared::cta.b64 p, [%0], %1;\n@p bra DONE_%=;\nmov.u32 n, 0;\n"
               "LOOP_%=:\nmbarrier.try_wait.parity.shared::cta.b64 p, [%0], %1;\n@p bra DONE_%=;\n"
               "add.u32 n, n, 1;\nsetp.lt.u32 p, n, 4194304;\n@p bra LOOP_%=;\ntrap;\nDONE_%=:\n}\n" :: "r"(bar), "r"(parity) : "memory");
}
__device__ __forceinline__ void data_poll(const uint4* p, uint4& v) {
  asm volatile("{\n.reg .pred p;\n.reg .u32 n, t;\nmov.u32 n, 0;\n"
               "LOOP_%=:\nld.relaxed.gpu.global.v4.u32 {%0,%1,%2,%3}, [%4];\n"
               "max.u32 t, %0, %1;\nmax.u32 t, t, %2;\nmax.u32 t, t, %3;\nsetp.ne.u32 p, t, 0xFFFFFFFF;\n@p bra DONE_%=;\n"
               "add.u32 n, n, 1;\nsetp.lt.u32 p, n, 16777216;\n@p bra LOOP_%=;\ntrap;\nDONE_%=:\n}\n"
               : "=&r"(v.x), "=&r"(v.y), "=&r"(v.z), "=&r"(v.w) : "l"(p) : "memory");
}
__device__ __forceinline__ void cnt_wait(const uint32_t* p, uint32_t target) {
  asm volatile("{\n.reg .pred p;\n.reg .u32 n, v;\nmov.u32 n, 0;\n"
               "LOOP_%=:\nld.relaxed.gpu.global.u32 v, [%0];\nsetp.ge.u32 p, v, %1;\n@p bra DONE_%=;\n"
               "add.u32 n, n, 1;\nsetp.lt.u32 p, n, 16777216;\n@p bra LOOP_%=;\ntrap;\nDONE_%=:\n}\n" :: "l"(p), "r"(target) : "memory");
}
__device__ __forceinline__ void cnt_signal(uint32_t* p) {
  asm volatile("red.relaxed.gpu.global.add.u32 [%0], 1;" :: "l"(p) : "memory");
}
__device__ __forceinline__ void tma_load_3d(uint32_t dst, const CUtensorMap* tm, uint32_t bar, int c0, int c1, int c2) {
  asm volatile("cp.async.bulk.tensor.3d.shared::cluster.global.mbarrier::complete_tx::bytes [%0], [%1, {%3, %4, %5}], [%2];"
    :: "r"(dst), "l"(tm), "r"(bar), "r"(c0), "r"(c1), "r"(c2) : "memory");
}
__device__ __forceinline__ void tma_store_3d(const CUtensorMap* tm, uint32_t src, int c0, int c1, int c2) {
  asm volatile("cp.async.bulk.tensor.3d.global.shared::cta.bulk_group [%0, {%2, %3, %4}], [%1];" :: "l"(tm), "r"(src), "r"(c0), "r"(c1), "r"(c2) : "memory");
}
__device__ __forceinline__ void bulk_commit() { asm volatile("cp.async.bulk.commit_group;" ::: "memory"); }
__device__ __forceinline__ void bulk_wait_read() { asm volatile("cp.async.bulk.wait_group.read 0;" ::: "memory"); }
__device__ __forceinline__ void bulk_wait_all() { asm volatile("cp.async.bulk.wait_group 0;" ::: "memory"); }
__device__ __forceinline__ void l2_prefetch(const void* p, uint32_t bytes) { asm volatile("cp.async.bulk.prefetch.L2.global [%0], %1;" :: "l"(p), "r"(bytes) : "memory"); }
__device__ __forceinline__ void prefetch_tmap(const CUtensorMap* tm) { asm volatile("prefetch.tensormap [%0];" :: "l"(tm) : "memory"); }
__device__ __forceinline__ void fence_async_smem() { asm volatile("fence.proxy.async.shared::cta;" ::: "memory"); }
__device__ __forceinline__ void wg_fence() { asm volatile("wgmma.fence.sync.aligned;" ::: "memory"); }
__device__ __forceinline__ void wg_commit() { asm volatile("wgmma.commit_group.sync.aligned;" ::: "memory"); }
template<int N> __device__ __forceinline__ void wg_wait() { asm volatile("wgmma.wait_group.sync.aligned %0;" :: "n"(N) : "memory"); }
__device__ __forceinline__ void bar_sync(int id, int n) { asm volatile("bar.sync %0, %1;" :: "r"(id), "r"(n) : "memory"); }
__device__ __forceinline__ void bar_arrive(int id, int n) { asm volatile("bar.arrive %0, %1;" :: "r"(id), "r"(n) : "memory"); }
__device__ __forceinline__ void pdl_wait() { asm volatile("griddepcontrol.wait;" ::: "memory"); }
__device__ __forceinline__ void pdl_launch() { asm volatile("griddepcontrol.launch_dependents;" ::: "memory"); }
__device__ __forceinline__ float ex2(float x) { float y; asm("ex2.approx.ftz.f32 %0, %1;" : "=f"(y) : "f"(x)); return y; }
__device__ __forceinline__ float tanh_fast(float x) { float y; asm("tanh.approx.f32 %0, %1;" : "=f"(y) : "f"(x)); return y; }
__device__ __forceinline__ uint32_t pack_bf16(float lo, float hi) { uint32_t r; asm("cvt.rn.bf16x2.f32 %0, %1, %2;" : "=r"(r) : "f"(hi), "f"(lo)); return r; }
__device__ __forceinline__ uint32_t bmul2(uint32_t a, uint32_t b) { uint32_t d; asm("mul.rn.bf16x2 %0, %1, %2;" : "=r"(d) : "r"(a), "r"(b)); return d; }
__device__ __forceinline__ uint32_t bfma2(uint32_t a, uint32_t b, uint32_t c) { uint32_t d; asm("fma.rn.bf16x2 %0, %1, %2, %3;" : "=r"(d) : "r"(a), "r"(b), "r"(c)); return d; }
__device__ __forceinline__ float bf_lo(uint32_t u) { return __uint_as_float(u << 16); }
__device__ __forceinline__ float bf_hi(uint32_t u) { return __uint_as_float(u & 0xffff0000u); }
__device__ __forceinline__ void ldsm_x4(uint32_t addr, uint32_t& r0, uint32_t& r1, uint32_t& r2, uint32_t& r3) {
  asm volatile("ldmatrix.sync.aligned.m8n8.x4.shared.b16 {%0,%1,%2,%3}, [%4];" : "=r"(r0), "=r"(r1), "=r"(r2), "=r"(r3) : "r"(addr) : "memory");
}
__device__ __forceinline__ void stsm_x4(uint32_t addr, uint32_t r0, uint32_t r1, uint32_t r2, uint32_t r3) {
  asm volatile("stmatrix.sync.aligned.m8n8.x4.shared.b16 [%0], {%1,%2,%3,%4};" :: "r"(addr), "r"(r0), "r"(r1), "r"(r2), "r"(r3) : "memory");
}
__device__ __forceinline__ void sts128(uint32_t addr, uint4 v) { asm volatile("st.shared.v4.b32 [%0], {%1,%2,%3,%4};" :: "r"(addr), "r"(v.x), "r"(v.y), "r"(v.z), "r"(v.w) : "memory"); }
__device__ __forceinline__ uint4 lds128(uint32_t addr) { uint4 v; asm volatile("ld.shared.v4.b32 {%0,%1,%2,%3}, [%4];" : "=r"(v.x), "=r"(v.y), "=r"(v.z), "=r"(v.w) : "r"(addr) : "memory"); return v; }
__device__ __forceinline__ void sts64f(uint32_t addr, float a, float b) { asm volatile("st.shared.v2.f32 [%0], {%1,%2};" :: "r"(addr), "f"(a), "f"(b) : "memory"); }
__device__ __forceinline__ float2 lds64f(uint32_t addr) { float2 v; asm volatile("ld.shared.v2.f32 {%0,%1}, [%2];" : "=f"(v.x), "=f"(v.y) : "r"(addr) : "memory"); return v; }
__device__ __forceinline__ uint32_t dlo(uint32_t addr, uint32_t lbo) { return ((addr & 0x3FFFF) >> 4) | ((lbo >> 4) << 16); }

template<int SD> __device__ __forceinline__ void wg_ss_n128_tb1(float (&d)[64], uint32_t da, uint32_t db) {
  asm volatile("{\n.reg .b64 da, db;\nmov.b64 da, {%64, 0x40000040};\nmov.b64 db, {%65, 0x40000040};\n"
    "wgmma.mma_async.sync.aligned.m64n128k16.f32.bf16.bf16 {%0, %1, %2, %3, %4, %5, %6, %7, %8, %9, %10, %11, %12, %13, %14, %15, %16, %17, %18, %19, %20, %21, %22, %23, %24, %25, %26, %27, %28, %29, %30, %31, %32, %33, %34, %35, %36, %37, %38, %39, %40, %41, %42, %43, %44, %45, %46, %47, %48, %49, %50, %51, %52, %53, %54, %55, %56, %57, %58, %59, %60, %61, %62, %63}, da, db, %66, 1, 1, 0, 1;\n}\n"
    : "+f"(d[0]), "+f"(d[1]), "+f"(d[2]), "+f"(d[3]), "+f"(d[4]), "+f"(d[5]), "+f"(d[6]), "+f"(d[7]), "+f"(d[8]), "+f"(d[9]), "+f"(d[10]), "+f"(d[11]), "+f"(d[12]), "+f"(d[13]), "+f"(d[14]), "+f"(d[15]), "+f"(d[16]), "+f"(d[17]), "+f"(d[18]), "+f"(d[19]), "+f"(d[20]), "+f"(d[21]), "+f"(d[22]), "+f"(d[23]), "+f"(d[24]), "+f"(d[25]), "+f"(d[26]), "+f"(d[27]), "+f"(d[28]), "+f"(d[29]), "+f"(d[30]), "+f"(d[31]), "+f"(d[32]), "+f"(d[33]), "+f"(d[34]), "+f"(d[35]), "+f"(d[36]), "+f"(d[37]), "+f"(d[38]), "+f"(d[39]), "+f"(d[40]), "+f"(d[41]), "+f"(d[42]), "+f"(d[43]), "+f"(d[44]), "+f"(d[45]), "+f"(d[46]), "+f"(d[47]), "+f"(d[48]), "+f"(d[49]), "+f"(d[50]), "+f"(d[51]), "+f"(d[52]), "+f"(d[53]), "+f"(d[54]), "+f"(d[55]), "+f"(d[56]), "+f"(d[57]), "+f"(d[58]), "+f"(d[59]), "+f"(d[60]), "+f"(d[61]), "+f"(d[62]), "+f"(d[63])
    : "r"(da), "r"(db), "n"(SD));
}
template<int SD> __device__ __forceinline__ void wg_rs_n128_tb1(float (&d)[64], uint32_t a0, uint32_t a1, uint32_t a2, uint32_t a3, uint32_t db) {
  asm volatile("{\n.reg .b64 db;\nmov.b64 db, {%68, 0x40000040};\n"
    "wgmma.mma_async.sync.aligned.m64n128k16.f32.bf16.bf16 {%0, %1, %2, %3, %4, %5, %6, %7, %8, %9, %10, %11, %12, %13, %14, %15, %16, %17, %18, %19, %20, %21, %22, %23, %24, %25, %26, %27, %28, %29, %30, %31, %32, %33, %34, %35, %36, %37, %38, %39, %40, %41, %42, %43, %44, %45, %46, %47, %48, %49, %50, %51, %52, %53, %54, %55, %56, %57, %58, %59, %60, %61, %62, %63}, {%64, %65, %66, %67}, db, %69, 1, 1, 1;\n}\n"
    : "+f"(d[0]), "+f"(d[1]), "+f"(d[2]), "+f"(d[3]), "+f"(d[4]), "+f"(d[5]), "+f"(d[6]), "+f"(d[7]), "+f"(d[8]), "+f"(d[9]), "+f"(d[10]), "+f"(d[11]), "+f"(d[12]), "+f"(d[13]), "+f"(d[14]), "+f"(d[15]), "+f"(d[16]), "+f"(d[17]), "+f"(d[18]), "+f"(d[19]), "+f"(d[20]), "+f"(d[21]), "+f"(d[22]), "+f"(d[23]), "+f"(d[24]), "+f"(d[25]), "+f"(d[26]), "+f"(d[27]), "+f"(d[28]), "+f"(d[29]), "+f"(d[30]), "+f"(d[31]), "+f"(d[32]), "+f"(d[33]), "+f"(d[34]), "+f"(d[35]), "+f"(d[36]), "+f"(d[37]), "+f"(d[38]), "+f"(d[39]), "+f"(d[40]), "+f"(d[41]), "+f"(d[42]), "+f"(d[43]), "+f"(d[44]), "+f"(d[45]), "+f"(d[46]), "+f"(d[47]), "+f"(d[48]), "+f"(d[49]), "+f"(d[50]), "+f"(d[51]), "+f"(d[52]), "+f"(d[53]), "+f"(d[54]), "+f"(d[55]), "+f"(d[56]), "+f"(d[57]), "+f"(d[58]), "+f"(d[59]), "+f"(d[60]), "+f"(d[61]), "+f"(d[62]), "+f"(d[63])
    : "r"(a0), "r"(a1), "r"(a2), "r"(a3), "r"(db), "n"(SD));
}
template<int SD> __device__ __forceinline__ void wg_ss_n64_tb1(float (&d)[32], uint32_t da, uint32_t db) {
  asm volatile("{\n.reg .b64 da, db;\nmov.b64 da, {%32, 0x40000040};\nmov.b64 db, {%33, 0x40000040};\n"
    "wgmma.mma_async.sync.aligned.m64n64k16.f32.bf16.bf16 {%0, %1, %2, %3, %4, %5, %6, %7, %8, %9, %10, %11, %12, %13, %14, %15, %16, %17, %18, %19, %20, %21, %22, %23, %24, %25, %26, %27, %28, %29, %30, %31}, da, db, %34, 1, 1, 0, 1;\n}\n"
    : "+f"(d[0]), "+f"(d[1]), "+f"(d[2]), "+f"(d[3]), "+f"(d[4]), "+f"(d[5]), "+f"(d[6]), "+f"(d[7]), "+f"(d[8]), "+f"(d[9]), "+f"(d[10]), "+f"(d[11]), "+f"(d[12]), "+f"(d[13]), "+f"(d[14]), "+f"(d[15]), "+f"(d[16]), "+f"(d[17]), "+f"(d[18]), "+f"(d[19]), "+f"(d[20]), "+f"(d[21]), "+f"(d[22]), "+f"(d[23]), "+f"(d[24]), "+f"(d[25]), "+f"(d[26]), "+f"(d[27]), "+f"(d[28]), "+f"(d[29]), "+f"(d[30]), "+f"(d[31])
    : "r"(da), "r"(db), "n"(SD));
}
template<int SD> __device__ __forceinline__ void wg_ss_n80_tb0(float (&d)[40], uint32_t da, uint32_t db) {
  asm volatile("{\n.reg .b64 da, db;\nmov.b64 da, {%40, 0x40000040};\nmov.b64 db, {%41, 0x40000040};\n"
    "wgmma.mma_async.sync.aligned.m64n80k16.f32.bf16.bf16 {%0, %1, %2, %3, %4, %5, %6, %7, %8, %9, %10, %11, %12, %13, %14, %15, %16, %17, %18, %19, %20, %21, %22, %23, %24, %25, %26, %27, %28, %29, %30, %31, %32, %33, %34, %35, %36, %37, %38, %39}, da, db, %42, 1, 1, 0, 0;\n}\n"
    : "+f"(d[0]), "+f"(d[1]), "+f"(d[2]), "+f"(d[3]), "+f"(d[4]), "+f"(d[5]), "+f"(d[6]), "+f"(d[7]), "+f"(d[8]), "+f"(d[9]), "+f"(d[10]), "+f"(d[11]), "+f"(d[12]), "+f"(d[13]), "+f"(d[14]), "+f"(d[15]), "+f"(d[16]), "+f"(d[17]), "+f"(d[18]), "+f"(d[19]), "+f"(d[20]), "+f"(d[21]), "+f"(d[22]), "+f"(d[23]), "+f"(d[24]), "+f"(d[25]), "+f"(d[26]), "+f"(d[27]), "+f"(d[28]), "+f"(d[29]), "+f"(d[30]), "+f"(d[31]), "+f"(d[32]), "+f"(d[33]), "+f"(d[34]), "+f"(d[35]), "+f"(d[36]), "+f"(d[37]), "+f"(d[38]), "+f"(d[39])
    : "r"(da), "r"(db), "n"(SD));
}
template<int SD> __device__ __forceinline__ void wg_rs_n64_tb1(float (&d)[32], uint32_t a0, uint32_t a1, uint32_t a2, uint32_t a3, uint32_t db) {
  asm volatile("{\n.reg .b64 db;\nmov.b64 db, {%36, 0x40000040};\n"
    "wgmma.mma_async.sync.aligned.m64n64k16.f32.bf16.bf16 {%0, %1, %2, %3, %4, %5, %6, %7, %8, %9, %10, %11, %12, %13, %14, %15, %16, %17, %18, %19, %20, %21, %22, %23, %24, %25, %26, %27, %28, %29, %30, %31}, {%32, %33, %34, %35}, db, %37, 1, 1, 1;\n}\n"
    : "+f"(d[0]), "+f"(d[1]), "+f"(d[2]), "+f"(d[3]), "+f"(d[4]), "+f"(d[5]), "+f"(d[6]), "+f"(d[7]), "+f"(d[8]), "+f"(d[9]), "+f"(d[10]), "+f"(d[11]), "+f"(d[12]), "+f"(d[13]), "+f"(d[14]), "+f"(d[15]), "+f"(d[16]), "+f"(d[17]), "+f"(d[18]), "+f"(d[19]), "+f"(d[20]), "+f"(d[21]), "+f"(d[22]), "+f"(d[23]), "+f"(d[24]), "+f"(d[25]), "+f"(d[26]), "+f"(d[27]), "+f"(d[28]), "+f"(d[29]), "+f"(d[30]), "+f"(d[31])
    : "r"(a0), "r"(a1), "r"(a2), "r"(a3), "r"(db), "n"(SD));
}

constexpr int RING = 5;
constexpr uint32_t STAGE = 32768;
constexpr uint32_t OFF_X = 32768, OFF_W = 65536, OFF_MISC = OFF_W + RING * STAGE;
constexpr int ROW_SMEM = OFF_MISC + 256 + 1024 + 1024;

struct Ctx {
  uint32_t sA, sX, sW, full, empty, stats;
  uint32_t frag;
  uint32_t rsw;
  uint32_t hi;
  int wg, tid, lane;
  int pk;
};
__device__ __forceinline__ uint32_t stage_wait(const Ctx& c, int n) {
  const int q = n / RING, s = n - q * RING;
  if (c.tid == 0) PROF_STG(n + c.pk, 1);
  mbar_wait(c.full + 8 * s, q & 1);
  if (c.tid == 0) PROF_STG(n + c.pk, 2);
  return dlo(c.sW + s * STAGE, 0);
}
__device__ __forceinline__ void stage_release(const Ctx& c, int n) {
  const int s = n % RING;
  if (c.tid == 0) { mbar_arrive(c.empty + 8 * s); PROF_STG(n + c.pk, 3); }
}
__device__ __forceinline__ void turn_begin(const Ctx& c) { bar_sync(5 + c.wg, 256); }
__device__ __forceinline__ void turn_end(const Ctx& c) { bar_arrive(5 + (c.wg ^ 1), 256); }
template<int FIRST> __device__ __forceinline__ void piece_ss(float (&acc)[64], uint32_t dA, uint32_t dB) {
  dB += (16384 >> 4) << 16;
  wg_ss_n128_tb1<FIRST ? 0 : 1>(acc, dA, dB);
#pragma unroll
  for (int kk = 1; kk < 8; kk++) wg_ss_n128_tb1<1>(acc, dA + (kk >> 2) * 512 + (kk & 3) * 2, dB + kk * 128);
}
__device__ __forceinline__ void ff_g1(float (&h)[32], uint32_t dA, uint32_t dB) {
  wg_ss_n64_tb1<0>(h, dA, dB);
#pragma unroll
  for (int kk = 1; kk < 16; kk++) wg_ss_n64_tb1<1>(h, dA + (kk >> 2) * 512 + (kk & 3) * 2, dB + kk * 128);
}
__device__ __forceinline__ void ff_g2(float (&acc)[64], const uint32_t (&P)[16], uint32_t dB, int half) {
  dB += ((8192 >> 4) << 16) + half * 1024;
#pragma unroll
  for (int kk = 0; kk < 4; kk++) wg_rs_n128_tb1<1>(acc, P[4 * kk], P[4 * kk + 1], P[4 * kk + 2], P[4 * kk + 3], dB + kk * 128);
}
template<int FIRST> __device__ __forceinline__ void gemm256(const Ctx& c, float (&acc)[64], int n) {
  const uint32_t dA = dlo(c.sA, 16);
  uint32_t b = stage_wait(c, n);
  turn_begin(c);
  wg_fence(); piece_ss<FIRST>(acc, dA, b); wg_commit();
  b = stage_wait(c, n + 1);
  wg_fence(); piece_ss<0>(acc, dA + 1024, b); wg_commit();
  turn_end(c);
  wg_wait<1>(); stage_release(c, n);
  wg_wait<0>(); stage_release(c, n + 1);
}
__device__ __forceinline__ uint32_t frag_addr(const Ctx& c, uint32_t tile, int j) {
  return tile + (2 * c.wg + (j >> 2)) * 8192 + c.frag + ((((j & 3) * 2 + c.hi) ^ c.rsw) << 4);
}
__device__ __forceinline__ void load_half(const Ctx& c, uint32_t tile, float (&v)[64]) {
#pragma unroll
  for (int j = 0; j < 8; j++) {
    uint32_t r0, r1, r2, r3;
    ldsm_x4(frag_addr(c, tile, j), r0, r1, r2, r3);
    v[8 * j] = bf_lo(r0); v[8 * j + 1] = bf_hi(r0); v[8 * j + 2] = bf_lo(r1); v[8 * j + 3] = bf_hi(r1);
    v[8 * j + 4] = bf_lo(r2); v[8 * j + 5] = bf_hi(r2); v[8 * j + 6] = bf_lo(r3); v[8 * j + 7] = bf_hi(r3);
  }
}
__device__ __forceinline__ void store_half(const Ctx& c, uint32_t tile, const float (&v)[64], float a0, float b0, float a1, float b1) {
#pragma unroll
  for (int j = 0; j < 8; j++)
    stsm_x4(frag_addr(c, tile, j),
            pack_bf16(fmaf(v[8 * j], a0, b0), fmaf(v[8 * j + 1], a0, b0)), pack_bf16(fmaf(v[8 * j + 2], a1, b1), fmaf(v[8 * j + 3], a1, b1)),
            pack_bf16(fmaf(v[8 * j + 4], a0, b0), fmaf(v[8 * j + 5], a0, b0)), pack_bf16(fmaf(v[8 * j + 6], a1, b1), fmaf(v[8 * j + 7], a1, b1)));
}
__device__ __forceinline__ void store_half_raw(const Ctx& c, uint32_t tile, const float (&v)[64]) {
#pragma unroll
  for (int j = 0; j < 8; j++)
    stsm_x4(frag_addr(c, tile, j), pack_bf16(v[8 * j], v[8 * j + 1]), pack_bf16(v[8 * j + 2], v[8 * j + 3]),
            pack_bf16(v[8 * j + 4], v[8 * j + 5]), pack_bf16(v[8 * j + 6], v[8 * j + 7]));
}
__device__ __forceinline__ void ln_stats(const Ctx& c, const float (&v)[64], float scale, float& a0, float& b0, float& a1, float& b1) {
  float s0 = 0.f, s1 = 0.f, q0 = 0.f, q1 = 0.f, s2 = 0.f, s3 = 0.f, q2 = 0.f, q3 = 0.f;
#pragma unroll
  for (int i = 0; i < 16; i++) {
    s0 += v[4 * i]; q0 = fmaf(v[4 * i], v[4 * i], q0);
    s2 += v[4 * i + 1]; q2 = fmaf(v[4 * i + 1], v[4 * i + 1], q2);
    s1 += v[4 * i + 2]; q1 = fmaf(v[4 * i + 2], v[4 * i + 2], q1);
    s3 += v[4 * i + 3]; q3 = fmaf(v[4 * i + 3], v[4 * i + 3], q3);
  }
  s0 += s2; q0 += q2; s1 += s3; q1 += q3;
  s0 += __shfl_xor_sync(0xffffffff, s0, 1); q0 += __shfl_xor_sync(0xffffffff, q0, 1);
  s1 += __shfl_xor_sync(0xffffffff, s1, 1); q1 += __shfl_xor_sync(0xffffffff, q1, 1);
  s0 += __shfl_xor_sync(0xffffffff, s0, 2); q0 += __shfl_xor_sync(0xffffffff, q0, 2);
  s1 += __shfl_xor_sync(0xffffffff, s1, 2); q1 += __shfl_xor_sync(0xffffffff, q1, 2);
  const uint32_t row = (c.tid >> 5) * 16 + (c.lane >> 2);
  if ((c.lane & 3) == 0) {
    sts64f(c.stats + c.wg * 512 + row * 8, s0, q0);
    sts64f(c.stats + c.wg * 512 + (row + 8) * 8, s1, q1);
  }
  bar_sync(1, 256);
  const float2 o0 = lds64f(c.stats + (c.wg ^ 1) * 512 + row * 8), o1 = lds64f(c.stats + (c.wg ^ 1) * 512 + (row + 8) * 8);
  const float m0 = (s0 + o0.x) * (1.f / 256.f), m1 = (s1 + o1.x) * (1.f / 256.f);
  const float var0 = fmaxf(fmaf(-m0, m0, (q0 + o0.y) * (1.f / 256.f)), 0.f), var1 = fmaxf(fmaf(-m1, m1, (q1 + o1.y) * (1.f / 256.f)), 0.f);
  a0 = rsqrtf(var0 + 1e-5f) * scale; a1 = rsqrtf(var1 + 1e-5f) * scale;
  b0 = -m0 * a0; b1 = -m1 * a1;
}
__device__ __forceinline__ float silu_half(float h) { return fmaf(h, tanh_fast(h), h); }
__device__ __forceinline__ float silu_quarter(float h) { const float q = 0.5f * h; return fmaf(q, tanh_fast(h), q); }
__device__ __forceinline__ void silu_pack(const float (&acc)[32], uint32_t (&P)[16]) {
#pragma unroll
  for (int i = 0; i < 16; i++) P[i] = pack_bf16(silu_quarter(acc[2 * i]), silu_quarter(acc[2 * i + 1]));
}
__device__ __forceinline__ void ff_block(const Ctx& c, int n0, float (&own)[64]) {
  float oth[64], h[32];
  uint32_t P[16];
#pragma unroll
  for (int i = 0; i < 64; i++) oth[i] = 0.f;
  const uint32_t dA = dlo(c.sA, 16);
  {
    const uint32_t b = stage_wait(c, n0 + c.wg);
    turn_begin(c);
    wg_fence(); ff_g1(h, dA, b); wg_commit();
    turn_end(c);
    wg_wait<0>(); stage_release(c, n0 + c.wg);
    silu_pack(h, P);
  }
#pragma unroll 1
  for (int it = 1; it < 8; it++) {
    const int n = n0 + 4 * it - 2 + 2 * c.wg;
    uint32_t b = stage_wait(c, n);
    turn_begin(c);
    wg_fence(); ff_g2(own, P, b, c.wg); ff_g2(oth, P, b, c.wg ^ 1); wg_commit();
    b = stage_wait(c, n + 1);
    wg_fence(); ff_g1(h, dA, b); wg_commit();
    turn_end(c);
    wg_wait<1>(); stage_release(c, n);
    wg_wait<0>(); stage_release(c, n + 1);
    silu_pack(h, P);
  }
  if (c.wg == 0) bar_arrive(2, 256);
  {
    const int n = n0 + 30 + c.wg;
    const uint32_t b = stage_wait(c, n);
    turn_begin(c);
    wg_fence(); ff_g2(oth, P, b, c.wg ^ 1); wg_commit();
    ff_g2(own, P, b, c.wg); wg_commit();
    turn_end(c);
    wg_wait<1>();
    if (c.wg == 1) bar_sync(2, 256);
    const uint32_t e = (c.wg == 0 ? c.sX : c.sA) + c.tid * 16;
#pragma unroll
    for (int i = 0; i < 16; i++)
      sts128(e + i * 2048, make_uint4(__float_as_uint(oth[4 * i]), __float_as_uint(oth[4 * i + 1]), __float_as_uint(oth[4 * i + 2]), __float_as_uint(oth[4 * i + 3])));
    wg_wait<0>(); stage_release(c, n);
  }
  bar_sync(1, 256);
  const uint32_t e = (c.wg == 0 ? c.sA : c.sX) + c.tid * 16;
#pragma unroll
  for (int i = 0; i < 16; i++) {
    const uint4 u = lds128(e + i * 2048);
    own[4 * i] += __uint_as_float(u.x); own[4 * i + 1] += __uint_as_float(u.y);
    own[4 * i + 2] += __uint_as_float(u.z); own[4 * i + 3] += __uint_as_float(u.w);
  }
}
__device__ __forceinline__ void produce(uint32_t sW, uint32_t full, uint32_t empty, int n, const CUtensorMap* tm, int k0, int nblk, int c0 = 0) {
  const int q = n / RING, s = n - q * RING;
  mbar_wait(empty + 8 * s, (q & 1) ^ 1);
  PROF_STG(n + ((sW & 1) ? 132 * 64 : 0), 0);
  sW &= ~1u;
  mbar_expect_tx(full + 8 * s, STAGE);
  tma_load_3d(sW + s * STAGE, tm, full + 8 * s, c0, k0, nblk);
}
__device__ __forceinline__ void produce_ff(uint32_t sW, uint32_t full, uint32_t empty, int n0, const CUtensorMap* tmA, const CUtensorMap* tmB) {
#pragma unroll 1
  for (int m = 0; m < 32; m++) {
    int is2, j;
    if (m < 2) { is2 = 0; j = m; }
    else if (m == 31) { is2 = 1; j = 15; }
    else { const int q = m - 2; is2 = !(q & 1); j = (q >> 1) + (is2 ? 0 : 2); }
    if (is2) produce(sW, full, empty, n0 + m, tmB, 64 * j, 0);
    else produce(sW, full, empty, n0 + m, tmA, 0, j);
  }
}
__device__ __forceinline__ Ctx make_ctx(uint32_t base, int pk = 0) {
  Ctx c; c.pk = pk;
  c.sA = base; c.sX = base + OFF_X; c.sW = base + OFF_W;
  c.full = base + OFF_MISC; c.empty = c.full + 8 * RING; c.stats = base + OFF_MISC + 256;
  c.wg = __shfl_sync(0xffffffff, (int)(threadIdx.x >> 7), 0);
  c.tid = threadIdx.x & 127; c.lane = threadIdx.x & 31;
  const uint32_t r = (c.tid >> 5) * 16 + (c.lane & 7) + ((c.lane >> 3) & 1) * 8;
  c.frag = r * 128; c.rsw = r & 7; c.hi = c.lane >> 4;
  return c;
}
__device__ __forceinline__ void row_init(uint32_t base) {
  if (threadIdx.x == 0) {
    const uint32_t full = base + OFF_MISC;
    for (int i = 0; i < RING; i++) { mbar_init(full + 8 * i, 1); mbar_init(full + 8 * RING + 8 * i, 1); }
    mbar_init(full + 16 * RING, 1);
    mbar_init(full + 16 * RING + 8, 1);
    asm volatile("fence.mbarrier_init.release.cluster;" ::: "memory");
  }
  __syncthreads();
}
struct Wptrs { const void* p[8]; uint32_t bytes[8]; };

__global__ void __launch_bounds__(384, 1) k1_ff1_qkv(const __grid_constant__ CUtensorMap tmX, const __grid_constant__ CUtensorMap tmW1a,
    const __grid_constant__ CUtensorMap tmW1b, const __grid_constant__ CUtensorMap tmWqkv, const __grid_constant__ CUtensorMap tmX1st,
    const __grid_constant__ CUtensorMap tmQKVst, const __grid_constant__ Wptrs wp) {
  extern __shared__ uint8_t smem_raw[];
  const uint32_t base = (smem_u32(smem_raw) + 1023) & ~1023u;
  const int tile = blockIdx.x;
  if (threadIdx.x == 256) { prefetch_tmap(&tmX); prefetch_tmap(&tmW1a); prefetch_tmap(&tmW1b); prefetch_tmap(&tmWqkv); prefetch_tmap(&tmX1st); prefetch_tmap(&tmQKVst); }
  if (threadIdx.x >= 128 && threadIdx.x < 256) g_halo[tile * 128 + threadIdx.x - 128] = make_uint4(~0u, ~0u, ~0u, ~0u);
  row_init(base);
  pdl_launch();
  if (threadIdx.x >= 256) {
    asm volatile("setmaxnreg.dec.sync.aligned.u32 24;");
    const uint32_t sW = base + OFF_W, full = base + OFF_MISC, empty = full + 8 * RING, inbar = full + 16 * RING;
    if (threadIdx.x == 256) {
      mbar_expect_tx(inbar, 32768);
      tma_load_3d(base + OFF_X, &tmX, inbar, 0, tile * 64, 0);
      produce_ff(sW, full, empty, 0, &tmW1a, &tmW1b);
#pragma unroll 1
      for (int m = 0; m < 12; m++) produce(sW, full, empty, 32 + m, &tmWqkv, 128 * (m & 1), 2 * (m >> 1));
    } else if (threadIdx.x >= 288 && threadIdx.x < 296) {
      const int w = threadIdx.x - 288;
      mbar_wait(inbar, 0);
      const uint32_t bytes = wp.bytes[w], per = ((bytes / NTILE) + 127) & ~127u, off = per * tile;
      if (off < bytes) l2_prefetch((const uint8_t*)wp.p[w] + off, min(per, bytes - off));
    }
  } else {
    asm volatile("setmaxnreg.inc.sync.aligned.u32 240;");
    const Ctx c = make_ctx(base);
    if (c.wg == 1) turn_end(c);
    float own[64];
    float a0, b0, a1, b1;
    PROF_MARK(0, 0);
#pragma unroll
    for (int i = 0; i < 8; i++) g_att[tile * 2048 + i * 256 + threadIdx.x] = make_uint4(~0u, ~0u, ~0u, ~0u);
    mbar_wait(c.full + 16 * RING, 0);
    PROF_MARK(0, 1);
    load_half(c, c.sX, own);
    ln_stats(c, own, 0.5f, a0, b0, a1, b1);
    store_half(c, c.sA, own, a0, b0, a1, b1);
    fence_async_smem();
    bar_sync(1, 256);
    PROF_MARK(0, 2);
    ff_block(c, 0, own);
    PROF_MARK(0, 3);
    ln_stats(c, own, 1.f, a0, b0, a1, b1);
    store_half(c, c.sA, own, a0, b0, a1, b1);
    store_half_raw(c, c.sX, own);
    fence_async_smem();
    bar_sync(1, 256);
    PROF_MARK(0, 4);
    if (c.tid == 0) { tma_store_3d(&tmX1st, c.sX + c.wg * 16384, 0, tile * 64, 2 * c.wg); bulk_commit(); }
#pragma unroll 1
    for (int cc = 0; cc < 3; cc++) {
      const int j = 2 * cc + c.wg;
      gemm256<1>(c, own, 32 + 2 * j);
      const float sc = (cc == 0) ? 0.125f * 1.4426950408889634f : 1.f;
      if (c.tid == 0) {
        if (cc == 2) {
          bulk_wait_all();
          if (tile <= 62) cnt_signal(g_cnt1);
          if (tile >= 62) cnt_signal(g_cnt1 + 64);
        } else bulk_wait_read();
      }
      bar_sync(3 + c.wg, 128);
      store_half(c, c.sX, own, sc, 0.f, sc, 0.f);
      fence_async_smem();
      bar_sync(3 + c.wg, 128);
      if (c.tid == 0) { tma_store_3d(&tmQKVst, c.sX + c.wg * 16384, 0, tile * 64, 2 * j); bulk_commit(); }
    }
    PROF_MARK(0, 5);
    if (c.tid == 0) {
      bulk_wait_all();
      if (tile <= 62) cnt_signal(g_cnt1 + 32);
      if (tile >= 62) cnt_signal(g_cnt1 + 96);
    }
    PROF_MARK(0, 6);
  }
}

__global__ void __launch_bounds__(384, 1) k3_tail(const __grid_constant__ CUtensorMap tmX1,
    const __grid_constant__ CUtensorMap tmWo, const __grid_constant__ CUtensorMap tmPw1, const __grid_constant__ CUtensorMap tmPw2,
    const __grid_constant__ CUtensorMap tmW2a, const __grid_constant__ CUtensorMap tmW2b, const __grid_constant__ CUtensorMap tmOut,
    const uint4* __restrict__ dw) {
  extern __shared__ uint8_t smem_raw[];
  const uint32_t base = (smem_u32(smem_raw) + 1023) & ~1023u;
  const int tile = blockIdx.x;
  if (threadIdx.x == 256) {
    prefetch_tmap(&tmX1); prefetch_tmap(&tmWo); prefetch_tmap(&tmPw1); prefetch_tmap(&tmPw2);
    prefetch_tmap(&tmW2a); prefetch_tmap(&tmW2b); prefetch_tmap(&tmOut);
  }
  row_init(base);
  if (threadIdx.x >= 256) {
    asm volatile("setmaxnreg.dec.sync.aligned.u32 24;");
    const uint32_t sW = (base + OFF_W) | 1, full = base + OFF_MISC, empty = full + 8 * RING, inbar = full + 16 * RING;
    if (threadIdx.x == 256) {
#pragma unroll 1
      for (int m = 0; m < 4; m++) produce(sW, full, empty, m, &tmWo, 128 * (m & 1), 2 * (m >> 1));
#pragma unroll 1
      for (int m = 0; m < 8; m++) produce(sW, full, empty, 4 + m, &tmPw1, 128 * (m & 1), 0, 64 * (2 * ((m >> 1) & 1) + (m >> 2)));
#pragma unroll 1
      for (int m = 0; m < 4; m++) produce(sW, full, empty, 12 + m, &tmPw2, 128 * (m & 1), 2 * (m >> 1));
      produce_ff(sW, full, empty, 16, &tmW2a, &tmW2b);
    } else if (threadIdx.x == 288) {
      mbar_expect_tx(inbar, 32768);
      tma_load_3d(base + OFF_X, &tmX1, inbar, 0, tile * 64, 0);
      if (tile == 0) { g_cnt1[0] = 0; g_cnt1[32] = 0; g_cnt1[64] = 0; g_cnt1[96] = 0; }
      pdl_wait();
    }
  } else {
    asm volatile("setmaxnreg.inc.sync.aligned.u32 240;");
    const Ctx c = make_ctx(base, 132 * 64);
    if (c.wg == 1) turn_end(c);
    float own[64];
    float a0, b0, a1, b1;
    PROF_MARK(2, 0);
    {
      uint4 af[16];
      const uint4* ap = g_att + (tile * 4 + (c.tid >> 5)) * 512 + c.lane;
#pragma unroll
      for (int i = 0; i < 16; i++)
        asm volatile("ld.relaxed.gpu.global.v4.u32 {%0,%1,%2,%3}, [%4];" : "=r"(af[i].x), "=r"(af[i].y), "=r"(af[i].z), "=r"(af[i].w) : "l"(ap + i * 32) : "memory");
      mbar_wait(c.full + 16 * RING, 0);
      PROF_MARK(2, 1);
      load_half(c, c.sX, own);
#pragma unroll
      for (int i = 0; i < 16; i++)
        if (max(max(af[i].x, af[i].y), max(af[i].z, af[i].w)) == ~0u) data_poll(ap + i * 32, af[i]);
      __syncwarp();
      PROF_MARK(2, 2);
      const int n = 2 * c.wg;
      uint32_t b = stage_wait(c, n) + ((16384 >> 4) << 16);
      turn_begin(c);
      wg_fence();
#pragma unroll
      for (int kk = 0; kk < 8; kk++) wg_rs_n128_tb1<1>(own, af[kk].x, af[kk].y, af[kk].z, af[kk].w, b + kk * 128);
      wg_commit();
      b = stage_wait(c, n + 1) + ((16384 >> 4) << 16);
      wg_fence();
#pragma unroll
      for (int kk = 0; kk < 8; kk++) wg_rs_n128_tb1<1>(own, af[8 + kk].x, af[8 + kk].y, af[8 + kk].z, af[8 + kk].w, b + kk * 128);
      wg_commit();
      turn_end(c);
      wg_wait<1>(); stage_release(c, n);
      wg_wait<0>(); stage_release(c, n + 1);
    }
    PROF_MARK(2, 3);
    ln_stats(c, own, 0.5f, a0, b0, a1, b1);
    store_half(c, c.sA, own, a0, b0, a1, b1);
    fence_async_smem();
    bar_sync(1, 256);
    PROF_MARK(2, 4);
    uint4 dwr[5];
#pragma unroll
    for (int i = 0; i < 5; i++) dwr[i] = __ldg(dw + i * 32 + c.lane);
    const bool top = c.tid < 8, pub = top || c.tid >= 120;
    uint32_t* halo_out = (uint32_t*)g_halo + (tile * 4 + (top ? (c.tid >> 2) : ((c.tid >> 2) - 28))) * 128 + c.wg * 64 + (c.lane & 3);
#pragma unroll 1
    for (int q = 0; q < 2; q++) {
      float ab[64];
      gemm256<1>(c, ab, 4 + 4 * q + 2 * c.wg);
#pragma unroll
      for (int j = 0; j < 4; j++) {
        float g[8];
#pragma unroll
        for (int i = 0; i < 8; i++) g[i] = fmaf(ab[8 * j + i], tanh_fast(ab[32 + 8 * j + i]), ab[8 * j + i]);
        const uint32_t p0 = pack_bf16(g[0], g[1]), p1 = pack_bf16(g[2], g[3]), p2 = pack_bf16(g[4], g[5]), p3 = pack_bf16(g[6], g[7]);
        if (pub) {
          uint32_t* hp = halo_out + q * 32 + j * 8;
          asm volatile("st.relaxed.gpu.global.u32 [%0], %1;" :: "l"(hp), "r"(top ? p0 : p1) : "memory");
          asm volatile("st.relaxed.gpu.global.u32 [%0], %1;" :: "l"(hp + 4), "r"(top ? p2 : p3) : "memory");
        }
        stsm_x4(c.sX + (2 * c.wg + q) * 8192 + c.frag + (((j * 2 + c.hi) ^ c.rsw) << 4), p0, p1, p2, p3);
      }
    }
    bar_sync(1, 256);
    PROF_MARK(2, 5);
    {
      const int wi = threadIdx.x >> 5;
      const uint32_t col = (c.lane >> 3) * 8192, ch = c.lane & 7;
      uint4 r[12];
#pragma unroll
      for (int i = 0; i < 12; i++) {
        const int row = (wi * 8 - 2 + i) & 63;
        r[i] = lds128(c.sX + col + row * 128 + ((ch ^ (row & 7)) << 4));
      }
      uint32_t w[5][4];
#pragma unroll
      for (int k = 0; k < 5; k++) {
        w[k][0] = bmul2(dwr[k].x, 0x3F003F00u); w[k][1] = bmul2(dwr[k].y, 0x3F003F00u);
        w[k][2] = bmul2(dwr[k].z, 0x3F003F00u); w[k][3] = bmul2(dwr[k].w, 0x3F003F00u);
      }
      auto conv_row = [&](int i) {
        uint32_t o[4];
#pragma unroll
        for (int q = 0; q < 4; q++) {
          uint32_t acc = bmul2(q == 0 ? r[i].x : q == 1 ? r[i].y : q == 2 ? r[i].z : r[i].w, w[0][q]);
#pragma unroll
          for (int k = 1; k < 5; k++) acc = bfma2(q == 0 ? r[i + k].x : q == 1 ? r[i + k].y : q == 2 ? r[i + k].z : r[i + k].w, w[k][q], acc);
          o[q] = pack_bf16(silu_half(bf_lo(acc)), silu_half(bf_hi(acc)));
        }
        sts128(c.sA + col + (wi * 8 + i) * 128 + ((ch ^ i) << 4), make_uint4(o[0], o[1], o[2], o[3]));
      };
      conv_row(2); conv_row(3); conv_row(4); conv_row(5);
      const int R0 = tile * 64 + wi * 8;
      if ((R0 % T_) == 0) { r[0] = make_uint4(0, 0, 0, 0); r[1] = r[0]; }
      else if (wi == 0) { const uint4* sp = g_halo + ((tile - 1) * 4 + 2) * 32 + c.lane; data_poll(sp, r[0]); data_poll(sp + 32, r[1]); }
      if (((R0 + 8) % T_) == 0) { r[10] = make_uint4(0, 0, 0, 0); r[11] = r[10]; }
      else if (wi == 7) { const uint4* sp = g_halo + ((tile + 1) * 4) * 32 + c.lane; data_poll(sp, r[10]); data_poll(sp + 32, r[11]); }
      conv_row(0); conv_row(1); conv_row(6); conv_row(7);
    }
    fence_async_smem();
    bar_sync(1, 256);
    PROF_MARK(2, 6);
    gemm256<0>(c, own, 12 + 2 * c.wg);
    PROF_MARK(2, 7);
    ln_stats(c, own, 0.5f, a0, b0, a1, b1);
    store_half(c, c.sA, own, a0, b0, a1, b1);
    fence_async_smem();
    bar_sync(1, 256);
    PROF_MARK(2, 8);
    ff_block(c, 16, own);
    PROF_MARK(2, 9);
    ln_stats(c, own, 1.f, a0, b0, a1, b1);
    store_half(c, c.sX, own, a0, b0, a1, b1);
    fence_async_smem();
    bar_sync(3 + c.wg, 128);
    if (c.tid == 0) { tma_store_3d(&tmOut, c.sX + c.wg * 16384, 0, tile * 64, 2 * c.wg); bulk_commit(); PROF_MARK(2, 10); bulk_wait_all(); }
    PROF_MARK(2, 11);
  }
}

constexpr int NSTG = 4;
constexpr int KVB = 160 * 128;
constexpr int NKV = T_ / 160;
constexpr int ATT_SMEM = 32768 + NSTG * 2 * KVB + 256 + 1024;

struct AttCtx { uint32_t sKV, full, empty; const CUtensorMap* tmKV; int h, b, wg; };
__device__ __forceinline__ void att_load(const AttCtx& a, int i, int v) {
  const int s = i & (NSTG - 1);
  mbar_expect_tx(a.full + 8 * (s + v * NSTG), KVB);
  tma_load_3d(a.sKV + s * 2 * KVB + v * KVB, a.tmKV, a.full + 8 * (s + v * NSTG), 256 + v * 256 + a.h * 64, i * 160, a.b);
}
__device__ __forceinline__ void att_load_stage(const AttCtx& a, int i) { att_load(a, i, 0); att_load(a, i, 1); }
__device__ __forceinline__ void att_init_bars(const AttCtx& a) {
  for (int i = 0; i < NSTG; i++) { mbar_init(a.full + 8 * i, 1); mbar_init(a.full + 8 * (NSTG + i), 1); mbar_init(a.empty + 8 * i, 4); }
}
__device__ __forceinline__ void att_qk(float (&S)[40], uint32_t dQ, uint32_t kd) {
  wg_ss_n80_tb0<0>(S, dQ, kd);
#pragma unroll
  for (int kk = 1; kk < 4; kk++) wg_ss_n80_tb0<1>(S, dQ + kk * 2, kd + kk * 2);
}
__device__ __forceinline__ void att_pv(float (&O)[32], const uint32_t (&P)[20], uint32_t vd) {
#pragma unroll
  for (int kk = 0; kk < 5; kk++) wg_rs_n64_tb1<1>(O, P[kk * 4], P[kk * 4 + 1], P[kk * 4 + 2], P[kk * 4 + 3], vd + kk * 128);
}
template<bool SAFE>
__device__ __forceinline__ void att_softmax(const float (&S)[40], uint32_t (&P)[20], float (&O)[32], float& m0, float& m1, float& l0, float& l1) {
  if (SAFE) {
    float x0 = fmaxf(S[0], S[1]), x1 = fmaxf(S[2], S[3]);
#pragma unroll
    for (int i = 1; i < 10; i++) { x0 = fmaxf(x0, fmaxf(S[4 * i], S[4 * i + 1])); x1 = fmaxf(x1, fmaxf(S[4 * i + 2], S[4 * i + 3])); }
    x0 = fmaxf(x0, __shfl_xor_sync(0xffffffff, x0, 1)); x1 = fmaxf(x1, __shfl_xor_sync(0xffffffff, x1, 1));
    x0 = fmaxf(x0, __shfl_xor_sync(0xffffffff, x0, 2)); x1 = fmaxf(x1, __shfl_xor_sync(0xffffffff, x1, 2));
    const float n0 = fmaxf(m0, x0), n1 = fmaxf(m1, x1);
    const float f0 = ex2(m0 - n0), f1 = ex2(m1 - n1);
    m0 = n0; m1 = n1; l0 *= f0; l1 *= f1;
#pragma unroll
    for (int i = 0; i < 8; i++) { O[4 * i] *= f0; O[4 * i + 1] *= f0; O[4 * i + 2] *= f1; O[4 * i + 3] *= f1; }
  }
#pragma unroll
  for (int i = 0; i < 10; i++) {
    float p0, p1, p2, p3;
    if (SAFE) { p0 = ex2(S[4 * i] - m0); p1 = ex2(S[4 * i + 1] - m0); p2 = ex2(S[4 * i + 2] - m1); p3 = ex2(S[4 * i + 3] - m1); }
    else { p0 = ex2(S[4 * i]); p1 = ex2(S[4 * i + 1]); p2 = ex2(S[4 * i + 2]); p3 = ex2(S[4 * i + 3]); }
    l0 += p0 + p1; l1 += p2 + p3;
    P[2 * i] = pack_bf16(p0, p1); P[2 * i + 1] = pack_bf16(p2, p3);
  }
}
template<bool SAFE>
__device__ __forceinline__ void att_pass(const AttCtx& a, uint32_t dQ, float (&O)[32], float& l0, float& l1) {
  float S[40];
  uint32_t P[20];
  float m0 = -INFINITY, m1 = -INFINITY;
  l0 = 0.f; l1 = 0.f;
#pragma unroll
  for (int i = 0; i < 32; i++) O[i] = 0.f;
  const uint32_t dKV = dlo(a.sKV, 16);
  constexpr uint32_t STG = 2 * KVB / 16, VOFF = KVB / 16, HALF = 80 * 128 / 16;
  constexpr int UNR = SAFE ? 1 : 4;
  mbar_wait(a.full, 0);
  wg_fence(); att_qk(S, dQ, dKV); wg_commit(); wg_wait<0>();
  att_softmax<SAFE>(S, P, O, m0, m1, l0, l1);
  mbar_wait(a.full + 8 * NSTG, 0);
  wg_fence(); att_pv(O, P, dKV + VOFF); att_qk(S, dQ, dKV + HALF); wg_commit(); wg_wait<0>();
#pragma unroll 1
  for (int it0 = 0; it0 < NKV - 1; it0 += UNR) {
#pragma unroll
    for (int u = 0; u < UNR; u++) {
      const int it = it0 + u;
      const int s = SAFE ? (it & 3) : u, sn = (s + 1) & 3, sp = (s + 3) & 3;
      const uint32_t kb = dKV + s * STG, kn = dKV + sn * STG;
      att_softmax<SAFE>(S, P, O, m0, m1, l0, l1);
      mbar_wait(a.full + 8 * sn, ((it + 1) >> 2) & 1);
      wg_fence(); att_pv(O, P, kb + VOFF + HALF); att_qk(S, dQ, kn); wg_commit(); wg_wait<0>();
      if ((threadIdx.x & 127) == 0) {
        mbar_arrive(a.empty + 8 * s);
        if (a.wg == s && it >= 1 && it - 1 + NSTG < NKV) {
          mbar_wait(a.empty + 8 * sp, ((it - 1) >> 2) & 1);
          att_load_stage(a, it - 1 + NSTG);
        }
      }
      __syncwarp();
      att_softmax<SAFE>(S, P, O, m0, m1, l0, l1);
      mbar_wait(a.full + 8 * (NSTG + sn), ((it + 1) >> 2) & 1);
      wg_fence(); att_pv(O, P, kn + VOFF); att_qk(S, dQ, kn + HALF); wg_commit(); wg_wait<0>();
    }
  }
  att_softmax<SAFE>(S, P, O, m0, m1, l0, l1);
  wg_fence(); att_pv(O, P, dKV + ((NKV - 1) & 3) * STG + VOFF + HALF); wg_commit(); wg_wait<0>();
  l0 += __shfl_xor_sync(0xffffffff, l0, 1); l1 += __shfl_xor_sync(0xffffffff, l1, 1);
  l0 += __shfl_xor_sync(0xffffffff, l0, 2); l1 += __shfl_xor_sync(0xffffffff, l1, 2);
}

__global__ void __launch_bounds__(512, 1) k2_attn(const __grid_constant__ CUtensorMap tmQ, const __grid_constant__ CUtensorMap tmKV) {
  extern __shared__ uint8_t smem_raw[];
  const uint32_t base = (smem_u32(smem_raw) + 1023) & ~1023u;
  const uint32_t sQ = base;
  AttCtx a;
  a.sKV = base + 32768; a.full = a.sKV + NSTG * 2 * KVB; a.empty = a.full + 16 * NSTG; a.tmKV = &tmKV;
  const uint32_t qbar = a.full + 24 * NSTG;
  const int qt = blockIdx.x & 15;
  a.h = (blockIdx.x >> 4) & 3; a.b = blockIdx.x >> 6;
  a.wg = __shfl_sync(0xffffffff, (int)(threadIdx.x >> 7), 0);
  const int lane = threadIdx.x & 31, wq = (threadIdx.x >> 5) & 3;
  PROF_MARK(1, 0);
  if (threadIdx.x == 0) {
    prefetch_tmap(&tmQ); prefetch_tmap(&tmKV);
    att_init_bars(a);
    mbar_init(qbar, 1);
    asm volatile("fence.mbarrier_init.release.cluster;" ::: "memory");
    cnt_wait(g_cnt1 + a.b * 64, 126);
    mbar_expect_tx(qbar, 32768);
    tma_load_3d(sQ, &tmQ, qbar, a.h * 64, qt * 256, a.b);
    for (int i = 0; i < NSTG; i++) att_load(a, i, 0);
  }
  __syncthreads();
  if (threadIdx.x == 384) {
    cnt_wait(g_cnt1 + a.b * 64 + 32, 126);
    for (int i = 0; i < NSTG; i++) att_load(a, i, 1);
    pdl_launch();
  }
  __syncwarp();
  const uint32_t sQw = sQ + a.wg * 8192, dQ = dlo(sQw, 16);
  float O[32], l0, l1;
  PROF_MARK(1, 1);
  mbar_wait(qbar, 0);
  PROF_MARK(1, 2);
  att_pass<false>(a, dQ, O, l0, l1);
  PROF_MARK(1, 3);
  float z = 0.f;
#pragma unroll
  for (int i = 0; i < 32; i++) z = fmaf(O[i], 0.f, z);
  const bool ok = (l0 >= 0x1p-80f) && (l0 <= 0x1p100f) && (l1 >= 0x1p-80f) && (l1 <= 0x1p100f) && (z == 0.f);
  uint32_t wg_bad;
  asm volatile("{\n.reg .pred p, q;\nsetp.eq.u32 p, %1, 0;\nbar.red.or.pred q, %2, 128, p;\nselp.u32 %0, 1, 0, q;\n}\n"
               : "=r"(wg_bad) : "r"((uint32_t)ok), "r"(1 + a.wg) : "memory");
  auto store_out = [&]() {
    const float i0 = 1.f / l0, i1 = 1.f / l1;
    const int row = qt * 256 + a.wg * 64 + wq * 16;
    if (row < T_) {
      uint4* op = g_att + ((a.b * T_ + row) / 16 * 16 + a.h * 4) * 32 + lane;
#pragma unroll
      for (int j = 0; j < 4; j++)
        asm volatile("st.relaxed.gpu.global.v4.u32 [%0], {%1,%2,%3,%4};" :: "l"(op + j * 32),
                     "r"(pack_bf16(O[8 * j] * i0, O[8 * j + 1] * i0)), "r"(pack_bf16(O[8 * j + 2] * i1, O[8 * j + 3] * i1)),
                     "r"(pack_bf16(O[8 * j + 4] * i0, O[8 * j + 5] * i0)), "r"(pack_bf16(O[8 * j + 6] * i1, O[8 * j + 7] * i1)) : "memory");
    }
    PROF_MARK(1, 4);
  };
  if (!wg_bad) store_out();
  if (__syncthreads_or(wg_bad)) {
    if (threadIdx.x == 0) {
      for (int i = 0; i < 3 * NSTG; i++) mbar_inval(a.full + 8 * i);
      att_init_bars(a);
      asm volatile("fence.mbarrier_init.release.cluster;" ::: "memory");
      fence_async_smem();
      for (int i = 0; i < NSTG; i++) att_load_stage(a, i);
    }
    __syncthreads();
    att_pass<true>(a, dQ, O, l0, l1);
    if (wg_bad) store_out();
  }
  if (threadIdx.x == 0) pdl_wait();
  PROF_MARK(1, 5);
}

typedef CUresult (*EncodeFn)(CUtensorMap*, CUtensorMapDataType, cuuint32_t, void*, const cuuint64_t*, const cuuint64_t*, const cuuint32_t*,
                             const cuuint32_t*, CUtensorMapInterleave, CUtensorMapSwizzle, CUtensorMapL2promotion, CUtensorMapFloatOOBfill);

CUtensorMap make_map(EncodeFn enc, const void* p, uint64_t d0, uint64_t d1, uint64_t d2, uint64_t s1, uint64_t s2, uint32_t b1, uint32_t b2) {
  CUtensorMap tm;
  cuuint64_t dims[3] = {d0, d1, d2};
  cuuint64_t strides[2] = {s1, s2};
  cuuint32_t box[3] = {64, b1, b2};
  cuuint32_t es[3] = {1, 1, 1};
  enc(&tm, CU_TENSOR_MAP_DATA_TYPE_BFLOAT16, 3, const_cast<void*>(p), dims, strides, box, es, CU_TENSOR_MAP_INTERLEAVE_NONE,
      CU_TENSOR_MAP_SWIZZLE_128B, CU_TENSOR_MAP_L2_PROMOTION_L2_256B, CU_TENSOR_MAP_FLOAT_OOB_FILL_NONE);
  return tm;
}
CUtensorMap blk_map(EncodeFn enc, const void* p, uint64_t rows, uint64_t cols, uint32_t boxrows, uint32_t boxblks) {
  return make_map(enc, p, 64, rows, cols / 64, cols * 2, 128, boxrows, boxblks);
}
CUtensorMap seq_map(EncodeFn enc, const void* p, uint64_t cols, uint32_t boxrows) {
  return make_map(enc, p, cols, T_, 2, cols * 2, cols * 2 * T_, boxrows, 1);
}

}

extern "C" void kernel_launch(void* const* d_in, const int* in_sizes, int n_in, void* d_out, int out_size) {
  (void)in_sizes; (void)n_in; (void)out_size;
  const void *x = d_in[0], *w1a = d_in[1], *w1b = d_in[2], *wqkv = d_in[3], *wo = d_in[4], *pw1 = d_in[5], *dw = d_in[6], *pw2 = d_in[7],
             *w2a = d_in[8], *w2b = d_in[9];
  void* fn = nullptr;
  cudaDriverEntryPointQueryResult qr;
  cudaGetDriverEntryPoint("cuTensorMapEncodeTiled", &fn, cudaEnableDefault, &qr);
  EncodeFn enc = (EncodeFn)fn;
  void *x1, *qkv;
  cudaGetSymbolAddress(&x1, g_x1);
  cudaGetSymbolAddress(&qkv, g_qkv);
  cudaFuncSetAttribute(k1_ff1_qkv, cudaFuncAttributeMaxDynamicSharedMemorySize, ROW_SMEM);
  cudaFuncSetAttribute(k2_attn, cudaFuncAttributeMaxDynamicSharedMemorySize, ATT_SMEM);
  cudaFuncSetAttribute(k3_tail, cudaFuncAttributeMaxDynamicSharedMemorySize, ROW_SMEM);

  Wptrs wp;
  const void* ws[8] = {w1a, w1b, wqkv, wo, pw1, pw2, w2a, w2b};
  const uint32_t wb[8] = {524288, 524288, 393216, 131072, 262144, 131072, 524288, 524288};
  for (int i = 0; i < 8; i++) { wp.p[i] = ws[i]; wp.bytes[i] = wb[i]; }

  cudaLaunchAttribute pdl[1];
  pdl[0].id = cudaLaunchAttributeProgrammaticStreamSerialization;
  pdl[0].val.programmaticStreamSerializationAllowed = 1;
  cudaLaunchConfig_t cfg = {};
  cfg.stream = cudaStreamPerThread;

  cfg.gridDim = dim3(NTILE); cfg.blockDim = dim3(384); cfg.dynamicSmemBytes = ROW_SMEM; cfg.attrs = nullptr; cfg.numAttrs = 0;
  cudaLaunchKernelEx(&cfg, k1_ff1_qkv, blk_map(enc, x, ROWS, 256, 64, 4), blk_map(enc, w1a, 256, 1024, 256, 1), blk_map(enc, w1b, 1024, 256, 64, 4),
                     blk_map(enc, wqkv, 256, 768, 128, 2), blk_map(enc, x1, ROWS, 256, 64, 2), blk_map(enc, qkv, ROWS, 768, 64, 2), wp);

  cfg.gridDim = dim3(128); cfg.blockDim = dim3(512); cfg.dynamicSmemBytes = ATT_SMEM; cfg.attrs = pdl; cfg.numAttrs = 1;
  cudaLaunchKernelEx(&cfg, k2_attn, seq_map(enc, qkv, 768, 256), seq_map(enc, qkv, 768, 160));

  cfg.gridDim = dim3(NTILE); cfg.blockDim = dim3(384); cfg.dynamicSmemBytes = ROW_SMEM;
  cudaLaunchKernelEx(&cfg, k3_tail, blk_map(enc, x1, ROWS, 256, 64, 4), blk_map(enc, wo, 256, 256, 128, 2),
                     make_map(enc, pw1, 256, 256, 2, 1024, 512, 128, 2), blk_map(enc, pw2, 256, 256, 128, 2), blk_map(enc, w2a, 256, 1024, 256, 1),
                     blk_map(enc, w2b, 1024, 256, 64, 4), blk_map(enc, d_out, ROWS, 256, 64, 2), (const uint4*)dw);
}
```

```cpp
#include <cuda_runtime.h>
#include <cuda_bf16.h>
#include <cuda.h>
#include <stdint.h>

namespace {

constexpr int T_ = 4000;
constexpr int ROWS = 8000;
constexpr int NTILE = 125;

__device__ __nv_bfloat16 g_qkv[ROWS * 768];
__device__ uint4 g_att[(ROWS / 16) * 16 * 32];
__device__ uint4 g_halo[NTILE * 4 * 32];
__device__ uint32_t g_start;
__device__ uint32_t g_cnt1[4 * 32];
__device__ uint32_t g_cnt2[ROWS / 16];

#define PROF_MARK(k, i) do {} while (0)
#define PROF_STG(n, i) do {} while (0)

__device__ __forceinline__ uint32_t smem_u32(const void* p) { return (uint32_t)__cvta_generic_to_shared(p); }
__device__ __forceinline__ void mbar_init(uint32_t bar, uint32_t cnt) { asm volatile("mbarrier.init.shared::cta.b64 [%0], %1;" :: "r"(bar), "r"(cnt) : "memory"); }
__device__ __forceinline__ void mbar_inval(uint32_t bar) { asm volatile("mbarrier.inval.shared::cta.b64 [%0];" :: "r"(bar) : "memory"); }
__device__ __forceinline__ void mbar_expect_tx(uint32_t bar, uint32_t bytes) { asm volatile("mbarrier.arrive.expect_tx.shared::cta.b64 _, [%0], %1;" :: "r"(bar), "r"(bytes) : "memory"); }
__device__ __forceinline__ void mbar_arrive(uint32_t bar) { asm volatile("mbarrier.arrive.shared::cta.b64 _, [%0];" :: "r"(bar) : "memory"); }
__device__ __forceinline__ void mbar_wait(uint32_t bar, uint32_t parity) {
  asm volatile("{\n.reg .pred p;\n.reg .u32 n;\n"
               "mbarrier.try_wait.parity.shared::cta.b64 p, [%0], %1;\n@p bra DONE_%=;\nmov.u32 n, 0;\n"
               "LOOP_%=:\nmbarrier.try_wait.parity.shared::cta.b64 p, [%0], %1;\n@p bra DONE_%=;\n"
               "add.u32 n, n, 1;\nsetp.lt.u32 p, n, 4194304;\n@p bra LOOP_%=;\ntrap;\nDONE_%=:\n}\n" :: "r"(bar), "r"(parity) : "memory");
}
__device__ __forceinline__ void data_poll(const uint4* p, uint4& v) {
  asm volatile("{\n.reg .pred p;\n.reg .u32 n, t;\nmov.u32 n, 0;\n"
               "LOOP_%=:\nld.relaxed.gpu.global.v4.u32 {%0,%1,%2,%3}, [%4];\n"
               "max.u32 t, %0, %1;\nmax.u32 t, t, %2;\nmax.u32 t, t, %3;\nsetp.ne.u32 p, t, 0xFFFFFFFF;\n@p bra DONE_%=;\n"
               "add.u32 n, n, 1;\nsetp.lt.u32 p, n, 16777216;\n@p bra LOOP_%=;\ntrap;\nDONE_%=:\n}\n"
               : "=&r"(v.x), "=&r"(v.y), "=&r"(v.z), "=&r"(v.w) : "l"(p) : "memory");
}
__device__ __forceinline__ void cnt_wait(const uint32_t* p, uint32_t target) {
  asm volatile("{\n.reg .pred p;\n.reg .u32 n, v;\nmov.u32 n, 0;\n"
               "LOOP_%=:\nld.relaxed.gpu.global.u32 v, [%0];\nsub.u32 v, v, %1;\nsetp.ge.s32 p, v, 0;\n@p bra DONE_%=;\n"
               "add.u32 n, n, 1;\nsetp.lt.u32 p, n, 16777216;\n@p bra LOOP_%=;\ntrap;\nDONE_%=:\n}\n" :: "l"(p), "r"(target) : "memory");
}
__device__ __forceinline__ void cnt_signal(uint32_t* p) {
  asm volatile("red.relaxed.gpu.global.add.u32 [%0], 1;" :: "l"(p) : "memory");
}
__device__ __forceinline__ void tma_load_3d(uint32_t dst, const CUtensorMap* tm, uint32_t bar, int c0, int c1, int c2) {
  asm volatile("cp.async.bulk.tensor.3d.shared::cluster.global.mbarrier::complete_tx::bytes [%0], [%1, {%3, %4, %5}], [%2];"
    :: "r"(dst), "l"(tm), "r"(bar), "r"(c0), "r"(c1), "r"(c2) : "memory");
}
__device__ __forceinline__ void tma_store_3d(const CUtensorMap* tm, uint32_t src, int c0, int c1, int c2) {
  asm volatile("cp.async.bulk.tensor.3d.global.shared::cta.bulk_group [%0, {%2, %3, %4}], [%1];" :: "l"(tm), "r"(src), "r"(c0), "r"(c1), "r"(c2) : "memory");
}
__device__ __forceinline__ void bulk_commit() { asm volatile("cp.async.bulk.commit_group;" ::: "memory"); }
__device__ __forceinline__ void bulk_wait_read() { asm volatile("cp.async.bulk.wait_group.read 0;" ::: "memory"); }
__device__ __forceinline__ void bulk_wait_all() { asm volatile("cp.async.bulk.wait_group 0;" ::: "memory"); }
__device__ __forceinline__ void l2_prefetch(const void* p, uint32_t bytes) { asm volatile("cp.async.bulk.prefetch.L2.global [%0], %1;" :: "l"(p), "r"(bytes) : "memory"); }
__device__ __forceinline__ void prefetch_tmap(const CUtensorMap* tm) { asm volatile("prefetch.tensormap [%0];" :: "l"(tm) : "memory"); }
__device__ __forceinline__ void fence_async_smem() { asm volatile("fence.proxy.async.shared::cta;" ::: "memory"); }
__device__ __forceinline__ void wg_fence() { asm volatile("wgmma.fence.sync.aligned;" ::: "memory"); }
__device__ __forceinline__ void wg_commit() { asm volatile("wgmma.commit_group.sync.aligned;" ::: "memory"); }
template<int N> __device__ __forceinline__ void wg_wait() { asm volatile("wgmma.wait_group.sync.aligned %0;" :: "n"(N) : "memory"); }
__device__ __forceinline__ void bar_sync(int id, int n) { asm volatile("bar.sync %0, %1;" :: "r"(id), "r"(n) : "memory"); }
__device__ __forceinline__ void bar_arrive(int id, int n) { asm volatile("bar.arrive %0, %1;" :: "r"(id), "r"(n) : "memory"); }
__device__ __forceinline__ void pdl_wait() { asm volatile("griddepcontrol.wait;" ::: "memory"); }
__device__ __forceinline__ void pdl_launch() { asm volatile("griddepcontrol.launch_dependents;" ::: "memory"); }
__device__ __forceinline__ float ex2(float x) { float y; asm("ex2.approx.ftz.f32 %0, %1;" : "=f"(y) : "f"(x)); return y; }
__device__ __forceinline__ float tanh_fast(float x) { float y; asm("tanh.approx.f32 %0, %1;" : "=f"(y) : "f"(x)); return y; }
__device__ __forceinline__ uint32_t pack_bf16(float lo, float hi) { uint32_t r; asm("cvt.rn.bf16x2.f32 %0, %1, %2;" : "=r"(r) : "f"(hi), "f"(lo)); return r; }
__device__ __forceinline__ uint32_t bmul2(uint32_t a, uint32_t b) { uint32_t d; asm("mul.rn.bf16x2 %0, %1, %2;" : "=r"(d) : "r"(a), "r"(b)); return d; }
__device__ __forceinline__ uint32_t bfma2(uint32_t a, uint32_t b, uint32_t c) { uint32_t d; asm("fma.rn.bf16x2 %0, %1, %2, %3;" : "=r"(d) : "r"(a), "r"(b), "r"(c)); return d; }
__device__ __forceinline__ float bf_lo(uint32_t u) { return __uint_as_float(u << 16); }
__device__ __forceinline__ float bf_hi(uint32_t u) { return __uint_as_float(u & 0xffff0000u); }
__device__ __forceinline__ void ldsm_x4(uint32_t addr, uint32_t& r0, uint32_t& r1, uint32_t& r2, uint32_t& r3) {
  asm volatile("ldmatrix.sync.aligned.m8n8.x4.shared.b16 {%0,%1,%2,%3}, [%4];" : "=r"(r0), "=r"(r1), "=r"(r2), "=r"(r3) : "r"(addr) : "memory");
}
__device__ __forceinline__ void stsm_x4(uint32_t addr, uint32_t r0, uint32_t r1, uint32_t r2, uint32_t r3) {
  asm volatile("stmatrix.sync.aligned.m8n8.x4.shared.b16 [%0], {%1,%2,%3,%4};" :: "r"(addr), "r"(r0), "r"(r1), "r"(r2), "r"(r3) : "memory");
}
__device__ __forceinline__ void sts128(uint32_t addr, uint4 v) { asm volatile("st.shared.v4.b32 [%0], {%1,%2,%3,%4};" :: "r"(addr), "r"(v.x), "r"(v.y), "r"(v.z), "r"(v.w) : "memory"); }
__device__ __forceinline__ uint4 lds128(uint32_t addr) { uint4 v; asm volatile("ld.shared.v4.b32 {%0,%1,%2,%3}, [%4];" : "=r"(v.x), "=r"(v.y), "=r"(v.z), "=r"(v.w) : "r"(addr) : "memory"); return v; }
__device__ __forceinline__ void sts64f(uint32_t addr, float a, float b) { asm volatile("st.shared.v2.f32 [%0], {%1,%2};" :: "r"(addr), "f"(a), "f"(b) : "memory"); }
__device__ __forceinline__ float2 lds64f(uint32_t addr) { float2 v; asm volatile("ld.shared.v2.f32 {%0,%1}, [%2];" : "=f"(v.x), "=f"(v.y) : "r"(addr) : "memory"); return v; }
__device__ __forceinline__ uint32_t dlo(uint32_t addr, uint32_t lbo) { return ((addr & 0x3FFFF) >> 4) | ((lbo >> 4) << 16); }

template<int SD> __device__ __forceinline__ void wg_ss_n128_tb1(float (&d)[64], uint32_t da, uint32_t db) {
  asm volatile("{\n.reg .b64 da, db;\nmov.b64 da, {%64, 0x40000040};\nmov.b64 db, {%65, 0x40000040};\n"
    "wgmma.mma_async.sync.aligned.m64n128k16.f32.bf16.bf16 {%0, %1, %2, %3, %4, %5, %6, %7, %8, %9, %10, %11, %12, %13, %14, %15, %16, %17, %18, %19, %20, %21, %22, %23, %24, %25, %26, %27, %28, %29, %30, %31, %32, %33, %34, %35, %36, %37, %38, %39, %40, %41, %42, %43, %44, %45, %46, %47, %48, %49, %50, %51, %52, %53, %54, %55, %56, %57, %58, %59, %60, %61, %62, %63}, da, db, %66, 1, 1, 0, 1;\n}\n"
    : "+f"(d[0]), "+f"(d[1]), "+f"(d[2]), "+f"(d[3]), "+f"(d[4]), "+f"(d[5]), "+f"(d[6]), "+f"(d[7]), "+f"(d[8]), "+f"(d[9]), "+f"(d[10]), "+f"(d[11]), "+f"(d[12]), "+f"(d[13]), "+f"(d[14]), "+f"(d[15]), "+f"(d[16]), "+f"(d[17]), "+f"(d[18]), "+f"(d[19]), "+f"(d[20]), "+f"(d[21]), "+f"(d[22]), "+f"(d[23]), "+f"(d[24]), "+f"(d[25]), "+f"(d[26]), "+f"(d[27]), "+f"(d[28]), "+f"(d[29]), "+f"(d[30]), "+f"(d[31]), "+f"(d[32]), "+f"(d[33]), "+f"(d[34]), "+f"(d[35]), "+f"(d[36]), "+f"(d[37]), "+f"(d[38]), "+f"(d[39]), "+f"(d[40]), "+f"(d[41]), "+f"(d[42]), "+f"(d[43]), "+f"(d[44]), "+f"(d[45]), "+f"(d[46]), "+f"(d[47]), "+f"(d[48]), "+f"(d[49]), "+f"(d[50]), "+f"(d[51]), "+f"(d[52]), "+f"(d[53]), "+f"(d[54]), "+f"(d[55]), "+f"(d[56]), "+f"(d[57]), "+f"(d[58]), "+f"(d[59]), "+f"(d[60]), "+f"(d[61]), "+f"(d[62]), "+f"(d[63])
    : "r"(da), "r"(db), "n"(SD));
}
template<int SD> __device__ __forceinline__ void wg_rs_n128_tb1(float (&d)[64], uint32_t a0, uint32_t a1, uint32_t a2, uint32_t a3, uint32_t db) {
  asm volatile("{\n.reg .b64 db;\nmov.b64 db, {%68, 0x40000040};\n"
    "wgmma.mma_async.sync.aligned.m64n128k16.f32.bf16.bf16 {%0, %1, %2, %3, %4, %5, %6, %7, %8, %9, %10, %11, %12, %13, %14, %15, %16, %17, %18, %19, %20, %21, %22, %23, %24, %25, %26, %27, %28, %29, %30, %31, %32, %33, %34, %35, %36, %37, %38, %39, %40, %41, %42, %43, %44, %45, %46, %47, %48, %49, %50, %51, %52, %53, %54, %55, %56, %57, %58, %59, %60, %61, %62, %63}, {%64, %65, %66, %67}, db, %69, 1, 1, 1;\n}\n"
    : "+f"(d[0]), "+f"(d[1]), "+f"(d[2]), "+f"(d[3]), "+f"(d[4]), "+f"(d[5]), "+f"(d[6]), "+f"(d[7]), "+f"(d[8]), "+f"(d[9]), "+f"(d[10]), "+f"(d[11]), "+f"(d[12]), "+f"(d[13]), "+f"(d[14]), "+f"(d[15]), "+f"(d[16]), "+f"(d[17]), "+f"(d[18]), "+f"(d[19]), "+f"(d[20]), "+f"(d[21]), "+f"(d[22]), "+f"(d[23]), "+f"(d[24]), "+f"(d[25]), "+f"(d[26]), "+f"(d[27]), "+f"(d[28]), "+f"(d[29]), "+f"(d[30]), "+f"(d[31]), "+f"(d[32]), "+f"(d[33]), "+f"(d[34]), "+f"(d[35]), "+f"(d[36]), "+f"(d[37]), "+f"(d[38]), "+f"(d[39]), "+f"(d[40]), "+f"(d[41]), "+f"(d[42]), "+f"(d[43]), "+f"(d[44]), "+f"(d[45]), "+f"(d[46]), "+f"(d[47]), "+f"(d[48]), "+f"(d[49]), "+f"(d[50]), "+f"(d[51]), "+f"(d[52]), "+f"(d[53]), "+f"(d[54]), "+f"(d[55]), "+f"(d[56]), "+f"(d[57]), "+f"(d[58]), "+f"(d[59]), "+f"(d[60]), "+f"(d[61]), "+f"(d[62]), "+f"(d[63])
    : "r"(a0), "r"(a1), "r"(a2), "r"(a3), "r"(db), "n"(SD));
}
template<int SD> __device__ __forceinline__ void wg_ss_n64_tb1(float (&d)[32], uint32_t da, uint32_t db) {
  asm volatile("{\n.reg .b64 da, db;\nmov.b64 da, {%32, 0x40000040};\nmov.b64 db, {%33, 0x40000040};\n"
    "wgmma.mma_async.sync.aligned.m64n64k16.f32.bf16.bf16 {%0, %1, %2, %3, %4, %5, %6, %7, %8, %9, %10, %11, %12, %13, %14, %15, %16, %17, %18, %19, %20, %21, %22, %23, %24, %25, %26, %27, %28, %29, %30, %31}, da, db, %34, 1, 1, 0, 1;\n}\n"
    : "+f"(d[0]), "+f"(d[1]), "+f"(d[2]), "+f"(d[3]), "+f"(d[4]), "+f"(d[5]), "+f"(d[6]), "+f"(d[7]), "+f"(d[8]), "+f"(d[9]), "+f"(d[10]), "+f"(d[11]), "+f"(d[12]), "+f"(d[13]), "+f"(d[14]), "+f"(d[15]), "+f"(d[16]), "+f"(d[17]), "+f"(d[18]), "+f"(d[19]), "+f"(d[20]), "+f"(d[21]), "+f"(d[22]), "+f"(d[23]), "+f"(d[24]), "+f"(d[25]), "+f"(d[26]), "+f"(d[27]), "+f"(d[28]), "+f"(d[29]), "+f"(d[30]), "+f"(d[31])
    : "r"(da), "r"(db), "n"(SD));
}
template<int SD> __device__ __forceinline__ void wg_ss_n80_tb0(float (&d)[40], uint32_t da, uint32_t db) {
  asm volatile("{\n.reg .b64 da, db;\nmov.b64 da, {%40, 0x40000040};\nmov.b64 db, {%41, 0x40000040};\n"
    "wgmma.mma_async.sync.aligned.m64n80k16.f32.bf16.bf16 {%0, %1, %2, %3, %4, %5, %6, %7, %8, %9, %10, %11, %12, %13, %14, %15, %16, %17, %18, %19, %20, %21, %22, %23, %24, %25, %26, %27, %28, %29, %30, %31, %32, %33, %34, %35, %36, %37, %38, %39}, da, db, %42, 1, 1, 0, 0;\n}\n"
    : "+f"(d[0]), "+f"(d[1]), "+f"(d[2]), "+f"(d[3]), "+f"(d[4]), "+f"(d[5]), "+f"(d[6]), "+f"(d[7]), "+f"(d[8]), "+f"(d[9]), "+f"(d[10]), "+f"(d[11]), "+f"(d[12]), "+f"(d[13]), "+f"(d[14]), "+f"(d[15]), "+f"(d[16]), "+f"(d[17]), "+f"(d[18]), "+f"(d[19]), "+f"(d[20]), "+f"(d[21]), "+f"(d[22]), "+f"(d[23]), "+f"(d[24]), "+f"(d[25]), "+f"(d[26]), "+f"(d[27]), "+f"(d[28]), "+f"(d[29]), "+f"(d[30]), "+f"(d[31]), "+f"(d[32]), "+f"(d[33]), "+f"(d[34]), "+f"(d[35]), "+f"(d[36]), "+f"(d[37]), "+f"(d[38]), "+f"(d[39])
    : "r"(da), "r"(db), "n"(SD));
}
template<int SD> __device__ __forceinline__ void wg_rs_n64_tb1(float (&d)[32], uint32_t a0, uint32_t a1, uint32_t a2, uint32_t a3, uint32_t db) {
  asm volatile("{\n.reg .b64 db;\nmov.b64 db, {%36, 0x40000040};\n"
    "wgmma.mma_async.sync.aligned.m64n64k16.f32.bf16.bf16 {%0, %1, %2, %3, %4, %5, %6, %7, %8, %9, %10, %11, %12, %13, %14, %15, %16, %17, %18, %19, %20, %21, %22, %23, %24, %25, %26, %27, %28, %29, %30, %31}, {%32, %33, %34, %35}, db, %37, 1, 1, 1;\n}\n"
    : "+f"(d[0]), "+f"(d[1]), "+f"(d[2]), "+f"(d[3]), "+f"(d[4]), "+f"(d[5]), "+f"(d[6]), "+f"(d[7]), "+f"(d[8]), "+f"(d[9]), "+f"(d[10]), "+f"(d[11]), "+f"(d[12]), "+f"(d[13]), "+f"(d[14]), "+f"(d[15]), "+f"(d[16]), "+f"(d[17]), "+f"(d[18]), "+f"(d[19]), "+f"(d[20]), "+f"(d[21]), "+f"(d[22]), "+f"(d[23]), "+f"(d[24]), "+f"(d[25]), "+f"(d[26]), "+f"(d[27]), "+f"(d[28]), "+f"(d[29]), "+f"(d[30]), "+f"(d[31])
    : "r"(a0), "r"(a1), "r"(a2), "r"(a3), "r"(db), "n"(SD));
}

constexpr int RING = 5;
constexpr uint32_t STAGE = 32768;
constexpr uint32_t OFF_X = 32768, OFF_W = 65536, OFF_MISC = OFF_W + RING * STAGE;
constexpr int SMEM_BYTES = OFF_MISC + 256 + 1024 + 1024;

struct Ctx {
  uint32_t sA, sX, sW, full, empty, stats;
  uint32_t frag;
  uint32_t rsw;
  uint32_t hi;
  int wg, tid, lane;
  int pk;
};
__device__ __forceinline__ uint32_t stage_wait(const Ctx& c, int n) {
  const int q = n / RING, s = n - q * RING;
  if (c.tid == 0) PROF_STG(n + c.pk, 1);
  mbar_wait(c.full + 8 * s, q & 1);
  if (c.tid == 0) PROF_STG(n + c.pk, 2);
  return dlo(c.sW + s * STAGE, 0);
}
__device__ __forceinline__ void stage_release(const Ctx& c, int n) {
  const int s = n % RING;
  if (c.tid == 0) { mbar_arrive(c.empty + 8 * s); PROF_STG(n + c.pk, 3); }
}
__device__ __forceinline__ void turn_begin(const Ctx& c) { bar_sync(5 + c.wg, 256); }
__device__ __forceinline__ void turn_end(const Ctx& c) { bar_arrive(5 + (c.wg ^ 1), 256); }
template<int FIRST> __device__ __forceinline__ void piece_ss(float (&acc)[64], uint32_t dA, uint32_t dB) {
  dB += (16384 >> 4) << 16;
  wg_ss_n128_tb1<FIRST ? 0 : 1>(acc, dA, dB);
#pragma unroll
  for (int kk = 1; kk < 8; kk++) wg_ss_n128_tb1<1>(acc, dA + (kk >> 2) * 512 + (kk & 3) * 2, dB + kk * 128);
}
__device__ __forceinline__ void ff_g1(float (&h)[32], uint32_t dA, uint32_t dB) {
  wg_ss_n64_tb1<0>(h, dA, dB);
#pragma unroll
  for (int kk = 1; kk < 16; kk++) wg_ss_n64_tb1<1>(h, dA + (kk >> 2) * 512 + (kk & 3) * 2, dB + kk * 128);
}
__device__ __forceinline__ void ff_g2(float (&acc)[64], const uint32_t (&P)[16], uint32_t dB, int half) {
  dB += ((8192 >> 4) << 16) + half * 1024;
#pragma unroll
  for (int kk = 0; kk < 4; kk++) wg_rs_n128_tb1<1>(acc, P[4 * kk], P[4 * kk + 1], P[4 * kk + 2], P[4 * kk + 3], dB + kk * 128);
}
template<int FIRST> __device__ __forceinline__ void gemm256(const Ctx& c, float (&acc)[64], int n) {
  const uint32_t dA = dlo(c.sA, 16);
  uint32_t b = stage_wait(c, n);
  turn_begin(c);
  wg_fence(); piece_ss<FIRST>(acc, dA, b); wg_commit();
  b = stage_wait(c, n + 1);
  wg_fence(); piece_ss<0>(acc, dA + 1024, b); wg_commit();
  turn_end(c);
  wg_wait<1>(); stage_release(c, n);
  wg_wait<0>(); stage_release(c, n + 1);
}
__device__ __forceinline__ uint32_t frag_addr(const Ctx& c, uint32_t tile, int j) {
  return tile + (2 * c.wg + (j >> 2)) * 8192 + c.frag + ((((j & 3) * 2 + c.hi) ^ c.rsw) << 4);
}
__device__ __forceinline__ void load_half(const Ctx& c, uint32_t tile, float (&v)[64]) {
#pragma unroll
  for (int j = 0; j < 8; j++) {
    uint32_t r0, r1, r2, r3;
    ldsm_x4(frag_addr(c, tile, j), r0, r1, r2, r3);
    v[8 * j] = bf_lo(r0); v[8 * j + 1] = bf_hi(r0); v[8 * j + 2] = bf_lo(r1); v[8 * j + 3] = bf_hi(r1);
    v[8 * j + 4] = bf_lo(r2); v[8 * j + 5] = bf_hi(r2); v[8 * j + 6] = bf_lo(r3); v[8 * j + 7] = bf_hi(r3);
  }
}
__device__ __forceinline__ void store_half(const Ctx& c, uint32_t tile, const float (&v)[64], float a0, float b0, float a1, float b1) {
#pragma unroll
  for (int j = 0; j < 8; j++)
    stsm_x4(frag_addr(c, tile, j),
            pack_bf16(fmaf(v[8 * j], a0, b0), fmaf(v[8 * j + 1], a0, b0)), pack_bf16(fmaf(v[8 * j + 2], a1, b1), fmaf(v[8 * j + 3], a1, b1)),
            pack_bf16(fmaf(v[8 * j + 4], a0, b0), fmaf(v[8 * j + 5], a0, b0)), pack_bf16(fmaf(v[8 * j + 6], a1, b1), fmaf(v[8 * j + 7], a1, b1)));
}
__device__ __forceinline__ void store_half_raw(const Ctx& c, uint32_t tile, const float (&v)[64]) {
#pragma unroll
  for (int j = 0; j < 8; j++)
    stsm_x4(frag_addr(c, tile, j), pack_bf16(v[8 * j], v[8 * j + 1]), pack_bf16(v[8 * j + 2], v[8 * j + 3]),
            pack_bf16(v[8 * j + 4], v[8 * j + 5]), pack_bf16(v[8 * j + 6], v[8 * j + 7]));
}
__device__ __forceinline__ void ln_stats(const Ctx& c, const float (&v)[64], float scale, float& a0, float& b0, float& a1, float& b1) {
  float s0 = 0.f, s1 = 0.f, q0 = 0.f, q1 = 0.f, s2 = 0.f, s3 = 0.f, q2 = 0.f, q3 = 0.f;
#pragma unroll
  for (int i = 0; i < 16; i++) {
    s0 += v[4 * i]; q0 = fmaf(v[4 * i], v[4 * i], q0);
    s2 += v[4 * i + 1]; q2 = fmaf(v[4 * i + 1], v[4 * i + 1], q2);
    s1 += v[4 * i + 2]; q1 = fmaf(v[4 * i + 2], v[4 * i + 2], q1);
    s3 += v[4 * i + 3]; q3 = fmaf(v[4 * i + 3], v[4 * i + 3], q3);
  }
  s0 += s2; q0 += q2; s1 += s3; q1 += q3;
  s0 += __shfl_xor_sync(0xffffffff, s0, 1); q0 += __shfl_xor_sync(0xffffffff, q0, 1);
  s1 += __shfl_xor_sync(0xffffffff, s1, 1); q1 += __shfl_xor_sync(0xffffffff, q1, 1);
  s0 += __shfl_xor_sync(0xffffffff, s0, 2); q0 += __shfl_xor_sync(0xffffffff, q0, 2);
  s1 += __shfl_xor_sync(0xffffffff, s1, 2); q1 += __shfl_xor_sync(0xffffffff, q1, 2);
  const uint32_t row = (c.tid >> 5) * 16 + (c.lane >> 2);
  if ((c.lane & 3) == 0) {
    sts64f(c.stats + c.wg * 512 + row * 8, s0, q0);
    sts64f(c.stats + c.wg * 512 + (row + 8) * 8, s1, q1);
  }
  bar_sync(1, 256);
  const float2 o0 = lds64f(c.stats + (c.wg ^ 1) * 512 + row * 8), o1 = lds64f(c.stats + (c.wg ^ 1) * 512 + (row + 8) * 8);
  const float m0 = (s0 + o0.x) * (1.f / 256.f), m1 = (s1 + o1.x) * (1.f / 256.f);
  const float var0 = fmaxf(fmaf(-m0, m0, (q0 + o0.y) * (1.f / 256.f)), 0.f), var1 = fmaxf(fmaf(-m1, m1, (q1 + o1.y) * (1.f / 256.f)), 0.f);
  a0 = rsqrtf(var0 + 1e-5f) * scale; a1 = rsqrtf(var1 + 1e-5f) * scale;
  b0 = -m0 * a0; b1 = -m1 * a1;
}
__device__ __forceinline__ float silu_half(float h) { return fmaf(h, tanh_fast(h), h); }
__device__ __forceinline__ float silu_quarter(float h) { const float q = 0.5f * h; return fmaf(q, tanh_fast(h), q); }
__device__ __forceinline__ void silu_pack(const float (&acc)[32], uint32_t (&P)[16]) {
#pragma unroll
  for (int i = 0; i < 16; i++) P[i] = pack_bf16(silu_quarter(acc[2 * i]), silu_quarter(acc[2 * i + 1]));
}
__device__ __forceinline__ void ff_block(const Ctx& c, int n0, float (&own)[64]) {
  float oth[64], h[32];
  uint32_t P[16];
#pragma unroll
  for (int i = 0; i < 64; i++) oth[i] = 0.f;
  const uint32_t dA = dlo(c.sA, 16);
  {
    const uint32_t b = stage_wait(c, n0 + c.wg);
    turn_begin(c);
    wg_fence(); ff_g1(h, dA, b); wg_commit();
    turn_end(c);
    wg_wait<0>(); stage_release(c, n0 + c.wg);
    silu_pack(h, P);
  }
#pragma unroll 1
  for (int it = 1; it < 8; it++) {
    const int n = n0 + 4 * it - 2 + 2 * c.wg;
    uint32_t b = stage_wait(c, n);
    turn_begin(c);
    wg_fence(); ff_g2(own, P, b, c.wg); ff_g2(oth, P, b, c.wg ^ 1); wg_commit();
    b = stage_wait(c, n + 1);
    wg_fence(); ff_g1(h, dA, b); wg_commit();
    turn_end(c);
    wg_wait<1>(); stage_release(c, n);
    wg_wait<0>(); stage_release(c, n + 1);
    silu_pack(h, P);
  }
  if (c.wg == 0) bar_arrive(2, 256);
  {
    const int n = n0 + 30 + c.wg;
    const uint32_t b = stage_wait(c, n);
    turn_begin(c);
    wg_fence(); ff_g2(oth, P, b, c.wg ^ 1); wg_commit();
    ff_g2(own, P, b, c.wg); wg_commit();
    turn_end(c);
    wg_wait<1>();
    if (c.wg == 1) bar_sync(2, 256);
    const uint32_t e = (c.wg == 0 ? c.sX : c.sA) + c.tid * 16;
#pragma unroll
    for (int i = 0; i < 16; i++)
      sts128(e + i * 2048, make_uint4(__float_as_uint(oth[4 * i]), __float_as_uint(oth[4 * i + 1]), __float_as_uint(oth[4 * i + 2]), __float_as_uint(oth[4 * i + 3])));
    wg_wait<0>(); stage_release(c, n);
  }
  bar_sync(1, 256);
  const uint32_t e = (c.wg == 0 ? c.sA : c.sX) + c.tid * 16;
#pragma unroll
  for (int i = 0; i < 16; i++) {
    const uint4 u = lds128(e + i * 2048);
    own[4 * i] += __uint_as_float(u.x); own[4 * i + 1] += __uint_as_float(u.y);
    own[4 * i + 2] += __uint_as_float(u.z); own[4 * i + 3] += __uint_as_float(u.w);
  }
}
__device__ __forceinline__ void produce(uint32_t sW, uint32_t full, uint32_t empty, int n, const CUtensorMap* tm, int k0, int nblk, int c0 = 0) {
  const int q = n / RING, s = n - q * RING;
  mbar_wait(empty + 8 * s, (q & 1) ^ 1);
  PROF_STG(n + ((sW & 1) ? 132 * 64 : 0), 0);
  sW &= ~1u;
  mbar_expect_tx(full + 8 * s, STAGE);
  tma_load_3d(sW + s * STAGE, tm, full + 8 * s, c0, k0, nblk);
}
__device__ __forceinline__ void produce_ff(uint32_t sW, uint32_t full, uint32_t empty, int n0, const CUtensorMap* tmA, const CUtensorMap* tmB) {
#pragma unroll 1
  for (int m = 0; m < 32; m++) {
    int is2, j;
    if (m < 2) { is2 = 0; j = m; }
    else if (m == 31) { is2 = 1; j = 15; }
    else { const int q = m - 2; is2 = !(q & 1); j = (q >> 1) + (is2 ? 0 : 2); }
    if (is2) produce(sW, full, empty, n0 + m, tmB, 64 * j, 0);
    else produce(sW, full, empty, n0 + m, tmA, 0, j);
  }
}
__device__ __forceinline__ Ctx make_ctx(uint32_t base, int pk = 0) {
  Ctx c; c.pk = pk;
  c.sA = base; c.sX = base + OFF_X; c.sW = base + OFF_W;
  c.full = base + OFF_MISC; c.empty = c.full + 8 * RING; c.stats = base + OFF_MISC + 256;
  c.wg = __shfl_sync(0xffffffff, (int)(threadIdx.x >> 7), 0);
  c.tid = threadIdx.x & 127; c.lane = threadIdx.x & 31;
  const uint32_t r = (c.tid >> 5) * 16 + (c.lane & 7) + ((c.lane >> 3) & 1) * 8;
  c.frag = r * 128; c.rsw = r & 7; c.hi = c.lane >> 4;
  return c;
}

constexpr int NSTG = 4;
constexpr int KVB = 160 * 128;
constexpr int NKV = T_ / 160;
static_assert(NSTG * 2 * KVB == RING * STAGE, "the K/V ring reuses the weight ring");

struct AttCtx { uint32_t sKV, full, empty; const CUtensorMap* tmKV; int h, b, wg; };
__device__ __forceinline__ void att_load(const AttCtx& a, int i, int v) {
  const int s = i & (NSTG - 1);
  mbar_expect_tx(a.full + 8 * (s + v * NSTG), KVB);
  tma_load_3d(a.sKV + s * 2 * KVB + v * KVB, a.tmKV, a.full + 8 * (s + v * NSTG), 256 + v * 256 + a.h * 64, i * 160, a.b);
}
__device__ __forceinline__ void att_load_stage(const AttCtx& a, int i) { att_load(a, i, 0); att_load(a, i, 1); }
__device__ __forceinline__ void att_init_bars(const AttCtx& a) {
  for (int i = 0; i < NSTG; i++) { mbar_init(a.full + 8 * i, 1); mbar_init(a.full + 8 * (NSTG + i), 1); mbar_init(a.empty + 8 * i, 4); }
}
__device__ __forceinline__ void att_qk(float (&S)[40], uint32_t dQ, uint32_t kd) {
  wg_ss_n80_tb0<0>(S, dQ, kd);
#pragma unroll
  for (int kk = 1; kk < 4; kk++) wg_ss_n80_tb0<1>(S, dQ + kk * 2, kd + kk * 2);
}
__device__ __forceinline__ void att_pv(float (&O)[32], const uint32_t (&P)[20], uint32_t vd) {
#pragma unroll
  for (int kk = 0; kk < 5; kk++) wg_rs_n64_tb1<1>(O, P[kk * 4], P[kk * 4 + 1], P[kk * 4 + 2], P[kk * 4 + 3], vd + kk * 128);
}
template<bool SAFE>
__device__ __forceinline__ void att_softmax(const float (&S)[40], uint32_t (&P)[20], float (&O)[32], float& m0, float& m1, float& l0, float& l1) {
  if (SAFE) {
    float x0 = fmaxf(S[0], S[1]), x1 = fmaxf(S[2], S[3]);
#pragma unroll
    for (int i = 1; i < 10; i++) { x0 = fmaxf(x0, fmaxf(S[4 * i], S[4 * i + 1])); x1 = fmaxf(x1, fmaxf(S[4 * i + 2], S[4 * i + 3])); }
    x0 = fmaxf(x0, __shfl_xor_sync(0xffffffff, x0, 1)); x1 = fmaxf(x1, __shfl_xor_sync(0xffffffff, x1, 1));
    x0 = fmaxf(x0, __shfl_xor_sync(0xffffffff, x0, 2)); x1 = fmaxf(x1, __shfl_xor_sync(0xffffffff, x1, 2));
    const float n0 = fmaxf(m0, x0), n1 = fmaxf(m1, x1);
    const float f0 = ex2(m0 - n0), f1 = ex2(m1 - n1);
    m0 = n0; m1 = n1; l0 *= f0; l1 *= f1;
#pragma unroll
    for (int i = 0; i < 8; i++) { O[4 * i] *= f0; O[4 * i + 1] *= f0; O[4 * i + 2] *= f1; O[4 * i + 3] *= f1; }
  }
#pragma unroll
  for (int i = 0; i < 10; i++) {
    float p0, p1, p2, p3;
    if (SAFE) { p0 = ex2(S[4 * i] - m0); p1 = ex2(S[4 * i + 1] - m0); p2 = ex2(S[4 * i + 2] - m1); p3 = ex2(S[4 * i + 3] - m1); }
    else { p0 = ex2(S[4 * i]); p1 = ex2(S[4 * i + 1]); p2 = ex2(S[4 * i + 2]); p3 = ex2(S[4 * i + 3]); }
    l0 += p0 + p1; l1 += p2 + p3;
    P[2 * i] = pack_bf16(p0, p1); P[2 * i + 1] = pack_bf16(p2, p3);
  }
}
template<bool SAFE>
__device__ __forceinline__ void att_pass(const AttCtx& a, uint32_t dQ, float (&O)[32], float& l0, float& l1) {
  float S[40];
  uint32_t P[20];
  float m0 = -INFINITY, m1 = -INFINITY;
  l0 = 0.f; l1 = 0.f;
#pragma unroll
  for (int i = 0; i < 32; i++) O[i] = 0.f;
  const uint32_t dKV = dlo(a.sKV, 16);
  constexpr uint32_t STG = 2 * KVB / 16, VOFF = KVB / 16, HALF = 80 * 128 / 16;
  constexpr int UNR = SAFE ? 1 : 4;
  mbar_wait(a.full, 0);
  wg_fence(); att_qk(S, dQ, dKV); wg_commit(); wg_wait<0>();
  att_softmax<SAFE>(S, P, O, m0, m1, l0, l1);
  mbar_wait(a.full + 8 * NSTG, 0);
  wg_fence(); att_pv(O, P, dKV + VOFF); att_qk(S, dQ, dKV + HALF); wg_commit(); wg_wait<0>();
#pragma unroll 1
  for (int it0 = 0; it0 < NKV - 1; it0 += UNR) {
#pragma unroll
    for (int u = 0; u < UNR; u++) {
      const int it = it0 + u;
      const int s = SAFE ? (it & 3) : u, sn = (s + 1) & 3, sp = (s + 3) & 3;
      const uint32_t kb = dKV + s * STG, kn = dKV + sn * STG;
      att_softmax<SAFE>(S, P, O, m0, m1, l0, l1);
      mbar_wait(a.full + 8 * sn, ((it + 1) >> 2) & 1);
      wg_fence(); att_pv(O, P, kb + VOFF + HALF); att_qk(S, dQ, kn); wg_commit(); wg_wait<0>();
      if ((threadIdx.x & 127) == 0) {
        mbar_arrive(a.empty + 8 * s);
        if (a.wg == s && it >= 1 && it - 1 + NSTG < NKV) {
          mbar_wait(a.empty + 8 * sp, ((it - 1) >> 2) & 1);
          att_load_stage(a, it - 1 + NSTG);
        }
      }
      __syncwarp();
      att_softmax<SAFE>(S, P, O, m0, m1, l0, l1);
      mbar_wait(a.full + 8 * (NSTG + sn), ((it + 1) >> 2) & 1);
      wg_fence(); att_pv(O, P, kn + VOFF); att_qk(S, dQ, kn + HALF); wg_commit(); wg_wait<0>();
    }
  }
  att_softmax<SAFE>(S, P, O, m0, m1, l0, l1);
  wg_fence(); att_pv(O, P, dKV + ((NKV - 1) & 3) * STG + VOFF + HALF); wg_commit(); wg_wait<0>();
  l0 += __shfl_xor_sync(0xffffffff, l0, 1); l1 += __shfl_xor_sync(0xffffffff, l1, 1);
  l0 += __shfl_xor_sync(0xffffffff, l0, 2); l1 += __shfl_xor_sync(0xffffffff, l1, 2);
}

struct Wptrs { const void* p[8]; uint32_t bytes[8]; };
struct Maps { CUtensorMap X, W1a, W1b, Wqkv, QKVst, Q, KV, Wo, Pw1, Pw2, W2a, W2b, Out; };

constexpr uint32_t B_FULL = 0, B_EMPTY = 8 * RING, B_X = 16 * RING, B_ADONE = B_X + 8, B_Q = B_X + 16, B_ATT = B_X + 24;

__global__ void __launch_bounds__(512, 1) conformer_kernel(const __grid_constant__ Maps tm, const __grid_constant__ Wptrs wp, const uint4* __restrict__ dw) {
  extern __shared__ uint8_t smem_raw[];
  const uint32_t base = (smem_u32(smem_raw) + 1023) & ~1023u, misc = base + OFF_MISC;
  const int tile = blockIdx.x;
  const bool has_tile = tile < NTILE;
  const int wg = __shfl_sync(0xffffffff, (int)(threadIdx.x >> 7), 0);
  AttCtx a;
  a.sKV = base + OFF_W; a.full = misc + B_ATT; a.empty = a.full + 16 * NSTG; a.tmKV = &tm.KV;
  a.h = (blockIdx.x >> 4) & 3; a.b = blockIdx.x >> 6; a.wg = wg;
  const int qt = blockIdx.x & 15;

  if (threadIdx.x == 256) {
    mbar_init(misc + B_X, 1);
    asm volatile("fence.mbarrier_init.release.cluster;" ::: "memory");
    if (has_tile) { mbar_expect_tx(misc + B_X, 32768); tma_load_3d(base + OFF_X, &tm.X, misc + B_X, 0, tile * 64, 0); }
    for (int i = 0; i < RING; i++) { mbar_init(misc + B_FULL + 8 * i, 1); mbar_init(misc + B_EMPTY + 8 * i, 1); }
    mbar_init(misc + B_ADONE, 2);
    mbar_init(misc + B_Q, 1);
    att_init_bars(a);
    asm volatile("fence.mbarrier_init.release.cluster;" ::: "memory");
  } else if (threadIdx.x == 288) {
    const uint32_t e = atomicAdd(&g_start, 1) >> 7;
    asm volatile("st.shared.u32 [%0], %1;" :: "r"(misc + 248), "r"(e + 1) : "memory");
  } else if (threadIdx.x >= 320 && threadIdx.x < 333) {
    prefetch_tmap(&tm.X + (threadIdx.x - 320));
  }
  __syncthreads();
  uint32_t epoch;
  asm volatile("ld.shared.u32 %0, [%1];" : "=r"(epoch) : "r"(misc + 248) : "memory");

  if (wg >= 2) {
    asm volatile("setmaxnreg.dec.sync.aligned.u32 24;");
    const uint32_t sW = base + OFF_W, full = misc + B_FULL, empty = misc + B_EMPTY;
    if (threadIdx.x == 256) {
      if (has_tile) {
        produce_ff(sW, full, empty, 0, &tm.W1a, &tm.W1b);
#pragma unroll 1
        for (int m = 0; m < 12; m++) produce(sW, full, empty, 32 + m, &tm.Wqkv, 128 * (m & 1), 2 * (m >> 1));
        mbar_wait(misc + B_ADONE, 0);
      }
      cnt_wait(g_cnt1 + a.b * 64, 126 * epoch);
      mbar_expect_tx(misc + B_Q, 32768);
      tma_load_3d(base, &tm.Q, misc + B_Q, a.h * 64, qt * 256, a.b);
      for (int i = 0; i < NSTG; i++) att_load(a, i, 0);
    } else if (threadIdx.x == 384) {
      if (has_tile) mbar_wait(misc + B_ADONE, 0);
      cnt_wait(g_cnt1 + a.b * 64 + 32, 126 * epoch);
      for (int i = 0; i < NSTG; i++) att_load(a, i, 1);
    } else if (has_tile && threadIdx.x >= 288 && threadIdx.x < 296) {
      const int w = threadIdx.x - 288;
      mbar_wait(misc + B_X, 0);
      const uint32_t bytes = wp.bytes[w], per = ((bytes / NTILE) + 127) & ~127u, off = per * tile;
      if (off < bytes) l2_prefetch((const uint8_t*)wp.p[w] + off, min(per, bytes - off));
    } else if (has_tile && threadIdx.x >= 416) {
      mbar_wait(full, 0);
      const int t = threadIdx.x - 416;
#pragma unroll 2
      for (int i = t; i < 2048; i += 96) g_att[tile * 2048 + i] = make_uint4(~0u, ~0u, ~0u, ~0u);
      g_halo[tile * 128 + t] = make_uint4(~0u, ~0u, ~0u, ~0u);
      if (t < 32) g_halo[tile * 128 + 96 + t] = make_uint4(~0u, ~0u, ~0u, ~0u);
    }
    __syncwarp();
    asm volatile("setmaxnreg.inc.sync.aligned.u32 128;");
  } else {
    asm volatile("setmaxnreg.inc.sync.aligned.u32 232;");
    if (has_tile) {
      const Ctx c = make_ctx(base);
      if (c.wg == 1) turn_end(c);
      float own[64];
      float a0, b0, a1, b1;
      PROF_MARK(0, 0);
      mbar_wait(misc + B_X, 0);
      PROF_MARK(0, 1);
      load_half(c, c.sX, own);
      ln_stats(c, own, 0.5f, a0, b0, a1, b1);
      store_half(c, c.sA, own, a0, b0, a1, b1);
      fence_async_smem();
      bar_sync(1, 256);
      PROF_MARK(0, 2);
      ff_block(c, 0, own);
      PROF_MARK(0, 3);
      ln_stats(c, own, 1.f, a0, b0, a1, b1);
      store_half(c, c.sA, own, a0, b0, a1, b1);
      fence_async_smem();
      bar_sync(1, 256);
      PROF_MARK(0, 4);
#pragma unroll 1
      for (int cc = 0; cc < 3; cc++) {
        float acc[64];
        const int j = 2 * cc + c.wg;
        gemm256<1>(c, acc, 32 + 2 * j);
        const float sc = (cc == 0) ? 0.125f * 1.4426950408889634f : 1.f;
        if (c.tid == 0) {
          if (cc == 2) {
            mbar_arrive(misc + B_ADONE);
            bulk_wait_all();
            if (tile <= 62) cnt_signal(g_cnt1);
            if (tile >= 62) cnt_signal(g_cnt1 + 64);
          } else bulk_wait_read();
        }
        bar_sync(3 + c.wg, 128);
        store_half(c, c.sX, acc, sc, 0.f, sc, 0.f);
        fence_async_smem();
        bar_sync(3 + c.wg, 128);
        if (c.tid == 0) { tma_store_3d(&tm.QKVst, c.sX + c.wg * 16384, 0, tile * 64, 2 * j); bulk_commit(); }
      }
      PROF_MARK(0, 5);
      if (c.tid == 0) bulk_wait_read();
      bar_sync(3 + c.wg, 128);
      store_half_raw(c, c.sX, own);
    }
    asm volatile("setmaxnreg.dec.sync.aligned.u32 128;");
    if (has_tile && (threadIdx.x & 127) == 0) {
      bulk_wait_all();
      if (tile <= 62) cnt_signal(g_cnt1 + 32);
      if (tile >= 62) cnt_signal(g_cnt1 + 96);
    }
    __syncwarp();
    PROF_MARK(0, 6);
  }

  {
    const int lane = threadIdx.x & 31, wq = (threadIdx.x >> 5) & 3;
    const uint32_t dQ = dlo(base + wg * 8192, 16);
    float O[32], l0, l1;
    PROF_MARK(1, 1);
    mbar_wait(misc + B_Q, 0);
    PROF_MARK(1, 2);
    att_pass<false>(a, dQ, O, l0, l1);
    PROF_MARK(1, 3);
    float z = 0.f;
#pragma unroll
    for (int i = 0; i < 32; i++) z = fmaf(O[i], 0.f, z);
    const bool ok = (l0 >= 0x1p-80f) && (l0 <= 0x1p100f) && (l1 >= 0x1p-80f) && (l1 <= 0x1p100f) && (z == 0.f);
    const bool warp_bad = !__all_sync(0xffffffff, ok);
    auto store_out = [&]() {
      const float i0 = 1.f / l0, i1 = 1.f / l1;
      const int row = qt * 256 + wg * 64 + wq * 16;
      if (row < T_) {
        const int slab = (a.b * T_ + row) / 16;
        uint4* op = g_att + (slab * 16 + a.h * 4) * 32 + lane;
#pragma unroll
        for (int j = 0; j < 4; j++)
          asm volatile("st.relaxed.gpu.global.v4.u32 [%0], {%1,%2,%3,%4};" :: "l"(op + j * 32),
                       "r"(pack_bf16(O[8 * j] * i0, O[8 * j + 1] * i0)), "r"(pack_bf16(O[8 * j + 2] * i1, O[8 * j + 3] * i1)),
                       "r"(pack_bf16(O[8 * j + 4] * i0, O[8 * j + 5] * i0)), "r"(pack_bf16(O[8 * j + 6] * i1, O[8 * j + 7] * i1)) : "memory");
        __syncwarp();
        if (lane == 0) cnt_signal(g_cnt2 + slab);
      }
      PROF_MARK(1, 4);
    };
    if (!warp_bad) store_out();
    if (__syncthreads_or(warp_bad)) {
      if (threadIdx.x == 0) {
        for (int i = 0; i < 3 * NSTG; i++) mbar_inval(a.full + 8 * i);
        att_init_bars(a);
        asm volatile("fence.mbarrier_init.release.cluster;" ::: "memory");
        fence_async_smem();
        for (int i = 0; i < NSTG; i++) att_load_stage(a, i);
      }
      __syncthreads();
      att_pass<true>(a, dQ, O, l0, l1);
      if (warp_bad) store_out();
      __syncthreads();
    }
    PROF_MARK(1, 5);
  }
  if (!has_tile) return;

  constexpr int NC = 44;
  if (wg >= 2) {
    asm volatile("setmaxnreg.dec.sync.aligned.u32 24;");
    if (threadIdx.x == 256) {
      const uint32_t sW = base + OFF_W, full = misc + B_FULL, empty = misc + B_EMPTY;
#pragma unroll 1
      for (int m = 0; m < 4; m++) produce(sW, full, empty, NC + m, &tm.Wo, 128 * (m & 1), 2 * (m >> 1));
#pragma unroll 1
      for (int m = 0; m < 8; m++) produce(sW, full, empty, NC + 4 + m, &tm.Pw1, 128 * (m & 1), 0, 64 * (2 * ((m >> 1) & 1) + (m >> 2)));
#pragma unroll 1
      for (int m = 0; m < 4; m++) produce(sW, full, empty, NC + 12 + m, &tm.Pw2, 128 * (m & 1), 2 * (m >> 1));
      produce_ff(sW, full, empty, NC + 16, &tm.W2a, &tm.W2b);
    }
  } else {
    asm volatile("setmaxnreg.inc.sync.aligned.u32 232;");
    const Ctx c = make_ctx(base);
    float own[64];
    float a0, b0, a1, b1;
    PROF_MARK(2, 0);
    load_half(c, c.sX, own);
    {
      uint4 af[16];
      const int slab = tile * 4 + (c.tid >> 5);
      const uint4* ap = g_att + slab * 512 + c.lane;
      if (c.lane == 0) cnt_wait(g_cnt2 + slab, 4 * epoch);
      __syncwarp();
      PROF_MARK(2, 1);
      for (uint32_t n = 0; n < (1u << 24); n++) {
        bool any = false;
#pragma unroll
        for (int i = 0; i < 16; i++)
          asm volatile("ld.relaxed.gpu.global.v4.u32 {%0,%1,%2,%3}, [%4];" : "=r"(af[i].x), "=r"(af[i].y), "=r"(af[i].z), "=r"(af[i].w) : "l"(ap + i * 32) : "memory");
#pragma unroll
        for (int i = 0; i < 16; i++) any |= max(max(af[i].x, af[i].y), max(af[i].z, af[i].w)) == ~0u;
        if (!__any_sync(0xffffffff, any)) break;
      }
      PROF_MARK(2, 2);
      const int n = NC + 2 * c.wg;
      uint32_t b = stage_wait(c, n) + ((16384 >> 4) << 16);
      turn_begin(c);
      wg_fence();
#pragma unroll
      for (int kk = 0; kk < 8; kk++) wg_rs_n128_tb1<1>(own, af[kk].x, af[kk].y, af[kk].z, af[kk].w, b + kk * 128);
      wg_commit();
      b = stage_wait(c, n + 1) + ((16384 >> 4) << 16);
      wg_fence();
#pragma unroll
      for (int kk = 0; kk < 8; kk++) wg_rs_n128_tb1<1>(own, af[8 + kk].x, af[8 + kk].y, af[8 + kk].z, af[8 + kk].w, b + kk * 128);
      wg_commit();
      turn_end(c);
      wg_wait<1>(); stage_release(c, n);
      wg_wait<0>(); stage_release(c, n + 1);
    }
    PROF_MARK(2, 3);
    ln_stats(c, own, 0.5f, a0, b0, a1, b1);
    store_half(c, c.sA, own, a0, b0, a1, b1);
    fence_async_smem();
    bar_sync(1, 256);
    PROF_MARK(2, 4);
    uint4 dwr[5];
#pragma unroll
    for (int i = 0; i < 5; i++) dwr[i] = __ldg(dw + i * 32 + c.lane);
    const bool top = c.tid < 8, pub = top || c.tid >= 120;
    uint32_t* halo_out = (uint32_t*)g_halo + (tile * 4 + (top ? (c.tid >> 2) : ((c.tid >> 2) - 28))) * 128 + c.wg * 64 + (c.lane & 3);
#pragma unroll 1
    for (int q = 0; q < 2; q++) {
      float ab[64];
      gemm256<1>(c, ab, NC + 4 + 4 * q + 2 * c.wg);
#pragma unroll
      for (int j = 0; j < 4; j++) {
        float g[8];
#pragma unroll
        for (int i = 0; i < 8; i++) g[i] = fmaf(ab[8 * j + i], tanh_fast(ab[32 + 8 * j + i]), ab[8 * j + i]);
        const uint32_t p0 = pack_bf16(g[0], g[1]), p1 = pack_bf16(g[2], g[3]), p2 = pack_bf16(g[4], g[5]), p3 = pack_bf16(g[6], g[7]);
        if (pub) {
          uint32_t* hp = halo_out + q * 32 + j * 8;
          asm volatile("st.relaxed.gpu.global.u32 [%0], %1;" :: "l"(hp), "r"(top ? p0 : p1) : "memory");
          asm volatile("st.relaxed.gpu.global.u32 [%0], %1;" :: "l"(hp + 4), "r"(top ? p2 : p3) : "memory");
        }
        stsm_x4(c.sX + (2 * c.wg + q) * 8192 + c.frag + (((j * 2 + c.hi) ^ c.rsw) << 4), p0, p1, p2, p3);
      }
    }
    bar_sync(1, 256);
    PROF_MARK(2, 5);
    {
      const int wi = threadIdx.x >> 5;
      const uint32_t col = (c.lane >> 3) * 8192, ch = c.lane & 7;
      uint4 r[12];
#pragma unroll
      for (int i = 0; i < 12; i++) {
        const int row = (wi * 8 - 2 + i) & 63;
        r[i] = lds128(c.sX + col + row * 128 + ((ch ^ (row & 7)) << 4));
      }
      uint32_t w[5][4];
#pragma unroll
      for (int k = 0; k < 5; k++) {
        w[k][0] = bmul2(dwr[k].x, 0x3F003F00u); w[k][1] = bmul2(dwr[k].y, 0x3F003F00u);
        w[k][2] = bmul2(dwr[k].z, 0x3F003F00u); w[k][3] = bmul2(dwr[k].w, 0x3F003F00u);
      }
      auto conv_row = [&](int i) {
        uint32_t o[4];
#pragma unroll
        for (int q = 0; q < 4; q++) {
          uint32_t acc = bmul2(q == 0 ? r[i].x : q == 1 ? r[i].y : q == 2 ? r[i].z : r[i].w, w[0][q]);
#pragma unroll
          for (int k = 1; k < 5; k++) acc = bfma2(q == 0 ? r[i + k].x : q == 1 ? r[i + k].y : q == 2 ? r[i + k].z : r[i + k].w, w[k][q], acc);
          o[q] = pack_bf16(silu_half(bf_lo(acc)), silu_half(bf_hi(acc)));
        }
        sts128(c.sA + col + (wi * 8 + i) * 128 + ((ch ^ i) << 4), make_uint4(o[0], o[1], o[2], o[3]));
      };
      conv_row(2); conv_row(3); conv_row(4); conv_row(5);
      const int R0 = tile * 64 + wi * 8;
      if ((R0 % T_) == 0) { r[0] = make_uint4(0, 0, 0, 0); r[1] = r[0]; }
      else if (wi == 0) { const uint4* sp = g_halo + ((tile - 1) * 4 + 2) * 32 + c.lane; data_poll(sp, r[0]); data_poll(sp + 32, r[1]); }
      if (((R0 + 8) % T_) == 0) { r[10] = make_uint4(0, 0, 0, 0); r[11] = r[10]; }
      else if (wi == 7) { const uint4* sp = g_halo + ((tile + 1) * 4) * 32 + c.lane; data_poll(sp, r[10]); data_poll(sp + 32, r[11]); }
      conv_row(0); conv_row(1); conv_row(6); conv_row(7);
    }
    fence_async_smem();
    bar_sync(1, 256);
    PROF_MARK(2, 6);
    gemm256<0>(c, own, NC + 12 + 2 * c.wg);
    PROF_MARK(2, 7);
    ln_stats(c, own, 0.5f, a0, b0, a1, b1);
    store_half(c, c.sA, own, a0, b0, a1, b1);
    fence_async_smem();
    bar_sync(1, 256);
    PROF_MARK(2, 8);
    ff_block(c, NC + 16, own);
    PROF_MARK(2, 9);
    ln_stats(c, own, 1.f, a0, b0, a1, b1);
    store_half(c, c.sX, own, a0, b0, a1, b1);
    fence_async_smem();
    bar_sync(3 + c.wg, 128);
    if (c.tid == 0) { tma_store_3d(&tm.Out, c.sX + c.wg * 16384, 0, tile * 64, 2 * c.wg); bulk_commit(); PROF_MARK(2, 10); bulk_wait_all(); }
    PROF_MARK(2, 11);
  }
}

typedef CUresult (*EncodeFn)(CUtensorMap*, CUtensorMapDataType, cuuint32_t, void*, const cuuint64_t*, const cuuint64_t*, const cuuint32_t*,
                             const cuuint32_t*, CUtensorMapInterleave, CUtensorMapSwizzle, CUtensorMapL2promotion, CUtensorMapFloatOOBfill);

CUtensorMap make_map(EncodeFn enc, const void* p, uint64_t d0, uint64_t d1, uint64_t d2, uint64_t s1, uint64_t s2, uint32_t b1, uint32_t b2) {
  CUtensorMap tm;
  cuuint64_t dims[3] = {d0, d1, d2};
  cuuint64_t strides[2] = {s1, s2};
  cuuint32_t box[3] = {64, b1, b2};
  cuuint32_t es[3] = {1, 1, 1};
  enc(&tm, CU_TENSOR_MAP_DATA_TYPE_BFLOAT16, 3, const_cast<void*>(p), dims, strides, box, es, CU_TENSOR_MAP_INTERLEAVE_NONE,
      CU_TENSOR_MAP_SWIZZLE_128B, CU_TENSOR_MAP_L2_PROMOTION_L2_256B, CU_TENSOR_MAP_FLOAT_OOB_FILL_NONE);
  return tm;
}
CUtensorMap blk_map(EncodeFn enc, const void* p, uint64_t rows, uint64_t cols, uint32_t boxrows, uint32_t boxblks) {
  return make_map(enc, p, 64, rows, cols / 64, cols * 2, 128, boxrows, boxblks);
}
CUtensorMap seq_map(EncodeFn enc, const void* p, uint64_t cols, uint32_t boxrows) {
  return make_map(enc, p, cols, T_, 2, cols * 2, cols * 2 * T_, boxrows, 1);
}

}

extern "C" void kernel_launch(void* const* d_in, const int* in_sizes, int n_in, void* d_out, int out_size) {
  (void)in_sizes; (void)n_in; (void)out_size;
  const void *x = d_in[0], *w1a = d_in[1], *w1b = d_in[2], *wqkv = d_in[3], *wo = d_in[4], *pw1 = d_in[5], *dw = d_in[6], *pw2 = d_in[7],
             *w2a = d_in[8], *w2b = d_in[9];
  void* fn = nullptr;
  cudaDriverEntryPointQueryResult qr;
  cudaGetDriverEntryPoint("cuTensorMapEncodeTiled", &fn, cudaEnableDefault, &qr);
  EncodeFn enc = (EncodeFn)fn;
  void* qkv;
  cudaGetSymbolAddress(&qkv, g_qkv);
  cudaFuncSetAttribute(conformer_kernel, cudaFuncAttributeMaxDynamicSharedMemorySize, SMEM_BYTES);

  Wptrs wp;
  const void* ws[8] = {w1a, w1b, wqkv, wo, pw1, pw2, w2a, w2b};
  const uint32_t wb[8] = {524288, 524288, 393216, 131072, 262144, 131072, 524288, 524288};
  for (int i = 0; i < 8; i++) { wp.p[i] = ws[i]; wp.bytes[i] = wb[i]; }
  Maps tm;
  tm.X = blk_map(enc, x, ROWS, 256, 64, 4);
  tm.W1a = blk_map(enc, w1a, 256, 1024, 256, 1);
  tm.W1b = blk_map(enc, w1b, 1024, 256, 64, 4);
  tm.Wqkv = blk_map(enc, wqkv, 256, 768, 128, 2);
  tm.QKVst = blk_map(enc, qkv, ROWS, 768, 64, 2);
  tm.Q = seq_map(enc, qkv, 768, 256);
  tm.KV = seq_map(enc, qkv, 768, 160);
  tm.Wo = blk_map(enc, wo, 256, 256, 128, 2);
  tm.Pw1 = make_map(enc, pw1, 256, 256, 2, 1024, 512, 128, 2);
  tm.Pw2 = blk_map(enc, pw2, 256, 256, 128, 2);
  tm.W2a = blk_map(enc, w2a, 256, 1024, 256, 1);
  tm.W2b = blk_map(enc, w2b, 1024, 256, 64, 4);
  tm.Out = blk_map(enc, d_out, ROWS, 256, 64, 2);
  conformer_kernel<<<128, 512, SMEM_BYTES, cudaStreamPerThread>>>(tm, wp, (const uint4*)dw);
}
```

```cpp
#include <cuda_runtime.h>
#include <cuda_bf16.h>
#include <cuda.h>
#include <stdint.h>

namespace {

constexpr int T_ = 4000;
constexpr int ROWS = 8000;
constexpr int NTILE = 125;
constexpr int NCTA = 129;

__device__ __nv_bfloat16 g_qkv[ROWS * 768];
__device__ uint4 g_att[(ROWS / 16) * 16 * 32];
__device__ uint4 g_halo[NTILE * 4 * 32];
__device__ uint32_t g_start;
__device__ uint32_t g_cnt1[4 * 32];
__device__ uint32_t g_cnt2[ROWS / 16];

#define PROF_MARK(k, i) do {} while (0)
#define PROF_STG(n, i) do {} while (0)

__device__ __forceinline__ uint32_t smem_u32(const void* p) { return (uint32_t)__cvta_generic_to_shared(p); }
__device__ __forceinline__ void mbar_init(uint32_t bar, uint32_t cnt) { asm volatile("mbarrier.init.shared::cta.b64 [%0], %1;" :: "r"(bar), "r"(cnt) : "memory"); }
__device__ __forceinline__ void mbar_inval(uint32_t bar) { asm volatile("mbarrier.inval.shared::cta.b64 [%0];" :: "r"(bar) : "memory"); }
__device__ __forceinline__ void mbar_expect_tx(uint32_t bar, uint32_t bytes) { asm volatile("mbarrier.arrive.expect_tx.shared::cta.b64 _, [%0], %1;" :: "r"(bar), "r"(bytes) : "memory"); }
__device__ __forceinline__ void mbar_arrive(uint32_t bar) { asm volatile("mbarrier.arrive.shared::cta.b64 _, [%0];" :: "r"(bar) : "memory"); }
__device__ __forceinline__ void mbar_wait(uint32_t bar, uint32_t parity) {
  asm volatile("{\n.reg .pred p;\n.reg .u32 n;\n"
               "mbarrier.try_wait.parity.shared::cta.b64 p, [%0], %1;\n@p bra DONE_%=;\nmov.u32 n, 0;\n"
               "LOOP_%=:\nmbarrier.try_wait.parity.shared::cta.b64 p, [%0], %1;\n@p bra DONE_%=;\n"
               "add.u32 n, n, 1;\nsetp.lt.u32 p, n, 262144;\n@p bra LOOP_%=;\ntrap;\nDONE_%=:\n}\n" :: "r"(bar), "r"(parity) : "memory");
}
__device__ __forceinline__ void data_poll(const uint4* p, uint4& v) {
  asm volatile("{\n.reg .pred p;\n.reg .u32 n, t;\nmov.u32 n, 0;\n"
               "LOOP_%=:\nld.relaxed.gpu.global.v4.u32 {%0,%1,%2,%3}, [%4];\n"
               "max.u32 t, %0, %1;\nmax.u32 t, t, %2;\nmax.u32 t, t, %3;\nsetp.ne.u32 p, t, 0xFFFFFFFF;\n@p bra DONE_%=;\n"
               "add.u32 n, n, 1;\nsetp.lt.u32 p, n, 262144;\n@p bra LOOP_%=;\ntrap;\nDONE_%=:\n}\n"
               : "=&r"(v.x), "=&r"(v.y), "=&r"(v.z), "=&r"(v.w) : "l"(p) : "memory");
}
__device__ __forceinline__ void cnt_wait(const uint32_t* p, uint32_t target) {
  asm volatile("{\n.reg .pred p;\n.reg .u32 n, v;\nmov.u32 n, 0;\n"
               "LOOP_%=:\nld.relaxed.gpu.global.u32 v, [%0];\nsub.u32 v, v, %1;\nsetp.ge.s32 p, v, 0;\n@p bra DONE_%=;\n"
               "nanosleep.u32 40;\nadd.u32 n, n, 1;\nsetp.lt.u32 p, n, 262144;\n@p bra LOOP_%=;\ntrap;\nDONE_%=:\n}\n" :: "l"(p), "r"(target) : "memory");
}
__device__ __forceinline__ void cnt_signal(uint32_t* p) {
  asm volatile("red.relaxed.gpu.global.add.u32 [%0], 1;" :: "l"(p) : "memory");
}
__device__ __forceinline__ void tma_load_3d(uint32_t dst, const CUtensorMap* tm, uint32_t bar, int c0, int c1, int c2) {
  asm volatile("cp.async.bulk.tensor.3d.shared::cluster.global.mbarrier::complete_tx::bytes [%0], [%1, {%3, %4, %5}], [%2];"
    :: "r"(dst), "l"(tm), "r"(bar), "r"(c0), "r"(c1), "r"(c2) : "memory");
}
__device__ __forceinline__ void tma_store_3d(const CUtensorMap* tm, uint32_t src, int c0, int c1, int c2) {
  asm volatile("cp.async.bulk.tensor.3d.global.shared::cta.bulk_group [%0, {%2, %3, %4}], [%1];" :: "l"(tm), "r"(src), "r"(c0), "r"(c1), "r"(c2) : "memory");
}
__device__ __forceinline__ void bulk_commit() { asm volatile("cp.async.bulk.commit_group;" ::: "memory"); }
__device__ __forceinline__ void bulk_wait_read() { asm volatile("cp.async.bulk.wait_group.read 0;" ::: "memory"); }
__device__ __forceinline__ void bulk_wait_all() { asm volatile("cp.async.bulk.wait_group 0;" ::: "memory"); }
__device__ __forceinline__ void l2_prefetch(const void* p, uint32_t bytes) { asm volatile("cp.async.bulk.prefetch.L2.global [%0], %1;" :: "l"(p), "r"(bytes) : "memory"); }
__device__ __forceinline__ void prefetch_tmap(const CUtensorMap* tm) { asm volatile("prefetch.tensormap [%0];" :: "l"(tm) : "memory"); }
__device__ __forceinline__ void fence_async_smem() { asm volatile("fence.proxy.async.shared::cta;" ::: "memory"); }
__device__ __forceinline__ void wg_fence() { asm volatile("wgmma.fence.sync.aligned;" ::: "memory"); }
__device__ __forceinline__ void wg_commit() { asm volatile("wgmma.commit_group.sync.aligned;" ::: "memory"); }
template<int N> __device__ __forceinline__ void wg_wait() { asm volatile("wgmma.wait_group.sync.aligned %0;" :: "n"(N) : "memory"); }
__device__ __forceinline__ void bar_sync(int id, int n) { asm volatile("bar.sync %0, %1;" :: "r"(id), "r"(n) : "memory"); }
__device__ __forceinline__ void bar_arrive(int id, int n) { asm volatile("bar.arrive %0, %1;" :: "r"(id), "r"(n) : "memory"); }
__device__ __forceinline__ float ex2(float x) { float y; asm("ex2.approx.ftz.f32 %0, %1;" : "=f"(y) : "f"(x)); return y; }
__device__ __forceinline__ float tanh_fast(float x) { float y; asm("tanh.approx.f32 %0, %1;" : "=f"(y) : "f"(x)); return y; }
__device__ __forceinline__ uint32_t pack_bf16(float lo, float hi) { uint32_t r; asm("cvt.rn.bf16x2.f32 %0, %1, %2;" : "=r"(r) : "f"(hi), "f"(lo)); return r; }
__device__ __forceinline__ uint32_t bmul2(uint32_t a, uint32_t b) { uint32_t d; asm("mul.rn.bf16x2 %0, %1, %2;" : "=r"(d) : "r"(a), "r"(b)); return d; }
__device__ __forceinline__ uint32_t bfma2(uint32_t a, uint32_t b, uint32_t c) { uint32_t d; asm("fma.rn.bf16x2 %0, %1, %2, %3;" : "=r"(d) : "r"(a), "r"(b), "r"(c)); return d; }
__device__ __forceinline__ float bf_lo(uint32_t u) { return __uint_as_float(u << 16); }
__device__ __forceinline__ float bf_hi(uint32_t u) { return __uint_as_float(u & 0xffff0000u); }
__device__ __forceinline__ void ldsm_x4(uint32_t addr, uint32_t& r0, uint32_t& r1, uint32_t& r2, uint32_t& r3) {
  asm volatile("ldmatrix.sync.aligned.m8n8.x4.shared.b16 {%0,%1,%2,%3}, [%4];" : "=r"(r0), "=r"(r1), "=r"(r2), "=r"(r3) : "r"(addr) : "memory");
}
__device__ __forceinline__ void stsm_x4(uint32_t addr, uint32_t r0, uint32_t r1, uint32_t r2, uint32_t r3) {
  asm volatile("stmatrix.sync.aligned.m8n8.x4.shared.b16 [%0], {%1,%2,%3,%4};" :: "r"(addr), "r"(r0), "r"(r1), "r"(r2), "r"(r3) : "memory");
}
__device__ __forceinline__ void sts128(uint32_t addr, uint4 v) { asm volatile("st.shared.v4.b32 [%0], {%1,%2,%3,%4};" :: "r"(addr), "r"(v.x), "r"(v.y), "r"(v.z), "r"(v.w) : "memory"); }
__device__ __forceinline__ uint4 lds128(uint32_t addr) { uint4 v; asm volatile("ld.shared.v4.b32 {%0,%1,%2,%3}, [%4];" : "=r"(v.x), "=r"(v.y), "=r"(v.z), "=r"(v.w) : "r"(addr) : "memory"); return v; }
__device__ __forceinline__ void sts64f(uint32_t addr, float a, float b) { asm volatile("st.shared.v2.f32 [%0], {%1,%2};" :: "r"(addr), "f"(a), "f"(b) : "memory"); }
__device__ __forceinline__ float2 lds64f(uint32_t addr) { float2 v; asm volatile("ld.shared.v2.f32 {%0,%1}, [%2];" : "=f"(v.x), "=f"(v.y) : "r"(addr) : "memory"); return v; }
__device__ __forceinline__ uint32_t dlo(uint32_t addr, uint32_t lbo) { return ((addr & 0x3FFFF) >> 4) | ((lbo >> 4) << 16); }

template<int SD> __device__ __forceinline__ void wg_ss_n128_tb1(float (&d)[64], uint32_t da, uint32_t db) {
  asm volatile("{\n.reg .b64 da, db;\nmov.b64 da, {%64, 0x40000040};\nmov.b64 db, {%65, 0x40000040};\n"
    "wgmma.mma_async.sync.aligned.m64n128k16.f32.bf16.bf16 {%0, %1, %2, %3, %4, %5, %6, %7, %8, %9, %10, %11, %12, %13, %14, %15, %16, %17, %18, %19, %20, %21, %22, %23, %24, %25, %26, %27, %28, %29, %30, %31, %32, %33, %34, %35, %36, %37, %38, %39, %40, %41, %42, %43, %44, %45, %46, %47, %48, %49, %50, %51, %52, %53, %54, %55, %56, %57, %58, %59, %60, %61, %62, %63}, da, db, %66, 1, 1, 0, 1;\n}\n"
    : "+f"(d[0]), "+f"(d[1]), "+f"(d[2]), "+f"(d[3]), "+f"(d[4]), "+f"(d[5]), "+f"(d[6]), "+f"(d[7]), "+f"(d[8]), "+f"(d[9]), "+f"(d[10]), "+f"(d[11]), "+f"(d[12]), "+f"(d[13]), "+f"(d[14]), "+f"(d[15]), "+f"(d[16]), "+f"(d[17]), "+f"(d[18]), "+f"(d[19]), "+f"(d[20]), "+f"(d[21]), "+f"(d[22]), "+f"(d[23]), "+f"(d[24]), "+f"(d[25]), "+f"(d[26]), "+f"(d[27]), "+f"(d[28]), "+f"(d[29]), "+f"(d[30]), "+f"(d[31]), "+f"(d[32]), "+f"(d[33]), "+f"(d[34]), "+f"(d[35]), "+f"(d[36]), "+f"(d[37]), "+f"(d[38]), "+f"(d[39]), "+f"(d[40]), "+f"(d[41]), "+f"(d[42]), "+f"(d[43]), "+f"(d[44]), "+f"(d[45]), "+f"(d[46]), "+f"(d[47]), "+f"(d[48]), "+f"(d[49]), "+f"(d[50]), "+f"(d[51]), "+f"(d[52]), "+f"(d[53]), "+f"(d[54]), "+f"(d[55]), "+f"(d[56]), "+f"(d[57]), "+f"(d[58]), "+f"(d[59]), "+f"(d[60]), "+f"(d[61]), "+f"(d[62]), "+f"(d[63])
    : "r"(da), "r"(db), "n"(SD));
}
template<int SD> __device__ __forceinline__ void wg_rs_n128_tb1(float (&d)[64], uint32_t a0, uint32_t a1, uint32_t a2, uint32_t a3, uint32_t db) {
  asm volatile("{\n.reg .b64 db;\nmov.b64 db, {%68, 0x40000040};\n"
    "wgmma.mma_async.sync.aligned.m64n128k16.f32.bf16.bf16 {%0, %1, %2, %3, %4, %5, %6, %7, %8, %9, %10, %11, %12, %13, %14, %15, %16, %17, %18, %19, %20, %21, %22, %23, %24, %25, %26, %27, %28, %29, %30, %31, %32, %33, %34, %35, %36, %37, %38, %39, %40, %41, %42, %43, %44, %45, %46, %47, %48, %49, %50, %51, %52, %53, %54, %55, %56, %57, %58, %59, %60, %61, %62, %63}, {%64, %65, %66, %67}, db, %69, 1, 1, 1;\n}\n"
    : "+f"(d[0]), "+f"(d[1]), "+f"(d[2]), "+f"(d[3]), "+f"(d[4]), "+f"(d[5]), "+f"(d[6]), "+f"(d[7]), "+f"(d[8]), "+f"(d[9]), "+f"(d[10]), "+f"(d[11]), "+f"(d[12]), "+f"(d[13]), "+f"(d[14]), "+f"(d[15]), "+f"(d[16]), "+f"(d[17]), "+f"(d[18]), "+f"(d[19]), "+f"(d[20]), "+f"(d[21]), "+f"(d[22]), "+f"(d[23]), "+f"(d[24]), "+f"(d[25]), "+f"(d[26]), "+f"(d[27]), "+f"(d[28]), "+f"(d[29]), "+f"(d[30]), "+f"(d[31]), "+f"(d[32]), "+f"(d[33]), "+f"(d[34]), "+f"(d[35]), "+f"(d[36]), "+f"(d[37]), "+f"(d[38]), "+f"(d[39]), "+f"(d[40]), "+f"(d[41]), "+f"(d[42]), "+f"(d[43]), "+f"(d[44]), "+f"(d[45]), "+f"(d[46]), "+f"(d[47]), "+f"(d[48]), "+f"(d[49]), "+f"(d[50]), "+f"(d[51]), "+f"(d[52]), "+f"(d[53]), "+f"(d[54]), "+f"(d[55]), "+f"(d[56]), "+f"(d[57]), "+f"(d[58]), "+f"(d[59]), "+f"(d[60]), "+f"(d[61]), "+f"(d[62]), "+f"(d[63])
    : "r"(a0), "r"(a1), "r"(a2), "r"(a3), "r"(db), "n"(SD));
}
template<int SD> __device__ __forceinline__ void wg_ss_n64_tb1(float (&d)[32], uint32_t da, uint32_t db) {
  asm volatile("{\n.reg .b64 da, db;\nmov.b64 da, {%32, 0x40000040};\nmov.b64 db, {%33, 0x40000040};\n"
    "wgmma.mma_async.sync.aligned.m64n64k16.f32.bf16.bf16 {%0, %1, %2, %3, %4, %5, %6, %7, %8, %9, %10, %11, %12, %13, %14, %15, %16, %17, %18, %19, %20, %21, %22, %23, %24, %25, %26, %27, %28, %29, %30, %31}, da, db, %34, 1, 1, 0, 1;\n}\n"
    : "+f"(d[0]), "+f"(d[1]), "+f"(d[2]), "+f"(d[3]), "+f"(d[4]), "+f"(d[5]), "+f"(d[6]), "+f"(d[7]), "+f"(d[8]), "+f"(d[9]), "+f"(d[10]), "+f"(d[11]), "+f"(d[12]), "+f"(d[13]), "+f"(d[14]), "+f"(d[15]), "+f"(d[16]), "+f"(d[17]), "+f"(d[18]), "+f"(d[19]), "+f"(d[20]), "+f"(d[21]), "+f"(d[22]), "+f"(d[23]), "+f"(d[24]), "+f"(d[25]), "+f"(d[26]), "+f"(d[27]), "+f"(d[28]), "+f"(d[29]), "+f"(d[30]), "+f"(d[31])
    : "r"(da), "r"(db), "n"(SD));
}
template<int SD> __device__ __forceinline__ void wg_ss_n80_tb0(float (&d)[40], uint32_t da, uint32_t db) {
  asm volatile("{\n.reg .b64 da, db;\nmov.b64 da, {%40, 0x40000040};\nmov.b64 db, {%41, 0x40000040};\n"
    "wgmma.mma_async.sync.aligned.m64n80k16.f32.bf16.bf16 {%0, %1, %2, %3, %4, %5, %6, %7, %8, %9, %10, %11, %12, %13, %14, %15, %16, %17, %18, %19, %20, %21, %22, %23, %24, %25, %26, %27, %28, %29, %30, %31, %32, %33, %34, %35, %36, %37, %38, %39}, da, db, %42, 1, 1, 0, 0;\n}\n"
    : "+f"(d[0]), "+f"(d[1]), "+f"(d[2]), "+f"(d[3]), "+f"(d[4]), "+f"(d[5]), "+f"(d[6]), "+f"(d[7]), "+f"(d[8]), "+f"(d[9]), "+f"(d[10]), "+f"(d[11]), "+f"(d[12]), "+f"(d[13]), "+f"(d[14]), "+f"(d[15]), "+f"(d[16]), "+f"(d[17]), "+f"(d[18]), "+f"(d[19]), "+f"(d[20]), "+f"(d[21]), "+f"(d[22]), "+f"(d[23]), "+f"(d[24]), "+f"(d[25]), "+f"(d[26]), "+f"(d[27]), "+f"(d[28]), "+f"(d[29]), "+f"(d[30]), "+f"(d[31]), "+f"(d[32]), "+f"(d[33]), "+f"(d[34]), "+f"(d[35]), "+f"(d[36]), "+f"(d[37]), "+f"(d[38]), "+f"(d[39])
    : "r"(da), "r"(db), "n"(SD));
}
template<int SD> __device__ __forceinline__ void wg_rs_n64_tb1(float (&d)[32], uint32_t a0, uint32_t a1, uint32_t a2, uint32_t a3, uint32_t db) {
  asm volatile("{\n.reg .b64 db;\nmov.b64 db, {%36, 0x40000040};\n"
    "wgmma.mma_async.sync.aligned.m64n64k16.f32.bf16.bf16 {%0, %1, %2, %3, %4, %5, %6, %7, %8, %9, %10, %11, %12, %13, %14, %15, %16, %17, %18, %19, %20, %21, %22, %23, %24, %25, %26, %27, %28, %29, %30, %31}, {%32, %33, %34, %35}, db, %37, 1, 1, 1;\n}\n"
    : "+f"(d[0]), "+f"(d[1]), "+f"(d[2]), "+f"(d[3]), "+f"(d[4]), "+f"(d[5]), "+f"(d[6]), "+f"(d[7]), "+f"(d[8]), "+f"(d[9]), "+f"(d[10]), "+f"(d[11]), "+f"(d[12]), "+f"(d[13]), "+f"(d[14]), "+f"(d[15]), "+f"(d[16]), "+f"(d[17]), "+f"(d[18]), "+f"(d[19]), "+f"(d[20]), "+f"(d[21]), "+f"(d[22]), "+f"(d[23]), "+f"(d[24]), "+f"(d[25]), "+f"(d[26]), "+f"(d[27]), "+f"(d[28]), "+f"(d[29]), "+f"(d[30]), "+f"(d[31])
    : "r"(a0), "r"(a1), "r"(a2), "r"(a3), "r"(db), "n"(SD));
}

constexpr int RING = 5;
constexpr uint32_t STAGE = 32768;
constexpr uint32_t OFF_X = 32768, OFF_W = 65536, OFF_MISC = OFF_W + RING * STAGE;
constexpr int SMEM_BYTES = OFF_MISC + 256 + 1024 + 1024;

struct Ctx {
  uint32_t sA, sX, sW, full, empty, stats;
  uint32_t frag;
  uint32_t rsw;
  uint32_t hi;
  int wg, tid, lane;
  int pk;
  uint32_t dry;
};
__device__ __forceinline__ uint32_t stage_wait(const Ctx& c, int n) {
  const int q = n / RING, s = n - q * RING;
  if (c.tid == 0) PROF_STG(n + c.pk, 1);
  mbar_wait(c.full + 8 * s, (q | c.dry) & 1);
  if (c.tid == 0) PROF_STG(n + c.pk, 2);
  return dlo(c.sW + s * STAGE, 0);
}
__device__ __forceinline__ void stage_release(const Ctx& c, int n) {
  const int s = n % RING;
  if (c.tid == 0) { mbar_arrive(c.empty + 8 * s); PROF_STG(n + c.pk, 3); }
}
__device__ __forceinline__ void turn_begin(const Ctx& c) { bar_sync(5 + c.wg, 256); }
__device__ __forceinline__ void turn_end(const Ctx& c) { bar_arrive(5 + (c.wg ^ 1), 256); }
template<int FIRST> __device__ __forceinline__ void piece_ss(float (&acc)[64], uint32_t dA, uint32_t dB) {
  dB += (16384 >> 4) << 16;
  wg_ss_n128_tb1<FIRST ? 0 : 1>(acc, dA, dB);
#pragma unroll
  for (int kk = 1; kk < 8; kk++) wg_ss_n128_tb1<1>(acc, dA + (kk >> 2) * 512 + (kk & 3) * 2, dB + kk * 128);
}
__device__ __forceinline__ void ff_g1(float (&h)[32], uint32_t dA, uint32_t dB) {
  wg_ss_n64_tb1<0>(h, dA, dB);
#pragma unroll
  for (int kk = 1; kk < 16; kk++) wg_ss_n64_tb1<1>(h, dA + (kk >> 2) * 512 + (kk & 3) * 2, dB + kk * 128);
}
__device__ __forceinline__ void ff_g2(float (&acc)[64], const uint32_t (&P)[16], uint32_t dB, int half) {
  dB += ((8192 >> 4) << 16) + half * 1024;
#pragma unroll
  for (int kk = 0; kk < 4; kk++) wg_rs_n128_tb1<1>(acc, P[4 * kk], P[4 * kk + 1], P[4 * kk + 2], P[4 * kk + 3], dB + kk * 128);
}
template<int FIRST> __device__ __forceinline__ void gemm256(const Ctx& c, float (&acc)[64], int n) {
  const uint32_t dA = dlo(c.sA, 16);
  uint32_t b = stage_wait(c, n);
  turn_begin(c);
  wg_fence(); piece_ss<FIRST>(acc, dA, b); wg_commit();
  b = stage_wait(c, n + 1);
  wg_fence(); piece_ss<0>(acc, dA + 1024, b); wg_commit();
  turn_end(c);
  wg_wait<1>(); stage_release(c, n);
  wg_wait<0>(); stage_release(c, n + 1);
}
__device__ __forceinline__ uint32_t frag_addr(const Ctx& c, uint32_t tile, int j) {
  return tile + (2 * c.wg + (j >> 2)) * 8192 + c.frag + ((((j & 3) * 2 + c.hi) ^ c.rsw) << 4);
}
__device__ __forceinline__ void load_half(const Ctx& c, uint32_t tile, float (&v)[64]) {
#pragma unroll
  for (int j = 0; j < 8; j++) {
    uint32_t r0, r1, r2, r3;
    ldsm_x4(frag_addr(c, tile, j), r0, r1, r2, r3);
    v[8 * j] = bf_lo(r0); v[8 * j + 1] = bf_hi(r0); v[8 * j + 2] = bf_lo(r1); v[8 * j + 3] = bf_hi(r1);
    v[8 * j + 4] = bf_lo(r2); v[8 * j + 5] = bf_hi(r2); v[8 * j + 6] = bf_lo(r3); v[8 * j + 7] = bf_hi(r3);
  }
}
__device__ __forceinline__ void store_half(const Ctx& c, uint32_t tile, const float (&v)[64], float a0, float b0, float a1, float b1) {
#pragma unroll
  for (int j = 0; j < 8; j++)
    stsm_x4(frag_addr(c, tile, j),
            pack_bf16(fmaf(v[8 * j], a0, b0), fmaf(v[8 * j + 1], a0, b0)), pack_bf16(fmaf(v[8 * j + 2], a1, b1), fmaf(v[8 * j + 3], a1, b1)),
            pack_bf16(fmaf(v[8 * j + 4], a0, b0), fmaf(v[8 * j + 5], a0, b0)), pack_bf16(fmaf(v[8 * j + 6], a1, b1), fmaf(v[8 * j + 7], a1, b1)));
}
__device__ __forceinline__ void store_half_raw(const Ctx& c, uint32_t tile, const float (&v)[64]) {
#pragma unroll
  for (int j = 0; j < 8; j++)
    stsm_x4(frag_addr(c, tile, j), pack_bf16(v[8 * j], v[8 * j + 1]), pack_bf16(v[8 * j + 2], v[8 * j + 3]),
            pack_bf16(v[8 * j + 4], v[8 * j + 5]), pack_bf16(v[8 * j + 6], v[8 * j + 7]));
}
__device__ __forceinline__ void ln_stats(const Ctx& c, const float (&v)[64], float scale, float& a0, float& b0, float& a1, float& b1) {
  float s0 = 0.f, s1 = 0.f, q0 = 0.f, q1 = 0.f, s2 = 0.f, s3 = 0.f, q2 = 0.f, q3 = 0.f;
#pragma unroll
  for (int i = 0; i < 16; i++) {
    s0 += v[4 * i]; q0 = fmaf(v[4 * i], v[4 * i], q0);
    s2 += v[4 * i + 1]; q2 = fmaf(v[4 * i + 1], v[4 * i + 1], q2);
    s1 += v[4 * i + 2]; q1 = fmaf(v[4 * i + 2], v[4 * i + 2], q1);
    s3 += v[4 * i + 3]; q3 = fmaf(v[4 * i + 3], v[4 * i + 3], q3);
  }
  s0 += s2; q0 += q2; s1 += s3; q1 += q3;
  s0 += __shfl_xor_sync(0xffffffff, s0, 1); q0 += __shfl_xor_sync(0xffffffff, q0, 1);
  s1 += __shfl_xor_sync(0xffffffff, s1, 1); q1 += __shfl_xor_sync(0xffffffff, q1, 1);
  s0 += __shfl_xor_sync(0xffffffff, s0, 2); q0 += __shfl_xor_sync(0xffffffff, q0, 2);
  s1 += __shfl_xor_sync(0xffffffff, s1, 2); q1 += __shfl_xor_sync(0xffffffff, q1, 2);
  const uint32_t row = (c.tid >> 5) * 16 + (c.lane >> 2);
  if ((c.lane & 3) == 0) {
    sts64f(c.stats + c.wg * 512 + row * 8, s0, q0);
    sts64f(c.stats + c.wg * 512 + (row + 8) * 8, s1, q1);
  }
  bar_sync(1, 256);
  const float2 o0 = lds64f(c.stats + (c.wg ^ 1) * 512 + row * 8), o1 = lds64f(c.stats + (c.wg ^ 1) * 512 + (row + 8) * 8);
  const float m0 = (s0 + o0.x) * (1.f / 256.f), m1 = (s1 + o1.x) * (1.f / 256.f);
  const float var0 = fmaxf(fmaf(-m0, m0, (q0 + o0.y) * (1.f / 256.f)), 0.f), var1 = fmaxf(fmaf(-m1, m1, (q1 + o1.y) * (1.f / 256.f)), 0.f);
  a0 = rsqrtf(var0 + 1e-5f) * scale; a1 = rsqrtf(var1 + 1e-5f) * scale;
  b0 = -m0 * a0; b1 = -m1 * a1;
}
__device__ __forceinline__ float silu_half(float h) { return fmaf(h, tanh_fast(h), h); }
__device__ __forceinline__ float silu_quarter(float h) { const float q = 0.5f * h; return fmaf(q, tanh_fast(h), q); }
__device__ __forceinline__ void silu_pack(const float (&acc)[32], uint32_t (&P)[16]) {
#pragma unroll
  for (int i = 0; i < 16; i++) P[i] = pack_bf16(silu_quarter(acc[2 * i]), silu_quarter(acc[2 * i + 1]));
}
__device__ __forceinline__ void ff_block(const Ctx& c, int n0, float (&own)[64]) {
  float oth[64], h[32];
  uint32_t P[16];
#pragma unroll
  for (int i = 0; i < 64; i++) oth[i] = 0.f;
  const uint32_t dA = dlo(c.sA, 16);
  {
    const uint32_t b = stage_wait(c, n0 + c.wg);
    turn_begin(c);
    wg_fence(); ff_g1(h, dA, b); wg_commit();
    turn_end(c);
    wg_wait<0>(); stage_release(c, n0 + c.wg);
    silu_pack(h, P);
  }
#pragma unroll 1
  for (int it = c.dry ? 7 : 1; it < 8; it++) {
    const int n = n0 + 4 * it - 2 + 2 * c.wg;
    uint32_t b = stage_wait(c, n);
    turn_begin(c);
    wg_fence(); ff_g2(own, P, b, c.wg); ff_g2(oth, P, b, c.wg ^ 1); wg_commit();
    b = stage_wait(c, n + 1);
    wg_fence(); ff_g1(h, dA, b); wg_commit();
    turn_end(c);
    wg_wait<1>(); stage_release(c, n);
    wg_wait<0>(); stage_release(c, n + 1);
    silu_pack(h, P);
  }
  if (c.wg == 0) bar_arrive(2, 256);
  {
    const int n = n0 + 30 + c.wg;
    const uint32_t b = stage_wait(c, n);
    turn_begin(c);
    wg_fence(); ff_g2(oth, P, b, c.wg ^ 1); wg_commit();
    ff_g2(own, P, b, c.wg); wg_commit();
    turn_end(c);
    wg_wait<1>();
    if (c.wg == 1) bar_sync(2, 256);
    const uint32_t e = (c.wg == 0 ? c.sX : c.sA) + c.tid * 16;
#pragma unroll
    for (int i = 0; i < 16; i++)
      sts128(e + i * 2048, make_uint4(__float_as_uint(oth[4 * i]), __float_as_uint(oth[4 * i + 1]), __float_as_uint(oth[4 * i + 2]), __float_as_uint(oth[4 * i + 3])));
    wg_wait<0>(); stage_release(c, n);
  }
  bar_sync(1, 256);
  const uint32_t e = (c.wg == 0 ? c.sA : c.sX) + c.tid * 16;
#pragma unroll
  for (int i = 0; i < 16; i++) {
    const uint4 u = lds128(e + i * 2048);
    own[4 * i] += __uint_as_float(u.x); own[4 * i + 1] += __uint_as_float(u.y);
    own[4 * i + 2] += __uint_as_float(u.z); own[4 * i + 3] += __uint_as_float(u.w);
  }
}
__device__ __forceinline__ void produce(uint32_t sW, uint32_t full, uint32_t empty, int n, const CUtensorMap* tm, int k0, int nblk, int c0 = 0) {
  const int q = n / RING, s = n - q * RING;
  mbar_wait(empty + 8 * s, (q & 1) ^ 1);
  PROF_STG(n + ((sW & 1) ? 132 * 64 : 0), 0);
  sW &= ~1u;
  mbar_expect_tx(full + 8 * s, STAGE);
  tma_load_3d(sW + s * STAGE, tm, full + 8 * s, c0, k0, nblk);
}
__device__ __forceinline__ void produce_ff(uint32_t sW, uint32_t full, uint32_t empty, int n0, const CUtensorMap* tmA, const CUtensorMap* tmB) {
#pragma unroll 1
  for (int m = 0; m < 32; m++) {
    int is2, j;
    if (m < 2) { is2 = 0; j = m; }
    else if (m == 31) { is2 = 1; j = 15; }
    else { const int q = m - 2; is2 = !(q & 1); j = (q >> 1) + (is2 ? 0 : 2); }
    if (is2) produce(sW, full, empty, n0 + m, tmB, 64 * j, 0);
    else produce(sW, full, empty, n0 + m, tmA, 0, j);
  }
}
__device__ __forceinline__ Ctx make_ctx(uint32_t base, uint32_t dry, int pk = 0) {
  Ctx c; c.pk = pk; c.dry = dry;
  c.sA = base; c.sX = base + OFF_X; c.sW = base + OFF_W;
  c.full = base + OFF_MISC; c.empty = c.full + 8 * RING; c.stats = base + OFF_MISC + 256;
  c.wg = __shfl_sync(0xffffffff, (int)(threadIdx.x >> 7), 0);
  c.tid = threadIdx.x & 127; c.lane = threadIdx.x & 31;
  const uint32_t r = (c.tid >> 5) * 16 + (c.lane & 7) + ((c.lane >> 3) & 1) * 8;
  c.frag = r * 128; c.rsw = r & 7; c.hi = c.lane >> 4;
  return c;
}

constexpr int NSTG = 4;
constexpr int KVB = 160 * 128;
constexpr int NKV = T_ / 160;
static_assert(NSTG * 2 * KVB == RING * STAGE, "the K/V ring reuses the weight ring");

struct AttCtx { uint32_t sKV, full, empty, dry; const CUtensorMap* tmKV; int h, b, wg; };
__device__ __forceinline__ void att_load(const AttCtx& a, int i, int v) {
  const int s = i & (NSTG - 1);
  mbar_expect_tx(a.full + 8 * (s + v * NSTG), KVB);
  tma_load_3d(a.sKV + s * 2 * KVB + v * KVB, a.tmKV, a.full + 8 * (s + v * NSTG), 256 + v * 256 + a.h * 64, i * 160, a.b);
}
__device__ __forceinline__ void att_load_stage(const AttCtx& a, int i) { att_load(a, i, 0); att_load(a, i, 1); }
__device__ __forceinline__ void att_init_bars(const AttCtx& a) {
  for (int i = 0; i < NSTG; i++) { mbar_init(a.full + 8 * i, 1); mbar_init(a.full + 8 * (NSTG + i), 1); mbar_init(a.empty + 8 * i, 4); }
}
__device__ __forceinline__ void att_qk(float (&S)[40], uint32_t dQ, uint32_t kd) {
  wg_ss_n80_tb0<0>(S, dQ, kd);
#pragma unroll
  for (int kk = 1; kk < 4; kk++) wg_ss_n80_tb0<1>(S, dQ + kk * 2, kd + kk * 2);
}
__device__ __forceinline__ void att_pv(float (&O)[32], const uint32_t (&P)[20], uint32_t vd) {
#pragma unroll
  for (int kk = 0; kk < 5; kk++) wg_rs_n64_tb1<1>(O, P[kk * 4], P[kk * 4 + 1], P[kk * 4 + 2], P[kk * 4 + 3], vd + kk * 128);
}
template<bool SAFE>
__device__ __forceinline__ void att_softmax(const float (&S)[40], uint32_t (&P)[20], float (&O)[32], float& m0, float& m1, float& l0, float& l1) {
  if (SAFE) {
    float x0 = fmaxf(S[0], S[1]), x1 = fmaxf(S[2], S[3]);
#pragma unroll
    for (int i = 1; i < 10; i++) { x0 = fmaxf(x0, fmaxf(S[4 * i], S[4 * i + 1])); x1 = fmaxf(x1, fmaxf(S[4 * i + 2], S[4 * i + 3])); }
    x0 = fmaxf(x0, __shfl_xor_sync(0xffffffff, x0, 1)); x1 = fmaxf(x1, __shfl_xor_sync(0xffffffff, x1, 1));
    x0 = fmaxf(x0, __shfl_xor_sync(0xffffffff, x0, 2)); x1 = fmaxf(x1, __shfl_xor_sync(0xffffffff, x1, 2));
    const float n0 = fmaxf(m0, x0), n1 = fmaxf(m1, x1);
    const float f0 = ex2(m0 - n0), f1 = ex2(m1 - n1);
    m0 = n0; m1 = n1; l0 *= f0; l1 *= f1;
#pragma unroll
    for (int i = 0; i < 8; i++) { O[4 * i] *= f0; O[4 * i + 1] *= f0; O[4 * i + 2] *= f1; O[4 * i + 3] *= f1; }
  }
#pragma unroll
  for (int i = 0; i < 10; i++) {
    float p0, p1, p2, p3;
    if (SAFE) { p0 = ex2(S[4 * i] - m0); p1 = ex2(S[4 * i + 1] - m0); p2 = ex2(S[4 * i + 2] - m1); p3 = ex2(S[4 * i + 3] - m1); }
    else { p0 = ex2(S[4 * i]); p1 = ex2(S[4 * i + 1]); p2 = ex2(S[4 * i + 2]); p3 = ex2(S[4 * i + 3]); }
    l0 += p0 + p1; l1 += p2 + p3;
    P[2 * i] = pack_bf16(p0, p1); P[2 * i + 1] = pack_bf16(p2, p3);
  }
}
template<bool SAFE>
__device__ __forceinline__ void att_pass(const AttCtx& a, uint32_t dQ, float (&O)[32], float& l0, float& l1) {
  float S[40];
  uint32_t P[20];
  float m0 = -INFINITY, m1 = -INFINITY;
  l0 = 0.f; l1 = 0.f;
#pragma unroll
  for (int i = 0; i < 32; i++) O[i] = 0.f;
  const uint32_t dKV = dlo(a.sKV, 16);
  constexpr uint32_t STG = 2 * KVB / 16, VOFF = KVB / 16, HALF = 80 * 128 / 16;
  constexpr int UNR = SAFE ? 1 : 4;
  mbar_wait(a.full, a.dry);
  wg_fence(); att_qk(S, dQ, dKV); wg_commit(); wg_wait<0>();
  att_softmax<SAFE>(S, P, O, m0, m1, l0, l1);
  mbar_wait(a.full + 8 * NSTG, a.dry);
  wg_fence(); att_pv(O, P, dKV + VOFF); att_qk(S, dQ, dKV + HALF); wg_commit(); wg_wait<0>();
#pragma unroll 1
  for (int it0 = a.dry ? NKV - 1 - UNR : 0; it0 < NKV - 1; it0 += UNR) {
#pragma unroll
    for (int u = 0; u < UNR; u++) {
      const int it = it0 + u;
      const int s = SAFE ? (it & 3) : u, sn = (s + 1) & 3, sp = (s + 3) & 3;
      const uint32_t kb = dKV + s * STG, kn = dKV + sn * STG;
      att_softmax<SAFE>(S, P, O, m0, m1, l0, l1);
      mbar_wait(a.full + 8 * sn, (((it + 1) >> 2) | a.dry) & 1);
      wg_fence(); att_pv(O, P, kb + VOFF + HALF); att_qk(S, dQ, kn); wg_commit(); wg_wait<0>();
      if ((threadIdx.x & 127) == 0) {
        mbar_arrive(a.empty + 8 * s);
        if (a.wg == s && it >= 1 && it - 1 + NSTG < NKV && !a.dry) {
          mbar_wait(a.empty + 8 * sp, ((it - 1) >> 2) & 1);
          att_load_stage(a, it - 1 + NSTG);
        }
      }
      __syncwarp();
      att_softmax<SAFE>(S, P, O, m0, m1, l0, l1);
      mbar_wait(a.full + 8 * (NSTG + sn), (((it + 1) >> 2) | a.dry) & 1);
      wg_fence(); att_pv(O, P, kn + VOFF); att_qk(S, dQ, kn + HALF); wg_commit(); wg_wait<0>();
    }
  }
  att_softmax<SAFE>(S, P, O, m0, m1, l0, l1);
  wg_fence(); att_pv(O, P, dKV + ((NKV - 1) & 3) * STG + VOFF + HALF); wg_commit(); wg_wait<0>();
  l0 += __shfl_xor_sync(0xffffffff, l0, 1); l1 += __shfl_xor_sync(0xffffffff, l1, 1);
  l0 += __shfl_xor_sync(0xffffffff, l0, 2); l1 += __shfl_xor_sync(0xffffffff, l1, 2);
}

struct Wptrs { const void* p[8]; uint32_t bytes[8]; };
struct Maps { CUtensorMap X, W1a, W1b, Wqkv, QKVst, Q, KV, Wo, Pw1, Pw2, W2a, W2b, Out; };

constexpr uint32_t B_FULL = 0, B_EMPTY = 8 * RING, B_X = 16 * RING, B_ADONE = B_X + 8, B_Q = B_X + 16, B_EP = B_X + 24, B_ATT = B_X + 32;

__global__ void __launch_bounds__(512, 1) conformer_kernel(const __grid_constant__ Maps tm, const __grid_constant__ Wptrs wp, const uint4* __restrict__ dw) {
  extern __shared__ uint8_t smem_raw[];
  const uint32_t base = (smem_u32(smem_raw) + 1023) & ~1023u, misc = base + OFF_MISC;
  const uint32_t dry = blockIdx.x == NCTA - 1;
  const int tile = dry ? 0 : blockIdx.x;
  const bool has_tile = tile < NTILE;
  const int wg = __shfl_sync(0xffffffff, (int)(threadIdx.x >> 7), 0);
  AttCtx a;
  a.sKV = base + OFF_W; a.full = misc + B_ATT; a.empty = a.full + 16 * NSTG; a.tmKV = &tm.KV;
  a.h = (blockIdx.x >> 4) & 3; a.b = (blockIdx.x >> 6) & 1; a.wg = wg; a.dry = dry;
  const int qt = blockIdx.x & 15;

  if (threadIdx.x == 256) {
    mbar_init(misc + B_X, 1);
    asm volatile("fence.mbarrier_init.release.cluster;" ::: "memory");
    if (has_tile && !dry) { mbar_expect_tx(misc + B_X, 32768); tma_load_3d(base + OFF_X, &tm.X, misc + B_X, 0, tile * 64, 0); }
    for (int i = 0; i < RING; i++) { mbar_init(misc + B_FULL + 8 * i, 1); mbar_init(misc + B_EMPTY + 8 * i, 1); }
    mbar_init(misc + B_ADONE, 2);
    mbar_init(misc + B_Q, 1);
    mbar_init(misc + B_EP, 1);
    att_init_bars(a);
    asm volatile("fence.mbarrier_init.release.cluster;" ::: "memory");
  } else if (threadIdx.x >= 320 && threadIdx.x < 333) {
    prefetch_tmap(&tm.X + (threadIdx.x - 320));
  }
  __syncthreads();
  auto get_epoch = [&]() {
    uint32_t e;
    mbar_wait(misc + B_EP, 0);
    asm volatile("ld.shared.u32 %0, [%1];" : "=r"(e) : "r"(misc + 248) : "memory");
    return e;
  };

  if (wg >= 2) {
    asm volatile("setmaxnreg.dec.sync.aligned.u32 24;");
    const uint32_t sW = base + OFF_W, full = misc + B_FULL, empty = misc + B_EMPTY;
    if (threadIdx.x == 320) {
      const uint32_t e = atomicAdd(&g_start, 1) / NCTA;
      asm volatile("st.shared.u32 [%0], %1;" :: "r"(misc + 248), "r"(e + 1) : "memory");
      mbar_arrive(misc + B_EP);
    }
    if (dry) {
    } else if (threadIdx.x == 256) {
      if (has_tile) {
        produce_ff(sW, full, empty, 0, &tm.W1a, &tm.W1b);
#pragma unroll 1
        for (int m = 0; m < 12; m++) produce(sW, full, empty, 32 + m, &tm.Wqkv, 128 * (m & 1), 2 * (m >> 1));
        mbar_wait(misc + B_ADONE, 0);
      }
      cnt_wait(g_cnt1 + a.b * 64, 126 * get_epoch());
      mbar_expect_tx(misc + B_Q, 32768);
      tma_load_3d(base, &tm.Q, misc + B_Q, a.h * 64, qt * 256, a.b);
      for (int i = 0; i < NSTG; i++) att_load(a, i, 0);
    } else if (threadIdx.x == 384) {
      if (has_tile) mbar_wait(misc + B_ADONE, 0);
      cnt_wait(g_cnt1 + a.b * 64 + 32, 126 * get_epoch());
      for (int i = 0; i < NSTG; i++) att_load(a, i, 1);
    } else if (has_tile && threadIdx.x >= 288 && threadIdx.x < 296) {
      const int w = threadIdx.x - 288;
      mbar_wait(misc + B_X, 0);
      const uint32_t bytes = wp.bytes[w], per = ((bytes / NTILE) + 127) & ~127u, off = per * tile;
      if (off < bytes) l2_prefetch((const uint8_t*)wp.p[w] + off, min(per, bytes - off));
    } else if (has_tile && threadIdx.x >= 416) {
      mbar_wait(full, 0);
      const int t = threadIdx.x - 416;
#pragma unroll 2
      for (int i = t; i < 2048; i += 96) g_att[tile * 2048 + i] = make_uint4(~0u, ~0u, ~0u, ~0u);
      g_halo[tile * 128 + t] = make_uint4(~0u, ~0u, ~0u, ~0u);
      if (t < 32) g_halo[tile * 128 + 96 + t] = make_uint4(~0u, ~0u, ~0u, ~0u);
    }
    __syncwarp();
    asm volatile("setmaxnreg.inc.sync.aligned.u32 128;");
  } else {
    asm volatile("setmaxnreg.inc.sync.aligned.u32 232;");
    if (has_tile) {
      const Ctx c = make_ctx(base, dry);
      if (c.wg == 1) turn_end(c);
      float own[64];
      float a0, b0, a1, b1;
      PROF_MARK(0, 0);
      mbar_wait(misc + B_X, dry);
      PROF_MARK(0, 1);
      load_half(c, c.sX, own);
      ln_stats(c, own, 0.5f, a0, b0, a1, b1);
      store_half(c, c.sA, own, a0, b0, a1, b1);
      fence_async_smem();
      bar_sync(1, 256);
      PROF_MARK(0, 2);
      ff_block(c, 0, own);
      PROF_MARK(0, 3);
      ln_stats(c, own, 1.f, a0, b0, a1, b1);
      store_half(c, c.sA, own, a0, b0, a1, b1);
      fence_async_smem();
      bar_sync(1, 256);
      PROF_MARK(0, 4);
#pragma unroll 1
      for (int cc = dry ? 2 : 0; cc < 3; cc++) {
        float acc[64];
        const int j = 2 * cc + c.wg;
        gemm256<1>(c, acc, 32 + 2 * j);
        const float sc = (cc == 0) ? 0.125f * 1.4426950408889634f : 1.f;
        if (c.tid == 0 && !dry) {
          if (cc == 2) {
            mbar_arrive(misc + B_ADONE);
            bulk_wait_all();
            if (tile <= 62) cnt_signal(g_cnt1);
            if (tile >= 62) cnt_signal(g_cnt1 + 64);
          } else bulk_wait_read();
        }
        bar_sync(3 + c.wg, 128);
        store_half(c, c.sX, acc, sc, 0.f, sc, 0.f);
        fence_async_smem();
        bar_sync(3 + c.wg, 128);
        if (c.tid == 0 && !dry) { tma_store_3d(&tm.QKVst, c.sX + c.wg * 16384, 0, tile * 64, 2 * j); bulk_commit(); }
      }
      PROF_MARK(0, 5);
      if (c.tid == 0) bulk_wait_read();
      bar_sync(3 + c.wg, 128);
      store_half_raw(c, c.sX, own);
    }
    asm volatile("setmaxnreg.dec.sync.aligned.u32 128;");
    if (has_tile && !dry && (threadIdx.x & 127) == 0) {
      bulk_wait_all();
      if (tile <= 62) cnt_signal(g_cnt1 + 32);
      if (tile >= 62) cnt_signal(g_cnt1 + 96);
    }
    __syncwarp();
    PROF_MARK(0, 6);
  }

  {
    const int lane = threadIdx.x & 31, wq = (threadIdx.x >> 5) & 3;
    const uint32_t dQ = dlo(base + wg * 8192, 16);
    float O[32], l0, l1;
    PROF_MARK(1, 1);
    mbar_wait(misc + B_Q, dry);
    PROF_MARK(1, 2);
    att_pass<false>(a, dQ, O, l0, l1);
    PROF_MARK(1, 3);
    float z = 0.f;
#pragma unroll
    for (int i = 0; i < 32; i++) z = fmaf(O[i], 0.f, z);
    const bool ok = (l0 >= 0x1p-80f) && (l0 <= 0x1p100f) && (l1 >= 0x1p-80f) && (l1 <= 0x1p100f) && (z == 0.f);
    const bool warp_bad = !__all_sync(0xffffffff, ok) && !dry;
    auto store_out = [&]() {
      const float i0 = 1.f / l0, i1 = 1.f / l1;
      const int row = qt * 256 + wg * 64 + wq * 16;
      if (row < T_ && !dry) {
        const int slab = (a.b * T_ + row) / 16;
        uint4* op = g_att + (slab * 16 + a.h * 4) * 32 + lane;
#pragma unroll
        for (int j = 0; j < 4; j++)
          asm volatile("st.relaxed.gpu.global.v4.u32 [%0], {%1,%2,%3,%4};" :: "l"(op + j * 32),
                       "r"(pack_bf16(O[8 * j] * i0, O[8 * j + 1] * i0)), "r"(pack_bf16(O[8 * j + 2] * i1, O[8 * j + 3] * i1)),
                       "r"(pack_bf16(O[8 * j + 4] * i0, O[8 * j + 5] * i0)), "r"(pack_bf16(O[8 * j + 6] * i1, O[8 * j + 7] * i1)) : "memory");
        __syncwarp();
        if (lane == 0) cnt_signal(g_cnt2 + slab);
      }
      PROF_MARK(1, 4);
    };
    if (!warp_bad) store_out();
    if (__syncthreads_or(warp_bad)) {
      if (threadIdx.x == 0) {
        for (int i = 0; i < 3 * NSTG; i++) mbar_inval(a.full + 8 * i);
        att_init_bars(a);
        asm volatile("fence.mbarrier_init.release.cluster;" ::: "memory");
        fence_async_smem();
        for (int i = 0; i < NSTG; i++) att_load_stage(a, i);
      }
      __syncthreads();
      att_pass<true>(a, dQ, O, l0, l1);
      if (warp_bad) store_out();
      __syncthreads();
    }
    PROF_MARK(1, 5);
  }
  if (!has_tile) return;

  constexpr int NC = 44;
  if (wg >= 2) {
    asm volatile("setmaxnreg.dec.sync.aligned.u32 24;");
    if (threadIdx.x == 256 && !dry) {
      const uint32_t sW = base + OFF_W, full = misc + B_FULL, empty = misc + B_EMPTY;
#pragma unroll 1
      for (int m = 0; m < 4; m++) produce(sW, full, empty, NC + m, &tm.Wo, 128 * (m & 1), 2 * (m >> 1));
#pragma unroll 1
      for (int m = 0; m < 8; m++) produce(sW, full, empty, NC + 4 + m, &tm.Pw1, 128 * (m & 1), 0, 64 * (2 * ((m >> 1) & 1) + (m >> 2)));
#pragma unroll 1
      for (int m = 0; m < 4; m++) produce(sW, full, empty, NC + 12 + m, &tm.Pw2, 128 * (m & 1), 2 * (m >> 1));
      produce_ff(sW, full, empty, NC + 16, &tm.W2a, &tm.W2b);
    }
  } else {
    asm volatile("setmaxnreg.inc.sync.aligned.u32 232;");
    const Ctx c = make_ctx(base, dry);
    float own[64];
    float a0, b0, a1, b1;
    PROF_MARK(2, 0);
    load_half(c, c.sX, own);
    {
      uint4 af[16];
      const int slab = tile * 4 + (c.tid >> 5);
      const uint4* ap = g_att + slab * 512 + c.lane;
      if (c.lane == 0 && !dry) cnt_wait(g_cnt2 + slab, 4 * get_epoch());
      __syncwarp();
      PROF_MARK(2, 1);
      for (uint32_t n = 0; n < (1u << 24); n++) {
        bool any = false;
#pragma unroll
        for (int i = 0; i < 16; i++)
          asm volatile("ld.relaxed.gpu.global.v4.u32 {%0,%1,%2,%3}, [%4];" : "=r"(af[i].x), "=r"(af[i].y), "=r"(af[i].z), "=r"(af[i].w) : "l"(ap + i * 32) : "memory");
#pragma unroll
        for (int i = 0; i < 16; i++) any |= max(max(af[i].x, af[i].y), max(af[i].z, af[i].w)) == ~0u;
        if (!__any_sync(0xffffffff, any) || dry) break;
      }
      PROF_MARK(2, 2);
      const int n = NC + 2 * c.wg;
      uint32_t b = stage_wait(c, n) + ((16384 >> 4) << 16);
      turn_begin(c);
      wg_fence();
#pragma unroll
      for (int kk = 0; kk < 8; kk++) wg_rs_n128_tb1<1>(own, af[kk].x, af[kk].y, af[kk].z, af[kk].w, b + kk * 128);
      wg_commit();
      b = stage_wait(c, n + 1) + ((16384 >> 4) << 16);
      wg_fence();
#pragma unroll
      for (int kk = 0; kk < 8; kk++) wg_rs_n128_tb1<1>(own, af[8 + kk].x, af[8 + kk].y, af[8 + kk].z, af[8 + kk].w, b + kk * 128);
      wg_commit();
      turn_end(c);
      wg_wait<1>(); stage_release(c, n);
      wg_wait<0>(); stage_release(c, n + 1);
    }
    PROF_MARK(2, 3);
    ln_stats(c, own, 0.5f, a0, b0, a1, b1);
    store_half(c, c.sA, own, a0, b0, a1, b1);
    fence_async_smem();
    bar_sync(1, 256);
    PROF_MARK(2, 4);
    uint4 dwr[5];
#pragma unroll
    for (int i = 0; i < 5; i++) dwr[i] = __ldg(dw + i * 32 + c.lane);
    const bool top = c.tid < 8, pub = (top || c.tid >= 120) && !dry;
    uint32_t* halo_out = (uint32_t*)g_halo + (tile * 4 + (top ? (c.tid >> 2) : ((c.tid >> 2) - 28))) * 128 + c.wg * 64 + (c.lane & 3);
#pragma unroll 1
    for (int q = dry; q < 2; q++) {
      float ab[64];
      gemm256<1>(c, ab, NC + 4 + 4 * q + 2 * c.wg);
#pragma unroll
      for (int j = 0; j < 4; j++) {
        float g[8];
#pragma unroll
        for (int i = 0; i < 8; i++) g[i] = fmaf(ab[8 * j + i], tanh_fast(ab[32 + 8 * j + i]), ab[8 * j + i]);
        const uint32_t p0 = pack_bf16(g[0], g[1]), p1 = pack_bf16(g[2], g[3]), p2 = pack_bf16(g[4], g[5]), p3 = pack_bf16(g[6], g[7]);
        if (pub) {
          uint32_t* hp = halo_out + q * 32 + j * 8;
          asm volatile("st.relaxed.gpu.global.u32 [%0], %1;" :: "l"(hp), "r"(top ? p0 : p1) : "memory");
          asm volatile("st.relaxed.gpu.global.u32 [%0], %1;" :: "l"(hp + 4), "r"(top ? p2 : p3) : "memory");
        }
        stsm_x4(c.sX + (2 * c.wg + q) * 8192 + c.frag + (((j * 2 + c.hi) ^ c.rsw) << 4), p0, p1, p2, p3);
      }
    }
    bar_sync(1, 256);
    PROF_MARK(2, 5);
    {
      const int wi = threadIdx.x >> 5;
      const uint32_t col = (c.lane >> 3) * 8192, ch = c.lane & 7;
      uint4 r[12];
#pragma unroll
      for (int i = 0; i < 12; i++) {
        const int row = (wi * 8 - 2 + i) & 63;
        r[i] = lds128(c.sX + col + row * 128 + ((ch ^ (row & 7)) << 4));
      }
      uint32_t w[5][4];
#pragma unroll
      for (int k = 0; k < 5; k++) {
        w[k][0] = bmul2(dwr[k].x, 0x3F003F00u); w[k][1] = bmul2(dwr[k].y, 0x3F003F00u);
        w[k][2] = bmul2(dwr[k].z, 0x3F003F00u); w[k][3] = bmul2(dwr[k].w, 0x3F003F00u);
      }
      auto conv_row = [&](int i) {
        uint32_t o[4];
#pragma unroll
        for (int q = 0; q < 4; q++) {
          uint32_t acc = bmul2(q == 0 ? r[i].x : q == 1 ? r[i].y : q == 2 ? r[i].z : r[i].w, w[0][q]);
#pragma unroll
          for (int k = 1; k < 5; k++) acc = bfma2(q == 0 ? r[i + k].x : q == 1 ? r[i + k].y : q == 2 ? r[i + k].z : r[i + k].w, w[k][q], acc);
          o[q] = pack_bf16(silu_half(bf_lo(acc)), silu_half(bf_hi(acc)));
        }
        sts128(c.sA + col + (wi * 8 + i) * 128 + ((ch ^ i) << 4), make_uint4(o[0], o[1], o[2], o[3]));
      };
      conv_row(2); conv_row(3); conv_row(4); conv_row(5);
      const int R0 = tile * 64 + wi * 8;
      if ((R0 % T_) == 0) { r[0] = make_uint4(0, 0, 0, 0); r[1] = r[0]; }
      else if (wi == 0 && !dry) { const uint4* sp = g_halo + ((tile - 1) * 4 + 2) * 32 + c.lane; data_poll(sp, r[0]); data_poll(sp + 32, r[1]); }
      if (((R0 + 8) % T_) == 0) { r[10] = make_uint4(0, 0, 0, 0); r[11] = r[10]; }
      else if (wi == 7 && !dry) { const uint4* sp = g_halo + ((tile + 1) * 4) * 32 + c.lane; data_poll(sp, r[10]); data_poll(sp + 32, r[11]); }
      conv_row(0); conv_row(1); conv_row(6); conv_row(7);
    }
    fence_async_smem();
    bar_sync(1, 256);
    PROF_MARK(2, 6);
    gemm256<0>(c, own, NC + 12 + 2 * c.wg);
    PROF_MARK(2, 7);
    ln_stats(c, own, 0.5f, a0, b0, a1, b1);
    store_half(c, c.sA, own, a0, b0, a1, b1);
    fence_async_smem();
    bar_sync(1, 256);
    PROF_MARK(2, 8);
    ff_block(c, NC + 16, own);
    PROF_MARK(2, 9);
    ln_stats(c, own, 1.f, a0, b0, a1, b1);
    store_half(c, c.sX, own, a0, b0, a1, b1);
    fence_async_smem();
    bar_sync(3 + c.wg, 128);
    if (c.tid == 0 && !dry) { tma_store_3d(&tm.Out, c.sX + c.wg * 16384, 0, tile * 64, 2 * c.wg); bulk_commit(); PROF_MARK(2, 10); bulk_wait_all(); }
    PROF_MARK(2, 11);
  }
}

typedef CUresult (*EncodeFn)(CUtensorMap*, CUtensorMapDataType, cuuint32_t, void*, const cuuint64_t*, const cuuint64_t*, const cuuint32_t*,
                             const cuuint32_t*, CUtensorMapInterleave, CUtensorMapSwizzle, CUtensorMapL2promotion, CUtensorMapFloatOOBfill);

CUtensorMap make_map(EncodeFn enc, const void* p, uint64_t d0, uint64_t d1, uint64_t d2, uint64_t s1, uint64_t s2, uint32_t b1, uint32_t b2) {
  CUtensorMap tm;
  cuuint64_t dims[3] = {d0, d1, d2};
  cuuint64_t strides[2] = {s1, s2};
  cuuint32_t box[3] = {64, b1, b2};
  cuuint32_t es[3] = {1, 1, 1};
  enc(&tm, CU_TENSOR_MAP_DATA_TYPE_BFLOAT16, 3, const_cast<void*>(p), dims, strides, box, es, CU_TENSOR_MAP_INTERLEAVE_NONE,
      CU_TENSOR_MAP_SWIZZLE_128B, CU_TENSOR_MAP_L2_PROMOTION_L2_256B, CU_TENSOR_MAP_FLOAT_OOB_FILL_NONE);
  return tm;
}
CUtensorMap blk_map(EncodeFn enc, const void* p, uint64_t rows, uint64_t cols, uint32_t boxrows, uint32_t boxblks) {
  return make_map(enc, p, 64, rows, cols / 64, cols * 2, 128, boxrows, boxblks);
}
CUtensorMap seq_map(EncodeFn enc, const void* p, uint64_t cols, uint32_t boxrows) {
  return make_map(enc, p, cols, T_, 2, cols * 2, cols * 2 * T_, boxrows, 1);
}

}

extern "C" void kernel_launch(void* const* d_in, const int* in_sizes, int n_in, void* d_out, int out_size) {
  (void)in_sizes; (void)n_in; (void)out_size;
  const void *x = d_in[0], *w1a = d_in[1], *w1b = d_in[2], *wqkv = d_in[3], *wo = d_in[4], *pw1 = d_in[5], *dw = d_in[6], *pw2 = d_in[7],
             *w2a = d_in[8], *w2b = d_in[9];
  void* fn = nullptr;
  cudaDriverEntryPointQueryResult qr;
  cudaGetDriverEntryPoint("cuTensorMapEncodeTiled", &fn, cudaEnableDefault, &qr);
  EncodeFn enc = (EncodeFn)fn;
  void* qkv;
  cudaGetSymbolAddress(&qkv, g_qkv);
  cudaFuncSetAttribute(conformer_kernel, cudaFuncAttributeMaxDynamicSharedMemorySize, SMEM_BYTES);

  Wptrs wp;
  const void* ws[8] = {w1a, w1b, wqkv, wo, pw1, pw2, w2a, w2b};
  const uint32_t wb[8] = {524288, 524288, 393216, 131072, 262144, 131072, 524288, 524288};
  for (int i = 0; i < 8; i++) { wp.p[i] = ws[i]; wp.bytes[i] = wb[i]; }
  Maps tm;
  tm.X = blk_map(enc, x, ROWS, 256, 64, 4);
  tm.W1a = blk_map(enc, w1a, 256, 1024, 256, 1);
  tm.W1b = blk_map(enc, w1b, 1024, 256, 64, 4);
  tm.Wqkv = blk_map(enc, wqkv, 256, 768, 128, 2);
  tm.QKVst = blk_map(enc, qkv, ROWS, 768, 64, 2);
  tm.Q = seq_map(enc, qkv, 768, 256);
  tm.KV = seq_map(enc, qkv, 768, 160);
  tm.Wo = blk_map(enc, wo, 256, 256, 128, 2);
  tm.Pw1 = make_map(enc, pw1, 256, 256, 2, 1024, 512, 128, 2);
  tm.Pw2 = blk_map(enc, pw2, 256, 256, 128, 2);
  tm.W2a = blk_map(enc, w2a, 256, 1024, 256, 1);
  tm.W2b = blk_map(enc, w2b, 1024, 256, 64, 4);
  tm.Out = blk_map(enc, d_out, ROWS, 256, 64, 2);
  conformer_kernel<<<NCTA, 512, SMEM_BYTES, cudaStreamPerThread>>>(tm, wp, (const uint4*)dw);
}
```

```cpp
#include <cuda_runtime.h>
#include <cuda_bf16.h>
#include <cuda.h>
#include <stdint.h>

namespace {

constexpr int T_ = 4000;
constexpr int ROWS = 8000;
constexpr int NTILE = 125;
constexpr int NCTA = 131;

__device__ __nv_bfloat16 g_qkv[ROWS * 768];
__device__ uint4 g_att[(ROWS / 16) * 16 * 32];
__device__ uint4 g_halo[NTILE * 4 * 32];
__device__ uint32_t g_start;
__device__ uint32_t g_cnt1[4 * 32];
__device__ uint32_t g_cnt2[ROWS / 16];

#define PROF_MARK(k, i) do {} while (0)
#define PROF_STG(n, i) do {} while (0)

__device__ __forceinline__ uint32_t smem_u32(const void* p) { return (uint32_t)__cvta_generic_to_shared(p); }
__device__ __forceinline__ void mbar_init(uint32_t bar, uint32_t cnt) { asm volatile("mbarrier.init.shared::cta.b64 [%0], %1;" :: "r"(bar), "r"(cnt) : "memory"); }
__device__ __forceinline__ void mbar_inval(uint32_t bar) { asm volatile("mbarrier.inval.shared::cta.b64 [%0];" :: "r"(bar) : "memory"); }
__device__ __forceinline__ void mbar_expect_tx(uint32_t bar, uint32_t bytes) { asm volatile("mbarrier.arrive.expect_tx.shared::cta.b64 _, [%0], %1;" :: "r"(bar), "r"(bytes) : "memory"); }
__device__ __forceinline__ void mbar_arrive(uint32_t bar) { asm volatile("mbarrier.arrive.shared::cta.b64 _, [%0];" :: "r"(bar) : "memory"); }
__device__ __forceinline__ void mbar_wait(uint32_t bar, uint32_t parity) {
  asm volatile("{\n.reg .pred p;\n.reg .u32 n;\n"
               "mbarrier.try_wait.parity.shared::cta.b64 p, [%0], %1;\n@p bra DONE_%=;\nmov.u32 n, 0;\n"
               "LOOP_%=:\nmbarrier.try_wait.parity.shared::cta.b64 p, [%0], %1;\n@p bra DONE_%=;\n"
               "add.u32 n, n, 1;\nsetp.lt.u32 p, n, 262144;\n@p bra LOOP_%=;\ntrap;\nDONE_%=:\n}\n" :: "r"(bar), "r"(parity) : "memory");
}
__device__ __forceinline__ void data_poll(const uint4* p, uint4& v) {
  asm volatile("{\n.reg .pred p;\n.reg .u32 n, t;\nmov.u32 n, 0;\n"
               "LOOP_%=:\nld.relaxed.gpu.global.v4.u32 {%0,%1,%2,%3}, [%4];\n"
               "max.u32 t, %0, %1;\nmax.u32 t, t, %2;\nmax.u32 t, t, %3;\nsetp.ne.u32 p, t, 0xFFFFFFFF;\n@p bra DONE_%=;\n"
               "add.u32 n, n, 1;\nsetp.lt.u32 p, n, 262144;\n@p bra LOOP_%=;\ntrap;\nDONE_%=:\n}\n"
               : "=&r"(v.x), "=&r"(v.y), "=&r"(v.z), "=&r"(v.w) : "l"(p) : "memory");
}
__device__ __forceinline__ void cnt_wait(const uint32_t* p, uint32_t target) {
  asm volatile("{\n.reg .pred p;\n.reg .u32 n, v;\nmov.u32 n, 0;\n"
               "LOOP_%=:\nld.relaxed.gpu.global.u32 v, [%0];\nsub.u32 v, v, %1;\nsetp.ge.s32 p, v, 0;\n@p bra DONE_%=;\n"
               "nanosleep.u32 40;\nadd.u32 n, n, 1;\nsetp.lt.u32 p, n, 262144;\n@p bra LOOP_%=;\ntrap;\nDONE_%=:\n}\n" :: "l"(p), "r"(target) : "memory");
}
__device__ __forceinline__ void cnt_signal(uint32_t* p) {
  asm volatile("red.relaxed.gpu.global.add.u32 [%0], 1;" :: "l"(p) : "memory");
}
__device__ __forceinline__ void tma_load_3d(uint32_t dst, const CUtensorMap* tm, uint32_t bar, int c0, int c1, int c2) {
  asm volatile("cp.async.bulk.tensor.3d.shared::cluster.global.mbarrier::complete_tx::bytes [%0], [%1, {%3, %4, %5}], [%2];"
    :: "r"(dst), "l"(tm), "r"(bar), "r"(c0), "r"(c1), "r"(c2) : "memory");
}
__device__ __forceinline__ void tma_store_3d(const CUtensorMap* tm, uint32_t src, int c0, int c1, int c2) {
  asm volatile("cp.async.bulk.tensor.3d.global.shared::cta.bulk_group [%0, {%2, %3, %4}], [%1];" :: "l"(tm), "r"(src), "r"(c0), "r"(c1), "r"(c2) : "memory");
}
__device__ __forceinline__ void bulk_commit() { asm volatile("cp.async.bulk.commit_group;" ::: "memory"); }
__device__ __forceinline__ void bulk_wait_read() { asm volatile("cp.async.bulk.wait_group.read 0;" ::: "memory"); }
__device__ __forceinline__ void bulk_wait_all() { asm volatile("cp.async.bulk.wait_group 0;" ::: "memory"); }
__device__ __forceinline__ void l2_prefetch(const void* p, uint32_t bytes) { asm volatile("cp.async.bulk.prefetch.L2.global [%0], %1;" :: "l"(p), "r"(bytes) : "memory"); }
__device__ __forceinline__ void prefetch_tmap(const CUtensorMap* tm) { asm volatile("prefetch.tensormap [%0];" :: "l"(tm) : "memory"); }
__device__ __forceinline__ void fence_async_smem() { asm volatile("fence.proxy.async.shared::cta;" ::: "memory"); }
__device__ __forceinline__ void wg_fence() { asm volatile("wgmma.fence.sync.aligned;" ::: "memory"); }
__device__ __forceinline__ void wg_commit() { asm volatile("wgmma.commit_group.sync.aligned;" ::: "memory"); }
template<int N> __device__ __forceinline__ void wg_wait() { asm volatile("wgmma.wait_group.sync.aligned %0;" :: "n"(N) : "memory"); }
__device__ __forceinline__ void bar_sync(int id, int n) { asm volatile("bar.sync %0, %1;" :: "r"(id), "r"(n) : "memory"); }
__device__ __forceinline__ void bar_arrive(int id, int n) { asm volatile("bar.arrive %0, %1;" :: "r"(id), "r"(n) : "memory"); }
__device__ __forceinline__ float ex2(float x) { float y; asm("ex2.approx.ftz.f32 %0, %1;" : "=f"(y) : "f"(x)); return y; }
__device__ __forceinline__ float tanh_fast(float x) { float y; asm("tanh.approx.f32 %0, %1;" : "=f"(y) : "f"(x)); return y; }
__device__ __forceinline__ uint32_t pack_bf16(float lo, float hi) { uint32_t r; asm("cvt.rn.bf16x2.f32 %0, %1, %2;" : "=r"(r) : "f"(hi), "f"(lo)); return r; }
__device__ __forceinline__ uint32_t bmul2(uint32_t a, uint32_t b) { uint32_t d; asm("mul.rn.bf16x2 %0, %1, %2;" : "=r"(d) : "r"(a), "r"(b)); return d; }
__device__ __forceinline__ uint32_t bfma2(uint32_t a, uint32_t b, uint32_t c) { uint32_t d; asm("fma.rn.bf16x2 %0, %1, %2, %3;" : "=r"(d) : "r"(a), "r"(b), "r"(c)); return d; }
__device__ __forceinline__ float bf_lo(uint32_t u) { return __uint_as_float(u << 16); }
__device__ __forceinline__ float bf_hi(uint32_t u) { return __uint_as_float(u & 0xffff0000u); }
__device__ __forceinline__ void ldsm_x4(uint32_t addr, uint32_t& r0, uint32_t& r1, uint32_t& r2, uint32_t& r3) {
  asm volatile("ldmatrix.sync.aligned.m8n8.x4.shared.b16 {%0,%1,%2,%3}, [%4];" : "=r"(r0), "=r"(r1), "=r"(r2), "=r"(r3) : "r"(addr) : "memory");
}
__device__ __forceinline__ void stsm_x4(uint32_t addr, uint32_t r0, uint32_t r1, uint32_t r2, uint32_t r3) {
  asm volatile("stmatrix.sync.aligned.m8n8.x4.shared.b16 [%0], {%1,%2,%3,%4};" :: "r"(addr), "r"(r0), "r"(r1), "r"(r2), "r"(r3) : "memory");
}
__device__ __forceinline__ void sts128(uint32_t addr, uint4 v) { asm volatile("st.shared.v4.b32 [%0], {%1,%2,%3,%4};" :: "r"(addr), "r"(v.x), "r"(v.y), "r"(v.z), "r"(v.w) : "memory"); }
__device__ __forceinline__ uint4 lds128(uint32_t addr) { uint4 v; asm volatile("ld.shared.v4.b32 {%0,%1,%2,%3}, [%4];" : "=r"(v.x), "=r"(v.y), "=r"(v.z), "=r"(v.w) : "r"(addr) : "memory"); return v; }
__device__ __forceinline__ void sts64f(uint32_t addr, float a, float b) { asm volatile("st.shared.v2.f32 [%0], {%1,%2};" :: "r"(addr), "f"(a), "f"(b) : "memory"); }
__device__ __forceinline__ float2 lds64f(uint32_t addr) { float2 v; asm volatile("ld.shared.v2.f32 {%0,%1}, [%2];" : "=f"(v.x), "=f"(v.y) : "r"(addr) : "memory"); return v; }
__device__ __forceinline__ uint32_t dlo(uint32_t addr, uint32_t lbo) { return ((addr & 0x3FFFF) >> 4) | ((lbo >> 4) << 16); }

template<int SD> __device__ __forceinline__ void wg_ss_n128_tb1(float (&d)[64], uint32_t da, uint32_t db) {
  asm volatile("{\n.reg .b64 da, db;\nmov.b64 da, {%64, 0x40000040};\nmov.b64 db, {%65, 0x40000040};\n"
    "wgmma.mma_async.sync.aligned.m64n128k16.f32.bf16.bf16 {%0, %1, %2, %3, %4, %5, %6, %7, %8, %9, %10, %11, %12, %13, %14, %15, %16, %17, %18, %19, %20, %21, %22, %23, %24, %25, %26, %27, %28, %29, %30, %31, %32, %33, %34, %35, %36, %37, %38, %39, %40, %41, %42, %43, %44, %45, %46, %47, %48, %49, %50, %51, %52, %53, %54, %55, %56, %57, %58, %59, %60, %61, %62, %63}, da, db, %66, 1, 1, 0, 1;\n}\n"
    : "+f"(d[0]), "+f"(d[1]), "+f"(d[2]), "+f"(d[3]), "+f"(d[4]), "+f"(d[5]), "+f"(d[6]), "+f"(d[7]), "+f"(d[8]), "+f"(d[9]), "+f"(d[10]), "+f"(d[11]), "+f"(d[12]), "+f"(d[13]), "+f"(d[14]), "+f"(d[15]), "+f"(d[16]), "+f"(d[17]), "+f"(d[18]), "+f"(d[19]), "+f"(d[20]), "+f"(d[21]), "+f"(d[22]), "+f"(d[23]), "+f"(d[24]), "+f"(d[25]), "+f"(d[26]), "+f"(d[27]), "+f"(d[28]), "+f"(d[29]), "+f"(d[30]), "+f"(d[31]), "+f"(d[32]), "+f"(d[33]), "+f"(d[34]), "+f"(d[35]), "+f"(d[36]), "+f"(d[37]), "+f"(d[38]), "+f"(d[39]), "+f"(d[40]), "+f"(d[41]), "+f"(d[42]), "+f"(d[43]), "+f"(d[44]), "+f"(d[45]), "+f"(d[46]), "+f"(d[47]), "+f"(d[48]), "+f"(d[49]), "+f"(d[50]), "+f"(d[51]), "+f"(d[52]), "+f"(d[53]), "+f"(d[54]), "+f"(d[55]), "+f"(d[56]), "+f"(d[57]), "+f"(d[58]), "+f"(d[59]), "+f"(d[60]), "+f"(d[61]), "+f"(d[62]), "+f"(d[63])
    : "r"(da), "r"(db), "n"(SD));
}
template<int SD> __device__ __forceinline__ void wg_rs_n128_tb1(float (&d)[64], uint32_t a0, uint32_t a1, uint32_t a2, uint32_t a3, uint32_t db) {
  asm volatile("{\n.reg .b64 db;\nmov.b64 db, {%68, 0x40000040};\n"
    "wgmma.mma_async.sync.aligned.m64n128k16.f32.bf16.bf16 {%0, %1, %2, %3, %4, %5, %6, %7, %8, %9, %10, %11, %12, %13, %14, %15, %16, %17, %18, %19, %20, %21, %22, %23, %24, %25, %26, %27, %28, %29, %30, %31, %32, %33, %34, %35, %36, %37, %38, %39, %40, %41, %42, %43, %44, %45, %46, %47, %48, %49, %50, %51, %52, %53, %54, %55, %56, %57, %58, %59, %60, %61, %62, %63}, {%64, %65, %66, %67}, db, %69, 1, 1, 1;\n}\n"
    : "+f"(d[0]), "+f"(d[1]), "+f"(d[2]), "+f"(d[3]), "+f"(d[4]), "+f"(d[5]), "+f"(d[6]), "+f"(d[7]), "+f"(d[8]), "+f"(d[9]), "+f"(d[10]), "+f"(d[11]), "+f"(d[12]), "+f"(d[13]), "+f"(d[14]), "+f"(d[15]), "+f"(d[16]), "+f"(d[17]), "+f"(d[18]), "+f"(d[19]), "+f"(d[20]), "+f"(d[21]), "+f"(d[22]), "+f"(d[23]), "+f"(d[24]), "+f"(d[25]), "+f"(d[26]), "+f"(d[27]), "+f"(d[28]), "+f"(d[29]), "+f"(d[30]), "+f"(d[31]), "+f"(d[32]), "+f"(d[33]), "+f"(d[34]), "+f"(d[35]), "+f"(d[36]), "+f"(d[37]), "+f"(d[38]), "+f"(d[39]), "+f"(d[40]), "+f"(d[41]), "+f"(d[42]), "+f"(d[43]), "+f"(d[44]), "+f"(d[45]), "+f"(d[46]), "+f"(d[47]), "+f"(d[48]), "+f"(d[49]), "+f"(d[50]), "+f"(d[51]), "+f"(d[52]), "+f"(d[53]), "+f"(d[54]), "+f"(d[55]), "+f"(d[56]), "+f"(d[57]), "+f"(d[58]), "+f"(d[59]), "+f"(d[60]), "+f"(d[61]), "+f"(d[62]), "+f"(d[63])
    : "r"(a0), "r"(a1), "r"(a2), "r"(a3), "r"(db), "n"(SD));
}
template<int SD> __device__ __forceinline__ void wg_ss_n64_tb1(float (&d)[32], uint32_t da, uint32_t db) {
  asm volatile("{\n.reg .b64 da, db;\nmov.b64 da, {%32, 0x40000040};\nmov.b64 db, {%33, 0x40000040};\n"
    "wgmma.mma_async.sync.aligned.m64n64k16.f32.bf16.bf16 {%0, %1, %2, %3, %4, %5, %6, %7, %8, %9, %10, %11, %12, %13, %14, %15, %16, %17, %18, %19, %20, %21, %22, %23, %24, %25, %26, %27, %28, %29, %30, %31}, da, db, %34, 1, 1, 0, 1;\n}\n"
    : "+f"(d[0]), "+f"(d[1]), "+f"(d[2]), "+f"(d[3]), "+f"(d[4]), "+f"(d[5]), "+f"(d[6]), "+f"(d[7]), "+f"(d[8]), "+f"(d[9]), "+f"(d[10]), "+f"(d[11]), "+f"(d[12]), "+f"(d[13]), "+f"(d[14]), "+f"(d[15]), "+f"(d[16]), "+f"(d[17]), "+f"(d[18]), "+f"(d[19]), "+f"(d[20]), "+f"(d[21]), "+f"(d[22]), "+f"(d[23]), "+f"(d[24]), "+f"(d[25]), "+f"(d[26]), "+f"(d[27]), "+f"(d[28]), "+f"(d[29]), "+f"(d[30]), "+f"(d[31])
    : "r"(da), "r"(db), "n"(SD));
}
template<int SD> __device__ __forceinline__ void wg_ss_n80_tb0(float (&d)[40], uint32_t da, uint32_t db) {
  asm volatile("{\n.reg .b64 da, db;\nmov.b64 da, {%40, 0x40000040};\nmov.b64 db, {%41, 0x40000040};\n"
    "wgmma.mma_async.sync.aligned.m64n80k16.f32.bf16.bf16 {%0, %1, %2, %3, %4, %5, %6, %7, %8, %9, %10, %11, %12, %13, %14, %15, %16, %17, %18, %19, %20, %21, %22, %23, %24, %25, %26, %27, %28, %29, %30, %31, %32, %33, %34, %35, %36, %37, %38, %39}, da, db, %42, 1, 1, 0, 0;\n}\n"
    : "+f"(d[0]), "+f"(d[1]), "+f"(d[2]), "+f"(d[3]), "+f"(d[4]), "+f"(d[5]), "+f"(d[6]), "+f"(d[7]), "+f"(d[8]), "+f"(d[9]), "+f"(d[10]), "+f"(d[11]), "+f"(d[12]), "+f"(d[13]), "+f"(d[14]), "+f"(d[15]), "+f"(d[16]), "+f"(d[17]), "+f"(d[18]), "+f"(d[19]), "+f"(d[20]), "+f"(d[21]), "+f"(d[22]), "+f"(d[23]), "+f"(d[24]), "+f"(d[25]), "+f"(d[26]), "+f"(d[27]), "+f"(d[28]), "+f"(d[29]), "+f"(d[30]), "+f"(d[31]), "+f"(d[32]), "+f"(d[33]), "+f"(d[34]), "+f"(d[35]), "+f"(d[36]), "+f"(d[37]), "+f"(d[38]), "+f"(d[39])
    : "r"(da), "r"(db), "n"(SD));
}
template<int SD> __device__ __forceinline__ void wg_rs_n64_tb1(float (&d)[32], uint32_t a0, uint32_t a1, uint32_t a2, uint32_t a3, uint32_t db) {
  asm volatile("{\n.reg .b64 db;\nmov.b64 db, {%36, 0x40000040};\n"
    "wgmma.mma_async.sync.aligned.m64n64k16.f32.bf16.bf16 {%0, %1, %2, %3, %4, %5, %6, %7, %8, %9, %10, %11, %12, %13, %14, %15, %16, %17, %18, %19, %20, %21, %22, %23, %24, %25, %26, %27, %28, %29, %30, %31}, {%32, %33, %34, %35}, db, %37, 1, 1, 1;\n}\n"
    : "+f"(d[0]), "+f"(d[1]), "+f"(d[2]), "+f"(d[3]), "+f"(d[4]), "+f"(d[5]), "+f"(d[6]), "+f"(d[7]), "+f"(d[8]), "+f"(d[9]), "+f"(d[10]), "+f"(d[11]), "+f"(d[12]), "+f"(d[13]), "+f"(d[14]), "+f"(d[15]), "+f"(d[16]), "+f"(d[17]), "+f"(d[18]), "+f"(d[19]), "+f"(d[20]), "+f"(d[21]), "+f"(d[22]), "+f"(d[23]), "+f"(d[24]), "+f"(d[25]), "+f"(d[26]), "+f"(d[27]), "+f"(d[28]), "+f"(d[29]), "+f"(d[30]), "+f"(d[31])
    : "r"(a0), "r"(a1), "r"(a2), "r"(a3), "r"(db), "n"(SD));
}

constexpr int RING = 5;
constexpr uint32_t STAGE = 32768;
constexpr uint32_t OFF_X = 32768, OFF_W = 65536, OFF_MISC = OFF_W + RING * STAGE;
constexpr int SMEM_BYTES = OFF_MISC + 256 + 1024 + 1024;

struct Ctx {
  uint32_t sA, sX, sW, full, empty, stats;
  uint32_t frag;
  uint32_t rsw;
  uint32_t hi;
  int wg, tid, lane;
  int pk;
  uint32_t dry;
};
__device__ __forceinline__ uint32_t stage_wait(const Ctx& c, int n) {
  const int q = n / RING, s = n - q * RING;
  if (c.tid == 0) PROF_STG(n + c.pk, 1);
  mbar_wait(c.full + 8 * s, (q | c.dry) & 1);
  if (c.tid == 0) PROF_STG(n + c.pk, 2);
  return dlo(c.sW + s * STAGE, 0);
}
__device__ __forceinline__ void stage_release(const Ctx& c, int n) {
  const int s = n % RING;
  if (c.tid == 0) { mbar_arrive(c.empty + 8 * s); PROF_STG(n + c.pk, 3); }
}
__device__ __forceinline__ void turn_begin(const Ctx& c) { bar_sync(5 + c.wg, 256); }
__device__ __forceinline__ void turn_end(const Ctx& c) { bar_arrive(5 + (c.wg ^ 1), 256); }
template<int FIRST> __device__ __forceinline__ void piece_ss(float (&acc)[64], uint32_t dA, uint32_t dB) {
  dB += (16384 >> 4) << 16;
  wg_ss_n128_tb1<FIRST ? 0 : 1>(acc, dA, dB);
#pragma unroll
  for (int kk = 1; kk < 8; kk++) wg_ss_n128_tb1<1>(acc, dA + (kk >> 2) * 512 + (kk & 3) * 2, dB + kk * 128);
}
__device__ __forceinline__ void ff_g1(float (&h)[32], uint32_t dA, uint32_t dB) {
  wg_ss_n64_tb1<0>(h, dA, dB);
#pragma unroll
  for (int kk = 1; kk < 16; kk++) wg_ss_n64_tb1<1>(h, dA + (kk >> 2) * 512 + (kk & 3) * 2, dB + kk * 128);
}
__device__ __forceinline__ void ff_g2(float (&acc)[64], const uint32_t (&P)[16], uint32_t dB, int half) {
  dB += ((8192 >> 4) << 16) + half * 1024;
#pragma unroll
  for (int kk = 0; kk < 4; kk++) wg_rs_n128_tb1<1>(acc, P[4 * kk], P[4 * kk + 1], P[4 * kk + 2], P[4 * kk + 3], dB + kk * 128);
}
template<int FIRST> __device__ __forceinline__ void gemm256(const Ctx& c, float (&acc)[64], int n) {
  const uint32_t dA = dlo(c.sA, 16);
  uint32_t b = stage_wait(c, n);
  turn_begin(c);
  wg_fence(); piece_ss<FIRST>(acc, dA, b); wg_commit();
  b = stage_wait(c, n + 1);
  wg_fence(); piece_ss<0>(acc, dA + 1024, b); wg_commit();
  turn_end(c);
  wg_wait<1>(); stage_release(c, n);
  wg_wait<0>(); stage_release(c, n + 1);
}
__device__ __forceinline__ uint32_t frag_addr(const Ctx& c, uint32_t tile, int j) {
  return tile + (2 * c.wg + (j >> 2)) * 8192 + c.frag + ((((j & 3) * 2 + c.hi) ^ c.rsw) << 4);
}
__device__ __forceinline__ void load_half(const Ctx& c, uint32_t tile, float (&v)[64]) {
#pragma unroll
  for (int j = 0; j < 8; j++) {
    uint32_t r0, r1, r2, r3;
    ldsm_x4(frag_addr(c, tile, j), r0, r1, r2, r3);
    v[8 * j] = bf_lo(r0); v[8 * j + 1] = bf_hi(r0); v[8 * j + 2] = bf_lo(r1); v[8 * j + 3] = bf_hi(r1);
    v[8 * j + 4] = bf_lo(r2); v[8 * j + 5] = bf_hi(r2); v[8 * j + 6] = bf_lo(r3); v[8 * j + 7] = bf_hi(r3);
  }
}
__device__ __forceinline__ void store_half(const Ctx& c, uint32_t tile, const float (&v)[64], float a0, float b0, float a1, float b1) {
#pragma unroll
  for (int j = 0; j < 8; j++)
    stsm_x4(frag_addr(c, tile, j),
            pack_bf16(fmaf(v[8 * j], a0, b0), fmaf(v[8 * j + 1], a0, b0)), pack_bf16(fmaf(v[8 * j + 2], a1, b1), fmaf(v[8 * j + 3], a1, b1)),
            pack_bf16(fmaf(v[8 * j + 4], a0, b0), fmaf(v[8 * j + 5], a0, b0)), pack_bf16(fmaf(v[8 * j + 6], a1, b1), fmaf(v[8 * j + 7], a1, b1)));
}
__device__ __forceinline__ void store_half_raw(const Ctx& c, uint32_t tile, const float (&v)[64]) {
#pragma unroll
  for (int j = 0; j < 8; j++)
    stsm_x4(frag_addr(c, tile, j), pack_bf16(v[8 * j], v[8 * j + 1]), pack_bf16(v[8 * j + 2], v[8 * j + 3]),
            pack_bf16(v[8 * j + 4], v[8 * j + 5]), pack_bf16(v[8 * j + 6], v[8 * j + 7]));
}
__device__ __forceinline__ void ln_stats(const Ctx& c, const float (&v)[64], float scale, float& a0, float& b0, float& a1, float& b1) {
  float s0 = 0.f, s1 = 0.f, q0 = 0.f, q1 = 0.f, s2 = 0.f, s3 = 0.f, q2 = 0.f, q3 = 0.f;
#pragma unroll
  for (int i = 0; i < 16; i++) {
    s0 += v[4 * i]; q0 = fmaf(v[4 * i], v[4 * i], q0);
    s2 += v[4 * i + 1]; q2 = fmaf(v[4 * i + 1], v[4 * i + 1], q2);
    s1 += v[4 * i + 2]; q1 = fmaf(v[4 * i + 2], v[4 * i + 2], q1);
    s3 += v[4 * i + 3]; q3 = fmaf(v[4 * i + 3], v[4 * i + 3], q3);
  }
  s0 += s2; q0 += q2; s1 += s3; q1 += q3;
  s0 += __shfl_xor_sync(0xffffffff, s0, 1); q0 += __shfl_xor_sync(0xffffffff, q0, 1);
  s1 += __shfl_xor_sync(0xffffffff, s1, 1); q1 += __shfl_xor_sync(0xffffffff, q1, 1);
  s0 += __shfl_xor_sync(0xffffffff, s0, 2); q0 += __shfl_xor_sync(0xffffffff, q0, 2);
  s1 += __shfl_xor_sync(0xffffffff, s1, 2); q1 += __shfl_xor_sync(0xffffffff, q1, 2);
  const uint32_t row = (c.tid >> 5) * 16 + (c.lane >> 2);
  if ((c.lane & 3) == 0) {
    sts64f(c.stats + c.wg * 512 + row * 8, s0, q0);
    sts64f(c.stats + c.wg * 512 + (row + 8) * 8, s1, q1);
  }
  bar_sync(1, 256);
  const float2 o0 = lds64f(c.stats + (c.wg ^ 1) * 512 + row * 8), o1 = lds64f(c.stats + (c.wg ^ 1) * 512 + (row + 8) * 8);
  const float m0 = (s0 + o0.x) * (1.f / 256.f), m1 = (s1 + o1.x) * (1.f / 256.f);
  const float var0 = fmaxf(fmaf(-m0, m0, (q0 + o0.y) * (1.f / 256.f)), 0.f), var1 = fmaxf(fmaf(-m1, m1, (q1 + o1.y) * (1.f / 256.f)), 0.f);
  a0 = rsqrtf(var0 + 1e-5f) * scale; a1 = rsqrtf(var1 + 1e-5f) * scale;
  b0 = -m0 * a0; b1 = -m1 * a1;
}
__device__ __forceinline__ float silu_half(float h) { return fmaf(h, tanh_fast(h), h); }
__device__ __forceinline__ float silu_quarter(float h) { const float q = 0.5f * h; return fmaf(q, tanh_fast(h), q); }
__device__ __forceinline__ void silu_pack(const float (&acc)[32], uint32_t (&P)[16]) {
#pragma unroll
  for (int i = 0; i < 16; i++) P[i] = pack_bf16(silu_quarter(acc[2 * i]), silu_quarter(acc[2 * i + 1]));
}
__device__ __forceinline__ void ff_block(const Ctx& c, int n0, float (&own)[64]) {
  float oth[64], h[32];
  uint32_t P[16];
#pragma unroll
  for (int i = 0; i < 64; i++) oth[i] = 0.f;
  const uint32_t dA = dlo(c.sA, 16);
  {
    const uint32_t b = stage_wait(c, n0 + c.wg);
    turn_begin(c);
    wg_fence(); ff_g1(h, dA, b); wg_commit();
    turn_end(c);
    wg_wait<0>(); stage_release(c, n0 + c.wg);
    silu_pack(h, P);
  }
#pragma unroll 1
  for (int it = c.dry ? 7 : 1; it < 8; it++) {
    const int n = n0 + 4 * it - 2 + 2 * c.wg;
    uint32_t b = stage_wait(c, n);
    turn_begin(c);
    wg_fence(); ff_g2(own, P, b, c.wg); ff_g2(oth, P, b, c.wg ^ 1); wg_commit();
    b = stage_wait(c, n + 1);
    wg_fence(); ff_g1(h, dA, b); wg_commit();
    turn_end(c);
    wg_wait<1>(); stage_release(c, n);
    wg_wait<0>(); stage_release(c, n + 1);
    silu_pack(h, P);
  }
  if (c.wg == 0) bar_arrive(2, 256);
  {
    const int n = n0 + 30 + c.wg;
    const uint32_t b = stage_wait(c, n);
    turn_begin(c);
    wg_fence(); ff_g2(oth, P, b, c.wg ^ 1); wg_commit();
    ff_g2(own, P, b, c.wg); wg_commit();
    turn_end(c);
    wg_wait<1>();
    if (c.wg == 1) bar_sync(2, 256);
    const uint32_t e = (c.wg == 0 ? c.sX : c.sA) + c.tid * 16;
#pragma unroll
    for (int i = 0; i < 16; i++)
      sts128(e + i * 2048, make_uint4(__float_as_uint(oth[4 * i]), __float_as_uint(oth[4 * i + 1]), __float_as_uint(oth[4 * i + 2]), __float_as_uint(oth[4 * i + 3])));
    wg_wait<0>(); stage_release(c, n);
  }
  bar_sync(1, 256);
  const uint32_t e = (c.wg == 0 ? c.sA : c.sX) + c.tid * 16;
#pragma unroll
  for (int i = 0; i < 16; i++) {
    const uint4 u = lds128(e + i * 2048);
    own[4 * i] += __uint_as_float(u.x); own[4 * i + 1] += __uint_as_float(u.y);
    own[4 * i + 2] += __uint_as_float(u.z); own[4 * i + 3] += __uint_as_float(u.w);
  }
}
__device__ __forceinline__ void produce(uint32_t sW, uint32_t full, uint32_t empty, int n, const CUtensorMap* tm, int k0, int nblk, int c0 = 0) {
  const int q = n / RING, s = n - q * RING;
  mbar_wait(empty + 8 * s, (q & 1) ^ 1);
  PROF_STG(n + ((sW & 1) ? 132 * 64 : 0), 0);
  sW &= ~1u;
  mbar_expect_tx(full + 8 * s, STAGE);
  tma_load_3d(sW + s * STAGE, tm, full + 8 * s, c0, k0, nblk);
}
__device__ __forceinline__ void produce_ff(uint32_t sW, uint32_t full, uint32_t empty, int n0, const CUtensorMap* tmA, const CUtensorMap* tmB) {
#pragma unroll 1
  for (int m = 0; m < 32; m++) {
    int is2, j;
    if (m < 2) { is2 = 0; j = m; }
    else if (m == 31) { is2 = 1; j = 15; }
    else { const int q = m - 2; is2 = !(q & 1); j = (q >> 1) + (is2 ? 0 : 2); }
    if (is2) produce(sW, full, empty, n0 + m, tmB, 64 * j, 0);
    else produce(sW, full, empty, n0 + m, tmA, 0, j);
  }
}
__device__ __forceinline__ Ctx make_ctx(uint32_t base, uint32_t dry, int pk = 0) {
  Ctx c; c.pk = pk; c.dry = dry;
  c.sA = base; c.sX = base + OFF_X; c.sW = base + OFF_W;
  c.full = base + OFF_MISC; c.empty = c.full + 8 * RING; c.stats = base + OFF_MISC + 256;
  c.wg = __shfl_sync(0xffffffff, (int)(threadIdx.x >> 7), 0);
  c.tid = threadIdx.x & 127; c.lane = threadIdx.x & 31;
  const uint32_t r = (c.tid >> 5) * 16 + (c.lane & 7) + ((c.lane >> 3) & 1) * 8;
  c.frag = r * 128; c.rsw = r & 7; c.hi = c.lane >> 4;
  return c;
}

constexpr int NSTG = 4;
constexpr int KVB = 160 * 128;
constexpr int NKV = T_ / 160;
static_assert(NSTG * 2 * KVB == RING * STAGE, "the K/V ring reuses the weight ring");

struct AttCtx { uint32_t sKV, full, empty, dry; const CUtensorMap* tmKV; int h, b, wg; };
__device__ __forceinline__ void att_load(const AttCtx& a, int i, int v) {
  const int s = i & (NSTG - 1);
  mbar_expect_tx(a.full + 8 * (s + v * NSTG), KVB);
  tma_load_3d(a.sKV + s * 2 * KVB + v * KVB, a.tmKV, a.full + 8 * (s + v * NSTG), 256 + v * 256 + a.h * 64, i * 160, a.b);
}
__device__ __forceinline__ void att_load_stage(const AttCtx& a, int i) { att_load(a, i, 0); att_load(a, i, 1); }
__device__ __forceinline__ void att_init_bars(const AttCtx& a) {
  for (int i = 0; i < NSTG; i++) { mbar_init(a.full + 8 * i, 1); mbar_init(a.full + 8 * (NSTG + i), 1); mbar_init(a.empty + 8 * i, 4); }
}
__device__ __forceinline__ void att_qk(float (&S)[40], uint32_t dQ, uint32_t kd) {
  wg_ss_n80_tb0<0>(S, dQ, kd);
#pragma unroll
  for (int kk = 1; kk < 4; kk++) wg_ss_n80_tb0<1>(S, dQ + kk * 2, kd + kk * 2);
}
__device__ __forceinline__ void att_pv(float (&O)[32], const uint32_t (&P)[20], uint32_t vd) {
#pragma unroll
  for (int kk = 0; kk < 5; kk++) wg_rs_n64_tb1<1>(O, P[kk * 4], P[kk * 4 + 1], P[kk * 4 + 2], P[kk * 4 + 3], vd + kk * 128);
}
template<bool SAFE>
__device__ __forceinline__ void att_softmax(const float (&S)[40], uint32_t (&P)[20], float (&O)[32], float& m0, float& m1, float& l0, float& l1) {
  if (SAFE) {
    float x0 = fmaxf(S[0], S[1]), x1 = fmaxf(S[2], S[3]);
#pragma unroll
    for (int i = 1; i < 10; i++) { x0 = fmaxf(x0, fmaxf(S[4 * i], S[4 * i + 1])); x1 = fmaxf(x1, fmaxf(S[4 * i + 2], S[4 * i + 3])); }
    x0 = fmaxf(x0, __shfl_xor_sync(0xffffffff, x0, 1)); x1 = fmaxf(x1, __shfl_xor_sync(0xffffffff, x1, 1));
    x0 = fmaxf(x0, __shfl_xor_sync(0xffffffff, x0, 2)); x1 = fmaxf(x1, __shfl_xor_sync(0xffffffff, x1, 2));
    const float n0 = fmaxf(m0, x0), n1 = fmaxf(m1, x1);
    const float f0 = ex2(m0 - n0), f1 = ex2(m1 - n1);
    m0 = n0; m1 = n1; l0 *= f0; l1 *= f1;
#pragma unroll
    for (int i = 0; i < 8; i++) { O[4 * i] *= f0; O[4 * i + 1] *= f0; O[4 * i + 2] *= f1; O[4 * i + 3] *= f1; }
  }
#pragma unroll
  for (int i = 0; i < 10; i++) {
    float p0, p1, p2, p3;
    if (SAFE) { p0 = ex2(S[4 * i] - m0); p1 = ex2(S[4 * i + 1] - m0); p2 = ex2(S[4 * i + 2] - m1); p3 = ex2(S[4 * i + 3] - m1); }
    else { p0 = ex2(S[4 * i]); p1 = ex2(S[4 * i + 1]); p2 = ex2(S[4 * i + 2]); p3 = ex2(S[4 * i + 3]); }
    l0 += p0 + p1; l1 += p2 + p3;
    P[2 * i] = pack_bf16(p0, p1); P[2 * i + 1] = pack_bf16(p2, p3);
  }
}
template<bool SAFE>
__device__ __forceinline__ void att_pass(const AttCtx& a, uint32_t dQ, float (&O)[32], float& l0, float& l1) {
  float S[40];
  uint32_t P[20];
  float m0 = -INFINITY, m1 = -INFINITY;
  l0 = 0.f; l1 = 0.f;
#pragma unroll
  for (int i = 0; i < 32; i++) O[i] = 0.f;
  const uint32_t dKV = dlo(a.sKV, 16);
  constexpr uint32_t STG = 2 * KVB / 16, VOFF = KVB / 16, HALF = 80 * 128 / 16;
  constexpr int UNR = SAFE ? 1 : 4;
  mbar_wait(a.full, a.dry);
  wg_fence(); att_qk(S, dQ, dKV); wg_commit(); wg_wait<0>();
  att_softmax<SAFE>(S, P, O, m0, m1, l0, l1);
  mbar_wait(a.full + 8 * NSTG, a.dry);
  wg_fence(); att_pv(O, P, dKV + VOFF); att_qk(S, dQ, dKV + HALF); wg_commit(); wg_wait<0>();
#pragma unroll 1
  for (int it0 = a.dry ? NKV - 1 - UNR : 0; it0 < NKV - 1; it0 += UNR) {
#pragma unroll
    for (int u = 0; u < UNR; u++) {
      const int it = it0 + u;
      const int s = SAFE ? (it & 3) : u, sn = (s + 1) & 3, sp = (s + 3) & 3;
      const uint32_t kb = dKV + s * STG, kn = dKV + sn * STG;
      att_softmax<SAFE>(S, P, O, m0, m1, l0, l1);
      mbar_wait(a.full + 8 * sn, (((it + 1) >> 2) | a.dry) & 1);
      wg_fence(); att_pv(O, P, kb + VOFF + HALF); att_qk(S, dQ, kn); wg_commit(); wg_wait<0>();
      if ((threadIdx.x & 127) == 0) {
        mbar_arrive(a.empty + 8 * s);
        if (a.wg == s && it >= 1 && it - 1 + NSTG < NKV && !a.dry) {
          mbar_wait(a.empty + 8 * sp, ((it - 1) >> 2) & 1);
          att_load_stage(a, it - 1 + NSTG);
        }
      }
      __syncwarp();
      att_softmax<SAFE>(S, P, O, m0, m1, l0, l1);
      mbar_wait(a.full + 8 * (NSTG + sn), (((it + 1) >> 2) | a.dry) & 1);
      wg_fence(); att_pv(O, P, kn + VOFF); att_qk(S, dQ, kn + HALF); wg_commit(); wg_wait<0>();
    }
  }
  att_softmax<SAFE>(S, P, O, m0, m1, l0, l1);
  wg_fence(); att_pv(O, P, dKV + ((NKV - 1) & 3) * STG + VOFF + HALF); wg_commit(); wg_wait<0>();
  l0 += __shfl_xor_sync(0xffffffff, l0, 1); l1 += __shfl_xor_sync(0xffffffff, l1, 1);
  l0 += __shfl_xor_sync(0xffffffff, l0, 2); l1 += __shfl_xor_sync(0xffffffff, l1, 2);
}

struct Wptrs { const void* p[8]; uint32_t bytes[8]; };
struct Maps { CUtensorMap X, W1a, W1b, Wqkv, QKVst, Q, KV, Wo, Pw1, Pw2, W2a, W2b, Out; };

constexpr uint32_t B_FULL = 0, B_EMPTY = 8 * RING, B_X = 16 * RING, B_ADONE = B_X + 8, B_Q = B_X + 16, B_EP = B_X + 24, B_ATT = B_X + 32;

__global__ void __launch_bounds__(512, 1) conformer_kernel(const __grid_constant__ Maps tm, const __grid_constant__ Wptrs wp, const uint4* __restrict__ dw) {
  extern __shared__ uint8_t smem_raw[];
  const uint32_t base = (smem_u32(smem_raw) + 1023) & ~1023u, misc = base + OFF_MISC;
  const uint32_t dry = blockIdx.x >= 128;
  const int tile = dry ? 0 : blockIdx.x;
  const bool has_tile = dry ? blockIdx.x == 128 : tile < NTILE;
  const int wg = __shfl_sync(0xffffffff, (int)(threadIdx.x >> 7), 0);
  AttCtx a;
  a.sKV = base + OFF_W; a.full = misc + B_ATT; a.empty = a.full + 16 * NSTG; a.tmKV = &tm.KV;
  a.h = (blockIdx.x >> 4) & 3; a.b = (blockIdx.x >> 6) & 1; a.wg = wg; a.dry = dry;
  const int qt = blockIdx.x & 15;

  if (threadIdx.x == 256) {
    mbar_init(misc + B_X, 1);
    asm volatile("fence.mbarrier_init.release.cluster;" ::: "memory");
    if (has_tile && !dry) { mbar_expect_tx(misc + B_X, 32768); tma_load_3d(base + OFF_X, &tm.X, misc + B_X, 0, tile * 64, 0); }
    for (int i = 0; i < RING; i++) { mbar_init(misc + B_FULL + 8 * i, 1); mbar_init(misc + B_EMPTY + 8 * i, 1); }
    mbar_init(misc + B_ADONE, 2);
    mbar_init(misc + B_Q, 1);
    mbar_init(misc + B_EP, 1);
    att_init_bars(a);
    asm volatile("fence.mbarrier_init.release.cluster;" ::: "memory");
  } else if (threadIdx.x >= 320 && threadIdx.x < 333) {
    prefetch_tmap(&tm.X + (threadIdx.x - 320));
  }
  __syncthreads();
  auto get_epoch = [&]() {
    uint32_t e;
    mbar_wait(misc + B_EP, 0);
    asm volatile("ld.shared.u32 %0, [%1];" : "=r"(e) : "r"(misc + 248) : "memory");
    return e;
  };

  if (wg >= 2) {
    asm volatile("setmaxnreg.dec.sync.aligned.u32 24;");
    const uint32_t sW = base + OFF_W, full = misc + B_FULL, empty = misc + B_EMPTY;
    if (threadIdx.x == 320) {
      const uint32_t e = atomicAdd(&g_start, 1) / NCTA;
      asm volatile("st.shared.u32 [%0], %1;" :: "r"(misc + 248), "r"(e + 1) : "memory");
      mbar_arrive(misc + B_EP);
    }
    if (dry) {
    } else if (threadIdx.x == 256) {
      if (has_tile) {
        produce_ff(sW, full, empty, 0, &tm.W1a, &tm.W1b);
#pragma unroll 1
        for (int m = 0; m < 12; m++) produce(sW, full, empty, 32 + m, &tm.Wqkv, 128 * (m & 1), 2 * (m >> 1));
        mbar_wait(misc + B_ADONE, 0);
      }
      cnt_wait(g_cnt1 + a.b * 64, 126 * get_epoch());
      mbar_expect_tx(misc + B_Q, 32768);
      tma_load_3d(base, &tm.Q, misc + B_Q, a.h * 64, qt * 256, a.b);
      for (int i = 0; i < NSTG; i++) att_load(a, i, 0);
    } else if (threadIdx.x == 384) {
      if (has_tile) mbar_wait(misc + B_ADONE, 0);
      cnt_wait(g_cnt1 + a.b * 64 + 32, 126 * get_epoch());
      for (int i = 0; i < NSTG; i++) att_load(a, i, 1);
    } else if (has_tile && threadIdx.x >= 288 && threadIdx.x < 296) {
      const int w = threadIdx.x - 288;
      mbar_wait(misc + B_X, 0);
      const uint32_t bytes = wp.bytes[w], per = ((bytes / NTILE) + 127) & ~127u, off = per * tile;
      if (off < bytes) l2_prefetch((const uint8_t*)wp.p[w] + off, min(per, bytes - off));
    } else if (has_tile && threadIdx.x >= 416) {
      mbar_wait(full, 0);
      const int t = threadIdx.x - 416;
#pragma unroll 2
      for (int i = t; i < 2048; i += 96) g_att[tile * 2048 + i] = make_uint4(~0u, ~0u, ~0u, ~0u);
      g_halo[tile * 128 + t] = make_uint4(~0u, ~0u, ~0u, ~0u);
      if (t < 32) g_halo[tile * 128 + 96 + t] = make_uint4(~0u, ~0u, ~0u, ~0u);
    }
    __syncwarp();
    bar_sync(5 + wg, 384);
    asm volatile("setmaxnreg.inc.sync.aligned.u32 128;");
  } else {
    asm volatile("setmaxnreg.inc.sync.aligned.u32 232;");
    if (has_tile) {
      const Ctx c = make_ctx(base, dry);
      if (c.wg == 1) turn_end(c);
      float own[64];
      float a0, b0, a1, b1;
      PROF_MARK(0, 0);
      mbar_wait(misc + B_X, dry);
      PROF_MARK(0, 1);
      load_half(c, c.sX, own);
      ln_stats(c, own, 0.5f, a0, b0, a1, b1);
      store_half(c, c.sA, own, a0, b0, a1, b1);
      fence_async_smem();
      bar_sync(1, 256);
      PROF_MARK(0, 2);
      ff_block(c, 0, own);
      PROF_MARK(0, 3);
      ln_stats(c, own, 1.f, a0, b0, a1, b1);
      store_half(c, c.sA, own, a0, b0, a1, b1);
      fence_async_smem();
      bar_sync(1, 256);
      PROF_MARK(0, 4);
#pragma unroll 1
      for (int cc = dry ? 2 : 0; cc < 3; cc++) {
        float acc[64];
        const int j = 2 * cc + c.wg;
        gemm256<1>(c, acc, 32 + 2 * j);
        const float sc = (cc == 0) ? 0.125f * 1.4426950408889634f : 1.f;
        if (c.tid == 0 && !dry) {
          if (cc == 2) {
            mbar_arrive(misc + B_ADONE);
            bulk_wait_all();
            if (tile <= 62) cnt_signal(g_cnt1);
            if (tile >= 62) cnt_signal(g_cnt1 + 64);
          } else bulk_wait_read();
        }
        bar_sync(3 + c.wg, 128);
        store_half(c, c.sX, acc, sc, 0.f, sc, 0.f);
        fence_async_smem();
        bar_sync(3 + c.wg, 128);
        if (c.tid == 0 && !dry) { tma_store_3d(&tm.QKVst, c.sX + c.wg * 16384, 0, tile * 64, 2 * j); bulk_commit(); }
      }
      PROF_MARK(0, 5);
      if (c.tid == 0) bulk_wait_read();
      bar_sync(3 + c.wg, 128);
      store_half_raw(c, c.sX, own);
    }
    else bar_sync(3 + wg, 128);
    asm volatile("setmaxnreg.dec.sync.aligned.u32 128;");
    bar_arrive(7, 384); bar_arrive(8, 384);
    if (has_tile && !dry && (threadIdx.x & 127) == 0) {
      bulk_wait_all();
      if (tile <= 62) cnt_signal(g_cnt1 + 32);
      if (tile >= 62) cnt_signal(g_cnt1 + 96);
    }
    __syncwarp();
    PROF_MARK(0, 6);
  }

  if (blockIdx.x == 128) return;
  if (blockIdx.x != 130) {
    const int lane = threadIdx.x & 31, wq = (threadIdx.x >> 5) & 3;
    const uint32_t dQ = dlo(base + wg * 8192, 16);
    float O[32], l0, l1;
    PROF_MARK(1, 1);
    mbar_wait(misc + B_Q, dry);
    PROF_MARK(1, 2);
    att_pass<false>(a, dQ, O, l0, l1);
    PROF_MARK(1, 3);
    float z = 0.f;
#pragma unroll
    for (int i = 0; i < 32; i++) z = fmaf(O[i], 0.f, z);
    const bool ok = (l0 >= 0x1p-80f) && (l0 <= 0x1p100f) && (l1 >= 0x1p-80f) && (l1 <= 0x1p100f) && (z == 0.f);
    const bool warp_bad = !__all_sync(0xffffffff, ok) && !dry;
    auto store_out = [&]() {
      const float i0 = 1.f / l0, i1 = 1.f / l1;
      const int row = qt * 256 + wg * 64 + wq * 16;
      if (row < T_ && !dry) {
        const int slab = (a.b * T_ + row) / 16;
        uint4* op = g_att + (slab * 16 + a.h * 4) * 32 + lane;
#pragma unroll
        for (int j = 0; j < 4; j++)
          asm volatile("st.relaxed.gpu.global.v4.u32 [%0], {%1,%2,%3,%4};" :: "l"(op + j * 32),
                       "r"(pack_bf16(O[8 * j] * i0, O[8 * j + 1] * i0)), "r"(pack_bf16(O[8 * j + 2] * i1, O[8 * j + 3] * i1)),
                       "r"(pack_bf16(O[8 * j + 4] * i0, O[8 * j + 5] * i0)), "r"(pack_bf16(O[8 * j + 6] * i1, O[8 * j + 7] * i1)) : "memory");
        __syncwarp();
        if (lane == 0) cnt_signal(g_cnt2 + slab);
      }
      PROF_MARK(1, 4);
    };
    if (!warp_bad) store_out();
    if (__syncthreads_or(warp_bad)) {
      if (threadIdx.x == 0) {
        for (int i = 0; i < 3 * NSTG; i++) mbar_inval(a.full + 8 * i);
        att_init_bars(a);
        asm volatile("fence.mbarrier_init.release.cluster;" ::: "memory");
        fence_async_smem();
        for (int i = 0; i < NSTG; i++) att_load_stage(a, i);
      }
      __syncthreads();
      att_pass<true>(a, dQ, O, l0, l1);
      if (warp_bad) store_out();
      __syncthreads();
    }
    PROF_MARK(1, 5);
  } else {
    __syncthreads();
  }
  if (dry ? blockIdx.x != 130 : !has_tile) return;

  constexpr int NC = 44;
  if (wg >= 2) {
    asm volatile("setmaxnreg.dec.sync.aligned.u32 24;");
    if (threadIdx.x == 256 && !dry) {
      const uint32_t sW = base + OFF_W, full = misc + B_FULL, empty = misc + B_EMPTY;
#pragma unroll 1
      for (int m = 0; m < 4; m++) produce(sW, full, empty, NC + m, &tm.Wo, 128 * (m & 1), 2 * (m >> 1));
#pragma unroll 1
      for (int m = 0; m < 8; m++) produce(sW, full, empty, NC + 4 + m, &tm.Pw1, 128 * (m & 1), 0, 64 * (2 * ((m >> 1) & 1) + (m >> 2)));
#pragma unroll 1
      for (int m = 0; m < 4; m++) produce(sW, full, empty, NC + 12 + m, &tm.Pw2, 128 * (m & 1), 2 * (m >> 1));
      produce_ff(sW, full, empty, NC + 16, &tm.W2a, &tm.W2b);
    }
  } else {
    asm volatile("setmaxnreg.inc.sync.aligned.u32 232;");
    const Ctx c = make_ctx(base, dry);
    if (dry && c.wg == 1) turn_end(c);
    float own[64];
    float a0, b0, a1, b1;
    PROF_MARK(2, 0);
    load_half(c, c.sX, own);
    {
      uint4 af[16];
      const int slab = tile * 4 + (c.tid >> 5);
      const uint4* ap = g_att + slab * 512 + c.lane;
      if (c.lane == 0 && !dry) cnt_wait(g_cnt2 + slab, 4 * get_epoch());
      __syncwarp();
      PROF_MARK(2, 1);
      for (uint32_t n = 0; n < (1u << 24); n++) {
        bool any = false;
#pragma unroll
        for (int i = 0; i < 16; i++)
          asm volatile("ld.relaxed.gpu.global.v4.u32 {%0,%1,%2,%3}, [%4];" : "=r"(af[i].x), "=r"(af[i].y), "=r"(af[i].z), "=r"(af[i].w) : "l"(ap + i * 32) : "memory");
#pragma unroll
        for (int i = 0; i < 16; i++) any |= max(max(af[i].x, af[i].y), max(af[i].z, af[i].w)) == ~0u;
        if (!__any_sync(0xffffffff, any) || dry) break;
      }
      PROF_MARK(2, 2);
      const int n = NC + 2 * c.wg;
      uint32_t b = stage_wait(c, n) + ((16384 >> 4) << 16);
      turn_begin(c);
      wg_fence();
#pragma unroll
      for (int kk = 0; kk < 8; kk++) wg_rs_n128_tb1<1>(own, af[kk].x, af[kk].y, af[kk].z, af[kk].w, b + kk * 128);
      wg_commit();
      b = stage_wait(c, n + 1) + ((16384 >> 4) << 16);
      wg_fence();
#pragma unroll
      for (int kk = 0; kk < 8; kk++) wg_rs_n128_tb1<1>(own, af[8 + kk].x, af[8 + kk].y, af[8 + kk].z, af[8 + kk].w, b + kk * 128);
      wg_commit();
      turn_end(c);
      wg_wait<1>(); stage_release(c, n);
      wg_wait<0>(); stage_release(c, n + 1);
    }
    PROF_MARK(2, 3);
    ln_stats(c, own, 0.5f, a0, b0, a1, b1);
    store_half(c, c.sA, own, a0, b0, a1, b1);
    fence_async_smem();
    bar_sync(1, 256);
    PROF_MARK(2, 4);
    uint4 dwr[5];
#pragma unroll
    for (int i = 0; i < 5; i++) dwr[i] = __ldg(dw + i * 32 + c.lane);
    const bool top = c.tid < 8, pub = (top || c.tid >= 120) && !dry;
    uint32_t* halo_out = (uint32_t*)g_halo + (tile * 4 + (top ? (c.tid >> 2) : ((c.tid >> 2) - 28))) * 128 + c.wg * 64 + (c.lane & 3);
#pragma unroll 1
    for (int q = dry; q < 2; q++) {
      float ab[64];
      gemm256<1>(c, ab, NC + 4 + 4 * q + 2 * c.wg);
#pragma unroll
      for (int j = 0; j < 4; j++) {
        float g[8];
#pragma unroll
        for (int i = 0; i < 8; i++) g[i] = fmaf(ab[8 * j + i], tanh_fast(ab[32 + 8 * j + i]), ab[8 * j + i]);
        const uint32_t p0 = pack_bf16(g[0], g[1]), p1 = pack_bf16(g[2], g[3]), p2 = pack_bf16(g[4], g[5]), p3 = pack_bf16(g[6], g[7]);
        if (pub) {
          uint32_t* hp = halo_out + q * 32 + j * 8;
          asm volatile("st.relaxed.gpu.global.u32 [%0], %1;" :: "l"(hp), "r"(top ? p0 : p1) : "memory");
          asm volatile("st.relaxed.gpu.global.u32 [%0], %1;" :: "l"(hp + 4), "r"(top ? p2 : p3) : "memory");
        }
        stsm_x4(c.sX + (2 * c.wg + q) * 8192 + c.frag + (((j * 2 + c.hi) ^ c.rsw) << 4), p0, p1, p2, p3);
      }
    }
    bar_sync(1, 256);
    PROF_MARK(2, 5);
    {
      const int wi = threadIdx.x >> 5;
      const uint32_t col = (c.lane >> 3) * 8192, ch = c.lane & 7;
      uint4 r[12];
#pragma unroll
      for (int i = 0; i < 12; i++) {
        const int row = (wi * 8 - 2 + i) & 63;
        r[i] = lds128(c.sX + col + row * 128 + ((ch ^ (row & 7)) << 4));
      }
      uint32_t w[5][4];
#pragma unroll
      for (int k = 0; k < 5; k++) {
        w[k][0] = bmul2(dwr[k].x, 0x3F003F00u); w[k][1] = bmul2(dwr[k].y, 0x3F003F00u);
        w[k][2] = bmul2(dwr[k].z, 0x3F003F00u); w[k][3] = bmul2(dwr[k].w, 0x3F003F00u);
      }
      auto conv_row = [&](int i) {
        uint32_t o[4];
#pragma unroll
        for (int q = 0; q < 4; q++) {
          uint32_t acc = bmul2(q == 0 ? r[i].x : q == 1 ? r[i].y : q == 2 ? r[i].z : r[i].w, w[0][q]);
#pragma unroll
          for (int k = 1; k < 5; k++) acc = bfma2(q == 0 ? r[i + k].x : q == 1 ? r[i + k].y : q == 2 ? r[i + k].z : r[i + k].w, w[k][q], acc);
          o[q] = pack_bf16(silu_half(bf_lo(acc)), silu_half(bf_hi(acc)));
        }
        sts128(c.sA + col + (wi * 8 + i) * 128 + ((ch ^ i) << 4), make_uint4(o[0], o[1], o[2], o[3]));
      };
      conv_row(2); conv_row(3); conv_row(4); conv_row(5);
      const int R0 = tile * 64 + wi * 8;
      if ((R0 % T_) == 0) { r[0] = make_uint4(0, 0, 0, 0); r[1] = r[0]; }
      else if (wi == 0 && !dry) { const uint4* sp = g_halo + ((tile - 1) * 4 + 2) * 32 + c.lane; data_poll(sp, r[0]); data_poll(sp + 32, r[1]); }
      if (((R0 + 8) % T_) == 0) { r[10] = make_uint4(0, 0, 0, 0); r[11] = r[10]; }
      else if (wi == 7 && !dry) { const uint4* sp = g_halo + ((tile + 1) * 4) * 32 + c.lane; data_poll(sp, r[10]); data_poll(sp + 32, r[11]); }
      conv_row(0); conv_row(1); conv_row(6); conv_row(7);
    }
    fence_async_smem();
    bar_sync(1, 256);
    PROF_MARK(2, 6);
    gemm256<0>(c, own, NC + 12 + 2 * c.wg);
    PROF_MARK(2, 7);
    ln_stats(c, own, 0.5f, a0, b0, a1, b1);
    store_half(c, c.sA, own, a0, b0, a1, b1);
    fence_async_smem();
    bar_sync(1, 256);
    PROF_MARK(2, 8);
    ff_block(c, NC + 16, own);
    PROF_MARK(2, 9);
    ln_stats(c, own, 1.f, a0, b0, a1, b1);
    store_half(c, c.sX, own, a0, b0, a1, b1);
    fence_async_smem();
    bar_sync(3 + c.wg, 128);
    if (c.tid == 0 && !dry) { tma_store_3d(&tm.Out, c.sX + c.wg * 16384, 0, tile * 64, 2 * c.wg); bulk_commit(); PROF_MARK(2, 10); bulk_wait_all(); }
    PROF_MARK(2, 11);
  }
}

typedef CUresult (*EncodeFn)(CUtensorMap*, CUtensorMapDataType, cuuint32_t, void*, const cuuint64_t*, const cuuint64_t*, const cuuint32_t*,
                             const cuuint32_t*, CUtensorMapInterleave, CUtensorMapSwizzle, CUtensorMapL2promotion, CUtensorMapFloatOOBfill);

CUtensorMap make_map(EncodeFn enc, const void* p, uint64_t d0, uint64_t d1, uint64_t d2, uint64_t s1, uint64_t s2, uint32_t b1, uint32_t b2) {
  CUtensorMap tm;
  cuuint64_t dims[3] = {d0, d1, d2};
  cuuint64_t strides[2] = {s1, s2};
  cuuint32_t box[3] = {64, b1, b2};
  cuuint32_t es[3] = {1, 1, 1};
  enc(&tm, CU_TENSOR_MAP_DATA_TYPE_BFLOAT16, 3, const_cast<void*>(p), dims, strides, box, es, CU_TENSOR_MAP_INTERLEAVE_NONE,
      CU_TENSOR_MAP_SWIZZLE_128B, CU_TENSOR_MAP_L2_PROMOTION_L2_256B, CU_TENSOR_MAP_FLOAT_OOB_FILL_NONE);
  return tm;
}
CUtensorMap blk_map(EncodeFn enc, const void* p, uint64_t rows, uint64_t cols, uint32_t boxrows, uint32_t boxblks) {
  return make_map(enc, p, 64, rows, cols / 64, cols * 2, 128, boxrows, boxblks);
}
CUtensorMap seq_map(EncodeFn enc, const void* p, uint64_t cols, uint32_t boxrows) {
  return make_map(enc, p, cols, T_, 2, cols * 2, cols * 2 * T_, boxrows, 1);
}

}

extern "C" void kernel_launch(void* const* d_in, const int* in_sizes, int n_in, void* d_out, int out_size) {
  (void)in_sizes; (void)n_in; (void)out_size;
  const void *x = d_in[0], *w1a = d_in[1], *w1b = d_in[2], *wqkv = d_in[3], *wo = d_in[4], *pw1 = d_in[5], *dw = d_in[6], *pw2 = d_in[7],
             *w2a = d_in[8], *w2b = d_in[9];
  void* fn = nullptr;
  cudaDriverEntryPointQueryResult qr;
  cudaGetDriverEntryPoint("cuTensorMapEncodeTiled", &fn, cudaEnableDefault, &qr);
  EncodeFn enc = (EncodeFn)fn;
  void* qkv;
  cudaGetSymbolAddress(&qkv, g_qkv);
  cudaFuncSetAttribute(conformer_kernel, cudaFuncAttributeMaxDynamicSharedMemorySize, SMEM_BYTES);

  Wptrs wp;
  const void* ws[8] = {w1a, w1b, wqkv, wo, pw1, pw2, w2a, w2b};
  const uint32_t wb[8] = {524288, 524288, 393216, 131072, 262144, 131072, 524288, 524288};
  for (int i = 0; i < 8; i++) { wp.p[i] = ws[i]; wp.bytes[i] = wb[i]; }
  Maps tm;
  tm.X = blk_map(enc, x, ROWS, 256, 64, 4);
  tm.W1a = blk_map(enc, w1a, 256, 1024, 256, 1);
  tm.W1b = blk_map(enc, w1b, 1024, 256, 64, 4);
  tm.Wqkv = blk_map(enc, wqkv, 256, 768, 128, 2);
  tm.QKVst = blk_map(enc, qkv, ROWS, 768, 64, 2);
  tm.Q = seq_map(enc, qkv, 768, 256);
  tm.KV = seq_map(enc, qkv, 768, 160);
  tm.Wo = blk_map(enc, wo, 256, 256, 128, 2);
  tm.Pw1 = make_map(enc, pw1, 256, 256, 2, 1024, 512, 128, 2);
  tm.Pw2 = blk_map(enc, pw2, 256, 256, 128, 2);
  tm.W2a = blk_map(enc, w2a, 256, 1024, 256, 1);
  tm.W2b = blk_map(enc, w2b, 1024, 256, 64, 4);
  tm.Out = blk_map(enc, d_out, ROWS, 256, 64, 2);
  conformer_kernel<<<NCTA, 512, SMEM_BYTES, cudaStreamPerThread>>>(tm, wp, (const uint4*)dw);
}
```

```cpp
#include <cuda_runtime.h>
#include <cuda_bf16.h>
#include <cuda.h>
#include <stdint.h>

namespace {

constexpr int T_ = 4000;
constexpr int ROWS = 8000;
constexpr int NTILE = 125;
constexpr int NCTA = 131;

__device__ __nv_bfloat16 g_qkv[ROWS * 768];
__device__ uint4 g_att[(ROWS / 16) * 16 * 32];
__device__ uint4 g_halo[NTILE * 4 * 32];
__device__ uint32_t g_start;
__device__ uint32_t g_cnt1[4 * 32];
__device__ uint32_t g_cnt2[ROWS / 16];

#define PROF_MARK(k, i) do {} while (0)
#define PROF_STG(n, i) do {} while (0)

__device__ __forceinline__ uint32_t smem_u32(const void* p) { return (uint32_t)__cvta_generic_to_shared(p); }
__device__ __forceinline__ void mbar_init(uint32_t bar, uint32_t cnt) { asm volatile("mbarrier.init.shared::cta.b64 [%0], %1;" :: "r"(bar), "r"(cnt) : "memory"); }
__device__ __forceinline__ void mbar_inval(uint32_t bar) { asm volatile("mbarrier.inval.shared::cta.b64 [%0];" :: "r"(bar) : "memory"); }
__device__ __forceinline__ void mbar_expect_tx(uint32_t bar, uint32_t bytes) { asm volatile("mbarrier.arrive.expect_tx.shared::cta.b64 _, [%0], %1;" :: "r"(bar), "r"(bytes) : "memory"); }
__device__ __forceinline__ void mbar_arrive(uint32_t bar) { asm volatile("mbarrier.arrive.shared::cta.b64 _, [%0];" :: "r"(bar) : "memory"); }
__device__ __forceinline__ void mbar_wait(uint32_t bar, uint32_t parity) {
  asm volatile("{\n.reg .pred p;\n.reg .u32 n;\n"
               "mbarrier.try_wait.parity.shared::cta.b64 p, [%0], %1;\n@p bra DONE_%=;\nmov.u32 n, 0;\n"
               "LOOP_%=:\nmbarrier.try_wait.parity.shared::cta.b64 p, [%0], %1;\n@p bra DONE_%=;\n"
               "add.u32 n, n, 1;\nsetp.lt.u32 p, n, 262144;\n@p bra LOOP_%=;\ntrap;\nDONE_%=:\n}\n" :: "r"(bar), "r"(parity) : "memory");
}
__device__ __forceinline__ void data_poll(const uint4* p, uint4& v) {
  asm volatile("{\n.reg .pred p;\n.reg .u32 n, t;\nmov.u32 n, 0;\n"
               "LOOP_%=:\nld.relaxed.gpu.global.v4.u32 {%0,%1,%2,%3}, [%4];\n"
               "max.u32 t, %0, %1;\nmax.u32 t, t, %2;\nmax.u32 t, t, %3;\nsetp.ne.u32 p, t, 0xFFFFFFFF;\n@p bra DONE_%=;\n"
               "add.u32 n, n, 1;\nsetp.lt.u32 p, n, 262144;\n@p bra LOOP_%=;\ntrap;\nDONE_%=:\n}\n"
               : "=&r"(v.x), "=&r"(v.y), "=&r"(v.z), "=&r"(v.w) : "l"(p) : "memory");
}
__device__ __forceinline__ void cnt_wait(const uint32_t* p, uint32_t target) {
  asm volatile("{\n.reg .pred p;\n.reg .u32 n, v;\nmov.u32 n, 0;\n"
               "LOOP_%=:\nld.relaxed.gpu.global.u32 v, [%0];\nsub.u32 v, v, %1;\nsetp.ge.s32 p, v, 0;\n@p bra DONE_%=;\n"
               "nanosleep.u32 40;\nadd.u32 n, n, 1;\nsetp.lt.u32 p, n, 262144;\n@p bra LOOP_%=;\ntrap;\nDONE_%=:\n}\n" :: "l"(p), "r"(target) : "memory");
}
__device__ __forceinline__ void cnt_signal(uint32_t* p) {
  asm volatile("red.relaxed.gpu.global.add.u32 [%0], 1;" :: "l"(p) : "memory");
}
__device__ __forceinline__ void tma_load_3d(uint32_t dst, const CUtensorMap* tm, uint32_t bar, int c0, int c1, int c2) {
  asm volatile("cp.async.bulk.tensor.3d.shared::cluster.global.mbarrier::complete_tx::bytes [%0], [%1, {%3, %4, %5}], [%2];"
    :: "r"(dst), "l"(tm), "r"(bar), "r"(c0), "r"(c1), "r"(c2) : "memory");
}
__device__ __forceinline__ void tma_store_3d(const CUtensorMap* tm, uint32_t src, int c0, int c1, int c2) {
  asm volatile("cp.async.bulk.tensor.3d.global.shared::cta.bulk_group [%0, {%2, %3, %4}], [%1];" :: "l"(tm), "r"(src), "r"(c0), "r"(c1), "r"(c2) : "memory");
}
__device__ __forceinline__ void bulk_commit() { asm volatile("cp.async.bulk.commit_group;" ::: "memory"); }
__device__ __forceinline__ void bulk_wait_read() { asm volatile("cp.async.bulk.wait_group.read 0;" ::: "memory"); }
__device__ __forceinline__ void bulk_wait_all() { asm volatile("cp.async.bulk.wait_group 0;" ::: "memory"); }
__device__ __forceinline__ void l2_prefetch(const void* p, uint32_t bytes) { asm volatile("cp.async.bulk.prefetch.L2.global [%0], %1;" :: "l"(p), "r"(bytes) : "memory"); }
__device__ __forceinline__ void prefetch_tmap(const CUtensorMap* tm) { asm volatile("prefetch.tensormap [%0];" :: "l"(tm) : "memory"); }
__device__ __forceinline__ void fence_async_smem() { asm volatile("fence.proxy.async.shared::cta;" ::: "memory"); }
__device__ __forceinline__ void wg_fence() { asm volatile("wgmma.fence.sync.aligned;" ::: "memory"); }
__device__ __forceinline__ void wg_commit() { asm volatile("wgmma.commit_group.sync.aligned;" ::: "memory"); }
template<int N> __device__ __forceinline__ void wg_wait() { asm volatile("wgmma.wait_group.sync.aligned %0;" :: "n"(N) : "memory"); }
__device__ __forceinline__ void bar_sync(int id, int n) { asm volatile("bar.sync %0, %1;" :: "r"(id), "r"(n) : "memory"); }
__device__ __forceinline__ void bar_arrive(int id, int n) { asm volatile("bar.arrive %0, %1;" :: "r"(id), "r"(n) : "memory"); }
__device__ __forceinline__ float ex2(float x) { float y; asm("ex2.approx.ftz.f32 %0, %1;" : "=f"(y) : "f"(x)); return y; }
__device__ __forceinline__ float tanh_fast(float x) { float y; asm("tanh.approx.f32 %0, %1;" : "=f"(y) : "f"(x)); return y; }
__device__ __forceinline__ uint32_t pack_bf16(float lo, float hi) { uint32_t r; asm("cvt.rn.bf16x2.f32 %0, %1, %2;" : "=r"(r) : "f"(hi), "f"(lo)); return r; }
__device__ __forceinline__ uint32_t bmul2(uint32_t a, uint32_t b) { uint32_t d; asm("mul.rn.bf16x2 %0, %1, %2;" : "=r"(d) : "r"(a), "r"(b)); return d; }
__device__ __forceinline__ uint32_t bfma2(uint32_t a, uint32_t b, uint32_t c) { uint32_t d; asm("fma.rn.bf16x2 %0, %1, %2, %3;" : "=r"(d) : "r"(a), "r"(b), "r"(c)); return d; }
__device__ __forceinline__ float bf_lo(uint32_t u) { return __uint_as_float(u << 16); }
__device__ __forceinline__ float bf_hi(uint32_t u) { return __uint_as_float(u & 0xffff0000u); }
__device__ __forceinline__ void ldsm_x4(uint32_t addr, uint32_t& r0, uint32_t& r1, uint32_t& r2, uint32_t& r3) {
  asm volatile("ldmatrix.sync.aligned.m8n8.x4.shared.b16 {%0,%1,%2,%3}, [%4];" : "=r"(r0), "=r"(r1), "=r"(r2), "=r"(r3) : "r"(addr) : "memory");
}
__device__ __forceinline__ void stsm_x4(uint32_t addr, uint32_t r0, uint32_t r1, uint32_t r2, uint32_t r3) {
  asm volatile("stmatrix.sync.aligned.m8n8.x4.shared.b16 [%0], {%1,%2,%3,%4};" :: "r"(addr), "r"(r0), "r"(r1), "r"(r2), "r"(r3) : "memory");
}
__device__ __forceinline__ void sts128(uint32_t addr, uint4 v) { asm volatile("st.shared.v4.b32 [%0], {%1,%2,%3,%4};" :: "r"(addr), "r"(v.x), "r"(v.y), "r"(v.z), "r"(v.w) : "memory"); }
__device__ __forceinline__ uint4 lds128(uint32_t addr) { uint4 v; asm volatile("ld.shared.v4.b32 {%0,%1,%2,%3}, [%4];" : "=r"(v.x), "=r"(v.y), "=r"(v.z), "=r"(v.w) : "r"(addr) : "memory"); return v; }
__device__ __forceinline__ void sts64f(uint32_t addr, float a, float b) { asm volatile("st.shared.v2.f32 [%0], {%1,%2};" :: "r"(addr), "f"(a), "f"(b) : "memory"); }
__device__ __forceinline__ float2 lds64f(uint32_t addr) { float2 v; asm volatile("ld.shared.v2.f32 {%0,%1}, [%2];" : "=f"(v.x), "=f"(v.y) : "r"(addr) : "memory"); return v; }
__device__ __forceinline__ uint32_t dlo(uint32_t addr, uint32_t lbo) { return ((addr & 0x3FFFF) >> 4) | ((lbo >> 4) << 16); }

template<int SD> __device__ __forceinline__ void wg_ss_n128_tb1(float (&d)[64], uint32_t da, uint32_t db) {
  asm volatile("{\n.reg .b64 da, db;\nmov.b64 da, {%64, 0x40000040};\nmov.b64 db, {%65, 0x40000040};\n"
    "wgmma.mma_async.sync.aligned.m64n128k16.f32.bf16.bf16 {%0, %1, %2, %3, %4, %5, %6, %7, %8, %9, %10, %11, %12, %13, %14, %15, %16, %17, %18, %19, %20, %21, %22, %23, %24, %25, %26, %27, %28, %29, %30, %31, %32, %33, %34, %35, %36, %37, %38, %39, %40, %41, %42, %43, %44, %45, %46, %47, %48, %49, %50, %51, %52, %53, %54, %55, %56, %57, %58, %59, %60, %61, %62, %63}, da, db, %66, 1, 1, 0, 1;\n}\n"
    : "+f"(d[0]), "+f"(d[1]), "+f"(d[2]), "+f"(d[3]), "+f"(d[4]), "+f"(d[5]), "+f"(d[6]), "+f"(d[7]), "+f"(d[8]), "+f"(d[9]), "+f"(d[10]), "+f"(d[11]), "+f"(d[12]), "+f"(d[13]), "+f"(d[14]), "+f"(d[15]), "+f"(d[16]), "+f"(d[17]), "+f"(d[18]), "+f"(d[19]), "+f"(d[20]), "+f"(d[21]), "+f"(d[22]), "+f"(d[23]), "+f"(d[24]), "+f"(d[25]), "+f"(d[26]), "+f"(d[27]), "+f"(d[28]), "+f"(d[29]), "+f"(d[30]), "+f"(d[31]), "+f"(d[32]), "+f"(d[33]), "+f"(d[34]), "+f"(d[35]), "+f"(d[36]), "+f"(d[37]), "+f"(d[38]), "+f"(d[39]), "+f"(d[40]), "+f"(d[41]), "+f"(d[42]), "+f"(d[43]), "+f"(d[44]), "+f"(d[45]), "+f"(d[46]), "+f"(d[47]), "+f"(d[48]), "+f"(d[49]), "+f"(d[50]), "+f"(d[51]), "+f"(d[52]), "+f"(d[53]), "+f"(d[54]), "+f"(d[55]), "+f"(d[56]), "+f"(d[57]), "+f"(d[58]), "+f"(d[59]), "+f"(d[60]), "+f"(d[61]), "+f"(d[62]), "+f"(d[63])
    : "r"(da), "r"(db), "n"(SD));
}
template<int SD> __device__ __forceinline__ void wg_rs_n128_tb1(float (&d)[64], uint32_t a0, uint32_t a1, uint32_t a2, uint32_t a3, uint32_t db) {
  asm volatile("{\n.reg .b64 db;\nmov.b64 db, {%68, 0x40000040};\n"
    "wgmma.mma_async.sync.aligned.m64n128k16.f32.bf16.bf16 {%0, %1, %2, %3, %4, %5, %6, %7, %8, %9, %10, %11, %12, %13, %14, %15, %16, %17, %18, %19, %20, %21, %22, %23, %24, %25, %26, %27, %28, %29, %30, %31, %32, %33, %34, %35, %36, %37, %38, %39, %40, %41, %42, %43, %44, %45, %46, %47, %48, %49, %50, %51, %52, %53, %54, %55, %56, %57, %58, %59, %60, %61, %62, %63}, {%64, %65, %66, %67}, db, %69, 1, 1, 1;\n}\n"
    : "+f"(d[0]), "+f"(d[1]), "+f"(d[2]), "+f"(d[3]), "+f"(d[4]), "+f"(d[5]), "+f"(d[6]), "+f"(d[7]), "+f"(d[8]), "+f"(d[9]), "+f"(d[10]), "+f"(d[11]), "+f"(d[12]), "+f"(d[13]), "+f"(d[14]), "+f"(d[15]), "+f"(d[16]), "+f"(d[17]), "+f"(d[18]), "+f"(d[19]), "+f"(d[20]), "+f"(d[21]), "+f"(d[22]), "+f"(d[23]), "+f"(d[24]), "+f"(d[25]), "+f"(d[26]), "+f"(d[27]), "+f"(d[28]), "+f"(d[29]), "+f"(d[30]), "+f"(d[31]), "+f"(d[32]), "+f"(d[33]), "+f"(d[34]), "+f"(d[35]), "+f"(d[36]), "+f"(d[37]), "+f"(d[38]), "+f"(d[39]), "+f"(d[40]), "+f"(d[41]), "+f"(d[42]), "+f"(d[43]), "+f"(d[44]), "+f"(d[45]), "+f"(d[46]), "+f"(d[47]), "+f"(d[48]), "+f"(d[49]), "+f"(d[50]), "+f"(d[51]), "+f"(d[52]), "+f"(d[53]), "+f"(d[54]), "+f"(d[55]), "+f"(d[56]), "+f"(d[57]), "+f"(d[58]), "+f"(d[59]), "+f"(d[60]), "+f"(d[61]), "+f"(d[62]), "+f"(d[63])
    : "r"(a0), "r"(a1), "r"(a2), "r"(a3), "r"(db), "n"(SD));
}
template<int SD> __device__ __forceinline__ void wg_ss_n64_tb1(float (&d)[32], uint32_t da, uint32_t db) {
  asm volatile("{\n.reg .b64 da, db;\nmov.b64 da, {%32, 0x40000040};\nmov.b64 db, {%33, 0x40000040};\n"
    "wgmma.mma_async.sync.aligned.m64n64k16.f32.bf16.bf16 {%0, %1, %2, %3, %4, %5, %6, %7, %8, %9, %10, %11, %12, %13, %14, %15, %16, %17, %18, %19, %20, %21, %22, %23, %24, %25, %26, %27, %28, %29, %30, %31}, da, db, %34, 1, 1, 0, 1;\n}\n"
    : "+f"(d[0]), "+f"(d[1]), "+f"(d[2]), "+f"(d[3]), "+f"(d[4]), "+f"(d[5]), "+f"(d[6]), "+f"(d[7]), "+f"(d[8]), "+f"(d[9]), "+f"(d[10]), "+f"(d[11]), "+f"(d[12]), "+f"(d[13]), "+f"(d[14]), "+f"(d[15]), "+f"(d[16]), "+f"(d[17]), "+f"(d[18]), "+f"(d[19]), "+f"(d[20]), "+f"(d[21]), "+f"(d[22]), "+f"(d[23]), "+f"(d[24]), "+f"(d[25]), "+f"(d[26]), "+f"(d[27]), "+f"(d[28]), "+f"(d[29]), "+f"(d[30]), "+f"(d[31])
    : "r"(da), "r"(db), "n"(SD));
}
template<int SD> __device__ __forceinline__ void wg_ss_n80_tb0(float (&d)[40], uint32_t da, uint32_t db) {
  asm volatile("{\n.reg .b64 da, db;\nmov.b64 da, {%40, 0x40000040};\nmov.b64 db, {%41, 0x40000040};\n"
    "wgmma.mma_async.sync.aligned.m64n80k16.f32.bf16.bf16 {%0, %1, %2, %3, %4, %5, %6, %7, %8, %9, %10, %11, %12, %13, %14, %15, %16, %17, %18, %19, %20, %21, %22, %23, %24, %25, %26, %27, %28, %29, %30, %31, %32, %33, %34, %35, %36, %37, %38, %39}, da, db, %42, 1, 1, 0, 0;\n}\n"
    : "+f"(d[0]), "+f"(d[1]), "+f"(d[2]), "+f"(d[3]), "+f"(d[4]), "+f"(d[5]), "+f"(d[6]), "+f"(d[7]), "+f"(d[8]), "+f"(d[9]), "+f"(d[10]), "+f"(d[11]), "+f"(d[12]), "+f"(d[13]), "+f"(d[14]), "+f"(d[15]), "+f"(d[16]), "+f"(d[17]), "+f"(d[18]), "+f"(d[19]), "+f"(d[20]), "+f"(d[21]), "+f"(d[22]), "+f"(d[23]), "+f"(d[24]), "+f"(d[25]), "+f"(d[26]), "+f"(d[27]), "+f"(d[28]), "+f"(d[29]), "+f"(d[30]), "+f"(d[31]), "+f"(d[32]), "+f"(d[33]), "+f"(d[34]), "+f"(d[35]), "+f"(d[36]), "+f"(d[37]), "+f"(d[38]), "+f"(d[39])
    : "r"(da), "r"(db), "n"(SD));
}
template<int SD> __device__ __forceinline__ void wg_rs_n64_tb1(float (&d)[32], uint32_t a0, uint32_t a1, uint32_t a2, uint32_t a3, uint32_t db) {
  asm volatile("{\n.reg .b64 db;\nmov.b64 db, {%36, 0x40000040};\n"
    "wgmma.mma_async.sync.aligned.m64n64k16.f32.bf16.bf16 {%0, %1, %2, %3, %4, %5, %6, %7, %8, %9, %10, %11, %12, %13, %14, %15, %16, %17, %18, %19, %20, %21, %22, %23, %24, %25, %26, %27, %28, %29, %30, %31}, {%32, %33, %34, %35}, db, %37, 1, 1, 1;\n}\n"
    : "+f"(d[0]), "+f"(d[1]), "+f"(d[2]), "+f"(d[3]), "+f"(d[4]), "+f"(d[5]), "+f"(d[6]), "+f"(d[7]), "+f"(d[8]), "+f"(d[9]), "+f"(d[10]), "+f"(d[11]), "+f"(d[12]), "+f"(d[13]), "+f"(d[14]), "+f"(d[15]), "+f"(d[16]), "+f"(d[17]), "+f"(d[18]), "+f"(d[19]), "+f"(d[20]), "+f"(d[21]), "+f"(d[22]), "+f"(d[23]), "+f"(d[24]), "+f"(d[25]), "+f"(d[26]), "+f"(d[27]), "+f"(d[28]), "+f"(d[29]), "+f"(d[30]), "+f"(d[31])
    : "r"(a0), "r"(a1), "r"(a2), "r"(a3), "r"(db), "n"(SD));
}

constexpr int RING = 5;
constexpr uint32_t STAGE = 32768;
constexpr uint32_t OFF_X = 32768, OFF_W = 65536, OFF_MISC = OFF_W + RING * STAGE;
constexpr int SMEM_BYTES = OFF_MISC + 256 + 1024 + 1024;

struct Ctx {
  uint32_t sA, sX, sW, full, empty, stats;
  uint32_t frag;
  uint32_t rsw;
  uint32_t hi;
  int wg, tid, lane;
  int pk;
  uint32_t dry;
};
__device__ __forceinline__ uint32_t stage_wait(const Ctx& c, int n) {
  const int q = n / RING, s = n - q * RING;
  if (c.tid == 0) PROF_STG(n + c.pk, 1);
  mbar_wait(c.full + 8 * s, (q | c.dry) & 1);
  if (c.tid == 0) PROF_STG(n + c.pk, 2);
  return dlo(c.sW + s * STAGE, 0);
}
__device__ __forceinline__ void stage_release(const Ctx& c, int n) {
  const int s = n % RING;
  if (c.tid == 0) { mbar_arrive(c.empty + 8 * s); PROF_STG(n + c.pk, 3); }
}
__device__ __forceinline__ void turn_begin(const Ctx& c) { bar_sync(5 + c.wg, 256); }
__device__ __forceinline__ void turn_end(const Ctx& c) { bar_arrive(5 + (c.wg ^ 1), 256); }
template<int FIRST> __device__ __forceinline__ void piece_ss(float (&acc)[64], uint32_t dA, uint32_t dB) {
  dB += (16384 >> 4) << 16;
  wg_ss_n128_tb1<FIRST ? 0 : 1>(acc, dA, dB);
#pragma unroll
  for (int kk = 1; kk < 8; kk++) wg_ss_n128_tb1<1>(acc, dA + (kk >> 2) * 512 + (kk & 3) * 2, dB + kk * 128);
}
__device__ __forceinline__ void ff_g1(float (&h)[32], uint32_t dA, uint32_t dB) {
  wg_ss_n64_tb1<0>(h, dA, dB);
#pragma unroll
  for (int kk = 1; kk < 16; kk++) wg_ss_n64_tb1<1>(h, dA + (kk >> 2) * 512 + (kk & 3) * 2, dB + kk * 128);
}
__device__ __forceinline__ void ff_g2(float (&acc)[64], const uint32_t (&P)[16], uint32_t dB, int half) {
  dB += ((8192 >> 4) << 16) + half * 1024;
#pragma unroll
  for (int kk = 0; kk < 4; kk++) wg_rs_n128_tb1<1>(acc, P[4 * kk], P[4 * kk + 1], P[4 * kk + 2], P[4 * kk + 3], dB + kk * 128);
}
template<int FIRST> __device__ __forceinline__ void gemm256(const Ctx& c, float (&acc)[64], int n) {
  const uint32_t dA = dlo(c.sA, 16);
  uint32_t b = stage_wait(c, n);
  turn_begin(c);
  wg_fence(); piece_ss<FIRST>(acc, dA, b); wg_commit();
  b = stage_wait(c, n + 1);
  wg_fence(); piece_ss<0>(acc, dA + 1024, b); wg_commit();
  turn_end(c);
  wg_wait<1>(); stage_release(c, n);
  wg_wait<0>(); stage_release(c, n + 1);
}
__device__ __forceinline__ uint32_t frag_addr(const Ctx& c, uint32_t tile, int j) {
  return tile + (2 * c.wg + (j >> 2)) * 8192 + c.frag + ((((j & 3) * 2 + c.hi) ^ c.rsw) << 4);
}
__device__ __forceinline__ void load_half(const Ctx& c, uint32_t tile, float (&v)[64]) {
#pragma unroll
  for (int j = 0; j < 8; j++) {
    uint32_t r0, r1, r2, r3;
    ldsm_x4(frag_addr(c, tile, j), r0, r1, r2, r3);
    v[8 * j] = bf_lo(r0); v[8 * j + 1] = bf_hi(r0); v[8 * j + 2] = bf_lo(r1); v[8 * j + 3] = bf_hi(r1);
    v[8 * j + 4] = bf_lo(r2); v[8 * j + 5] = bf_hi(r2); v[8 * j + 6] = bf_lo(r3); v[8 * j + 7] = bf_hi(r3);
  }
}
__device__ __forceinline__ void store_half(const Ctx& c, uint32_t tile, const float (&v)[64], float a0, float b0, float a1, float b1) {
#pragma unroll
  for (int j = 0; j < 8; j++)
    stsm_x4(frag_addr(c, tile, j),
            pack_bf16(fmaf(v[8 * j], a0, b0), fmaf(v[8 * j + 1], a0, b0)), pack_bf16(fmaf(v[8 * j + 2], a1, b1), fmaf(v[8 * j + 3], a1, b1)),
            pack_bf16(fmaf(v[8 * j + 4], a0, b0), fmaf(v[8 * j + 5], a0, b0)), pack_bf16(fmaf(v[8 * j + 6], a1, b1), fmaf(v[8 * j + 7], a1, b1)));
}
__device__ __forceinline__ void store_half_raw(const Ctx& c, uint32_t tile, const float (&v)[64]) {
#pragma unroll
  for (int j = 0; j < 8; j++)
    stsm_x4(frag_addr(c, tile, j), pack_bf16(v[8 * j], v[8 * j + 1]), pack_bf16(v[8 * j + 2], v[8 * j + 3]),
            pack_bf16(v[8 * j + 4], v[8 * j + 5]), pack_bf16(v[8 * j + 6], v[8 * j + 7]));
}
__device__ __forceinline__ void ln_stats(const Ctx& c, const float (&v)[64], float scale, float& a0, float& b0, float& a1, float& b1) {
  float s0 = 0.f, s1 = 0.f, q0 = 0.f, q1 = 0.f, s2 = 0.f, s3 = 0.f, q2 = 0.f, q3 = 0.f;
#pragma unroll
  for (int i = 0; i < 16; i++) {
    s0 += v[4 * i]; q0 = fmaf(v[4 * i], v[4 * i], q0);
    s2 += v[4 * i + 1]; q2 = fmaf(v[4 * i + 1], v[4 * i + 1], q2);
    s1 += v[4 * i + 2]; q1 = fmaf(v[4 * i + 2], v[4 * i + 2], q1);
    s3 += v[4 * i + 3]; q3 = fmaf(v[4 * i + 3], v[4 * i + 3], q3);
  }
  s0 += s2; q0 += q2; s1 += s3; q1 += q3;
  s0 += __shfl_xor_sync(0xffffffff, s0, 1); q0 += __shfl_xor_sync(0xffffffff, q0, 1);
  s1 += __shfl_xor_sync(0xffffffff, s1, 1); q1 += __shfl_xor_sync(0xffffffff, q1, 1);
  s0 += __shfl_xor_sync(0xffffffff, s0, 2); q0 += __shfl_xor_sync(0xffffffff, q0, 2);
  s1 += __shfl_xor_sync(0xffffffff, s1, 2); q1 += __shfl_xor_sync(0xffffffff, q1, 2);
  const uint32_t row = (c.tid >> 5) * 16 + (c.lane >> 2);
  if ((c.lane & 3) == 0) {
    sts64f(c.stats + c.wg * 512 + row * 8, s0, q0);
    sts64f(c.stats + c.wg * 512 + (row + 8) * 8, s1, q1);
  }
  bar_sync(1, 256);
  const float2 o0 = lds64f(c.stats + (c.wg ^ 1) * 512 + row * 8), o1 = lds64f(c.stats + (c.wg ^ 1) * 512 + (row + 8) * 8);
  const float m0 = (s0 + o0.x) * (1.f / 256.f), m1 = (s1 + o1.x) * (1.f / 256.f);
  const float var0 = fmaxf(fmaf(-m0, m0, (q0 + o0.y) * (1.f / 256.f)), 0.f), var1 = fmaxf(fmaf(-m1, m1, (q1 + o1.y) * (1.f / 256.f)), 0.f);
  a0 = rsqrtf(var0 + 1e-5f) * scale; a1 = rsqrtf(var1 + 1e-5f) * scale;
  b0 = -m0 * a0; b1 = -m1 * a1;
}
__device__ __forceinline__ float silu_half(float h) { return fmaf(h, tanh_fast(h), h); }
__device__ __forceinline__ float silu_quarter(float h) { const float q = 0.5f * h; return fmaf(q, tanh_fast(h), q); }
__device__ __forceinline__ void silu_pack(const float (&acc)[32], uint32_t (&P)[16]) {
#pragma unroll
  for (int i = 0; i < 16; i++) P[i] = pack_bf16(silu_quarter(acc[2 * i]), silu_quarter(acc[2 * i + 1]));
}
__device__ __forceinline__ void ff_block(const Ctx& c, int n0, float (&own)[64]) {
  float oth[64], h[32];
  uint32_t P[16];
#pragma unroll
  for (int i = 0; i < 64; i++) oth[i] = 0.f;
  const uint32_t dA = dlo(c.sA, 16);
  {
    const uint32_t b = stage_wait(c, n0 + c.wg);
    turn_begin(c);
    wg_fence(); ff_g1(h, dA, b); wg_commit();
    turn_end(c);
    wg_wait<0>(); stage_release(c, n0 + c.wg);
    silu_pack(h, P);
  }
#pragma unroll 1
  for (int it = c.dry ? 7 : 1; it < 8; it++) {
    const int n = n0 + 4 * it - 2 + 2 * c.wg;
    uint32_t b = stage_wait(c, n);
    turn_begin(c);
    wg_fence(); ff_g2(own, P, b, c.wg); ff_g2(oth, P, b, c.wg ^ 1); wg_commit();
    b = stage_wait(c, n + 1);
    wg_fence(); ff_g1(h, dA, b); wg_commit();
    turn_end(c);
    wg_wait<1>(); stage_release(c, n);
    wg_wait<0>(); stage_release(c, n + 1);
    silu_pack(h, P);
  }
  if (c.wg == 0) bar_arrive(2, 256);
  {
    const int n = n0 + 30 + c.wg;
    const uint32_t b = stage_wait(c, n);
    turn_begin(c);
    wg_fence(); ff_g2(oth, P, b, c.wg ^ 1); wg_commit();
    ff_g2(own, P, b, c.wg); wg_commit();
    turn_end(c);
    wg_wait<1>();
    if (c.wg == 1) bar_sync(2, 256);
    const uint32_t e = (c.wg == 0 ? c.sX : c.sA) + c.tid * 16;
#pragma unroll
    for (int i = 0; i < 16; i++)
      sts128(e + i * 2048, make_uint4(__float_as_uint(oth[4 * i]), __float_as_uint(oth[4 * i + 1]), __float_as_uint(oth[4 * i + 2]), __float_as_uint(oth[4 * i + 3])));
    wg_wait<0>(); stage_release(c, n);
  }
  bar_sync(1, 256);
  const uint32_t e = (c.wg == 0 ? c.sA : c.sX) + c.tid * 16;
#pragma unroll
  for (int i = 0; i < 16; i++) {
    const uint4 u = lds128(e + i * 2048);
    own[4 * i] += __uint_as_float(u.x); own[4 * i + 1] += __uint_as_float(u.y);
    own[4 * i + 2] += __uint_as_float(u.z); own[4 * i + 3] += __uint_as_float(u.w);
  }
}
struct Maps { CUtensorMap X, W1a, W1b, Wqkv, QKVst, Q, KV, Wo, Pw1, Pw2, W2a, W2b, Out; };
constexpr int NC = 44;
__device__ __forceinline__ void produce(uint32_t sW, uint32_t full, uint32_t empty, const Maps& tm, int n0, int n1) {
#pragma unroll 1
  for (int n = n0; n < n1; n++) {
    const CUtensorMap* mp;
    int c0 = 0, k0, nb;
    if (n < 32 || n >= NC + 16) {
      const int m = n < 32 ? n : n - (NC + 16);
      const int is2 = m >= 2 && (!(m & 1) || m == 31);
      const int j = m < 2 ? m : (m == 31 ? 15 : ((m - 2) >> 1) + (is2 ? 0 : 2));
      mp = (n < 32 ? &tm.W1a : &tm.W2a) + is2;
      k0 = is2 ? 64 * j : 0; nb = is2 ? 0 : j;
    } else {
      k0 = 128 * (n & 1);
      if (n < NC) { mp = &tm.Wqkv; nb = (n - 32) & ~1; }
      else if (n < NC + 4) { mp = &tm.Wo; nb = n & 2; }
      else if (n < NC + 12) { mp = &tm.Pw1; nb = 0; c0 = 64 * ((n & 2) + ((n >> 2) & 1)); }
      else { mp = &tm.Pw2; nb = n & 2; }
    }
    const int q = n / RING, s = n - q * RING;
    mbar_wait(empty + 8 * s, (q & 1) ^ 1);
    mbar_expect_tx(full + 8 * s, STAGE);
    tma_load_3d(sW + s * STAGE, mp, full + 8 * s, c0, k0, nb);
  }
}
__device__ __forceinline__ Ctx make_ctx(uint32_t base, uint32_t dry, int pk = 0) {
  Ctx c; c.pk = pk; c.dry = dry;
  c.sA = base; c.sX = base + OFF_X; c.sW = base + OFF_W;
  c.full = base + OFF_MISC; c.empty = c.full + 8 * RING; c.stats = base + OFF_MISC + 256;
  c.wg = __shfl_sync(0xffffffff, (int)(threadIdx.x >> 7), 0);
  c.tid = threadIdx.x & 127; c.lane = threadIdx.x & 31;
  const uint32_t r = (c.tid >> 5) * 16 + (c.lane & 7) + ((c.lane >> 3) & 1) * 8;
  c.frag = r * 128; c.rsw = r & 7; c.hi = c.lane >> 4;
  return c;
}

constexpr int NSTG = 4;
constexpr int KVB = 160 * 128;
constexpr int NKV = T_ / 160;
static_assert(NSTG * 2 * KVB == RING * STAGE, "the K/V ring reuses the weight ring");

struct AttCtx { uint32_t sKV, full, empty, dry; const CUtensorMap* tmKV; int h, b, wg; };
__device__ __forceinline__ void att_load(const AttCtx& a, int i, int v) {
  const int s = i & (NSTG - 1);
  mbar_expect_tx(a.full + 8 * (s + v * NSTG), KVB);
  tma_load_3d(a.sKV + s * 2 * KVB + v * KVB, a.tmKV, a.full + 8 * (s + v * NSTG), 256 + v * 256 + a.h * 64, i * 160, a.b);
}
__device__ __forceinline__ void att_load_stage(const AttCtx& a, int i) { att_load(a, i, 0); att_load(a, i, 1); }
__device__ __forceinline__ void att_init_bars(const AttCtx& a) {
  for (int i = 0; i < NSTG; i++) { mbar_init(a.full + 8 * i, 1); mbar_init(a.full + 8 * (NSTG + i), 1); mbar_init(a.empty + 8 * i, 4); }
}
__device__ __forceinline__ void att_qk(float (&S)[40], uint32_t dQ, uint32_t kd) {
  wg_ss_n80_tb0<0>(S, dQ, kd);
#pragma unroll
  for (int kk = 1; kk < 4; kk++) wg_ss_n80_tb0<1>(S, dQ + kk * 2, kd + kk * 2);
}
__device__ __forceinline__ void att_pv(float (&O)[32], const uint32_t (&P)[20], uint32_t vd) {
#pragma unroll
  for (int kk = 0; kk < 5; kk++) wg_rs_n64_tb1<1>(O, P[kk * 4], P[kk * 4 + 1], P[kk * 4 + 2], P[kk * 4 + 3], vd + kk * 128);
}
template<bool SAFE>
__device__ __forceinline__ void att_softmax(const float (&S)[40], uint32_t (&P)[20], float (&O)[32], float& m0, float& m1, float& l0, float& l1) {
  if (SAFE) {
    float x0 = fmaxf(S[0], S[1]), x1 = fmaxf(S[2], S[3]);
#pragma unroll
    for (int i = 1; i < 10; i++) { x0 = fmaxf(x0, fmaxf(S[4 * i], S[4 * i + 1])); x1 = fmaxf(x1, fmaxf(S[4 * i + 2], S[4 * i + 3])); }
    x0 = fmaxf(x0, __shfl_xor_sync(0xffffffff, x0, 1)); x1 = fmaxf(x1, __shfl_xor_sync(0xffffffff, x1, 1));
    x0 = fmaxf(x0, __shfl_xor_sync(0xffffffff, x0, 2)); x1 = fmaxf(x1, __shfl_xor_sync(0xffffffff, x1, 2));
    const float n0 = fmaxf(m0, x0), n1 = fmaxf(m1, x1);
    const float f0 = ex2(m0 - n0), f1 = ex2(m1 - n1);
    m0 = n0; m1 = n1; l0 *= f0; l1 *= f1;
#pragma unroll
    for (int i = 0; i < 8; i++) { O[4 * i] *= f0; O[4 * i + 1] *= f0; O[4 * i + 2] *= f1; O[4 * i + 3] *= f1; }
  }
#pragma unroll
  for (int i = 0; i < 10; i++) {
    float p0, p1, p2, p3;
    if (SAFE) { p0 = ex2(S[4 * i] - m0); p1 = ex2(S[4 * i + 1] - m0); p2 = ex2(S[4 * i + 2] - m1); p3 = ex2(S[4 * i + 3] - m1); }
    else { p0 = ex2(S[4 * i]); p1 = ex2(S[4 * i + 1]); p2 = ex2(S[4 * i + 2]); p3 = ex2(S[4 * i + 3]); }
    l0 += p0 + p1; l1 += p2 + p3;
    P[2 * i] = pack_bf16(p0, p1); P[2 * i + 1] = pack_bf16(p2, p3);
  }
}
__device__ __forceinline__ void att_refill(const AttCtx& a, int it) {
  if ((threadIdx.x & 127) == 0) {
    mbar_arrive(a.empty + 8 * (it & 3));
    if (a.wg == (it & 3) && it >= 1 && it - 1 + NSTG < NKV && !a.dry) {
      mbar_wait(a.empty + 8 * ((it - 1) & 3), ((it - 1) >> 2) & 1);
      att_load_stage(a, it - 1 + NSTG);
    }
  }
  __syncwarp();
}
constexpr uint32_t KV_STG = 2 * KVB / 16, KV_VOFF = KVB / 16, KV_HALF = 80 * 128 / 16;
template<bool SAFE>
__device__ __forceinline__ void att_pass(const AttCtx& a, uint32_t dQ, float (&O)[32], float& l0, float& l1) {
  float S[40];
  uint32_t P[20];
  float m0 = -INFINITY, m1 = -INFINITY;
  l0 = 0.f; l1 = 0.f;
#pragma unroll
  for (int i = 0; i < 32; i++) O[i] = 0.f;
  const uint32_t dKV = dlo(a.sKV, 16);
  if (SAFE) {
#pragma unroll 1
    for (int j = 0; j < 2 * NKV; j++) {
      const int it = j >> 1, s = it & 3;
      const uint32_t kb = dKV + s * KV_STG + (j & 1) * KV_HALF;
      mbar_wait(a.full + 8 * s, (it >> 2) & 1);
      wg_fence(); att_qk(S, dQ, kb); wg_commit(); wg_wait<0>();
      att_softmax<true>(S, P, O, m0, m1, l0, l1);
      mbar_wait(a.full + 8 * (NSTG + s), (it >> 2) & 1);
      wg_fence(); att_pv(O, P, kb + KV_VOFF); wg_commit(); wg_wait<0>();
      if (j & 1) att_refill(a, it);
    }
  } else {
    mbar_wait(a.full, a.dry);
    wg_fence(); att_qk(S, dQ, dKV); wg_commit(); wg_wait<0>();
    att_softmax<false>(S, P, O, m0, m1, l0, l1);
    mbar_wait(a.full + 8 * NSTG, a.dry);
    wg_fence(); att_pv(O, P, dKV + KV_VOFF); att_qk(S, dQ, dKV + KV_HALF); wg_commit(); wg_wait<0>();
#pragma unroll 1
    for (int it = a.dry ? NKV - 2 : 0; it < NKV - 1; it++) {
      const int s = it & 3, sn = (it + 1) & 3;
      const uint32_t kb = dKV + s * KV_STG, kn = dKV + sn * KV_STG, par = (((it + 1) >> 2) | a.dry) & 1;
      att_softmax<false>(S, P, O, m0, m1, l0, l1);
      mbar_wait(a.full + 8 * sn, par);
      wg_fence(); att_pv(O, P, kb + KV_VOFF + KV_HALF); att_qk(S, dQ, kn); wg_commit(); wg_wait<0>();
      att_refill(a, it);
      att_softmax<false>(S, P, O, m0, m1, l0, l1);
      mbar_wait(a.full + 8 * (NSTG + sn), par);
      wg_fence(); att_pv(O, P, kn + KV_VOFF); att_qk(S, dQ, kn + KV_HALF); wg_commit(); wg_wait<0>();
    }
    att_softmax<false>(S, P, O, m0, m1, l0, l1);
    wg_fence(); att_pv(O, P, dKV + ((NKV - 1) & 3) * KV_STG + KV_VOFF + KV_HALF); wg_commit(); wg_wait<0>();
  }
  l0 += __shfl_xor_sync(0xffffffff, l0, 1); l1 += __shfl_xor_sync(0xffffffff, l1, 1);
  l0 += __shfl_xor_sync(0xffffffff, l0, 2); l1 += __shfl_xor_sync(0xffffffff, l1, 2);
}

struct Wptrs { const void* p[8]; uint32_t bytes[8]; };

constexpr uint32_t B_FULL = 0, B_EMPTY = 8 * RING, B_X = 16 * RING, B_ADONE = B_X + 8, B_Q = B_X + 16, B_EP = B_X + 24, B_ATT = B_X + 32;

__global__ void __launch_bounds__(512, 1) conformer_kernel(const __grid_constant__ Maps tm, const __grid_constant__ Wptrs wp, const uint4* __restrict__ dw) {
  extern __shared__ uint8_t smem_raw[];
  const uint32_t base = (smem_u32(smem_raw) + 1023) & ~1023u, misc = base + OFF_MISC;
  const uint32_t dry = blockIdx.x >= 128;
  const int tile = dry ? 0 : blockIdx.x;
  const bool has_tile = dry ? blockIdx.x == 128 : tile < NTILE;
  const int wg = __shfl_sync(0xffffffff, (int)(threadIdx.x >> 7), 0);
  AttCtx a;
  a.sKV = base + OFF_W; a.full = misc + B_ATT; a.empty = a.full + 16 * NSTG; a.tmKV = &tm.KV;
  a.h = (blockIdx.x >> 4) & 3; a.b = (blockIdx.x >> 6) & 1; a.wg = wg; a.dry = dry;
  const int qt = blockIdx.x & 15;

  if (threadIdx.x == 256) {
    mbar_init(misc + B_X, 1);
    asm volatile("fence.mbarrier_init.release.cluster;" ::: "memory");
    if (has_tile && !dry) { mbar_expect_tx(misc + B_X, 32768); tma_load_3d(base + OFF_X, &tm.X, misc + B_X, 0, tile * 64, 0); }
    for (int i = 0; i < RING; i++) { mbar_init(misc + B_FULL + 8 * i, 1); mbar_init(misc + B_EMPTY + 8 * i, 1); }
    mbar_init(misc + B_ADONE, 2);
    mbar_init(misc + B_Q, 1);
    mbar_init(misc + B_EP, 1);
    att_init_bars(a);
    asm volatile("fence.mbarrier_init.release.cluster;" ::: "memory");
  } else if (threadIdx.x >= 320 && threadIdx.x < 333) {
    prefetch_tmap(&tm.X + (threadIdx.x - 320));
  }
  __syncthreads();
  auto get_epoch = [&]() {
    uint32_t e;
    mbar_wait(misc + B_EP, 0);
    asm volatile("ld.shared.u32 %0, [%1];" : "=r"(e) : "r"(misc + 248) : "memory");
    return e;
  };

  if (wg >= 2) {
    asm volatile("setmaxnreg.dec.sync.aligned.u32 24;");
    const uint32_t sW = base + OFF_W, full = misc + B_FULL, empty = misc + B_EMPTY;
    if (threadIdx.x == 320) {
      const uint32_t e = atomicAdd(&g_start, 1) / NCTA;
      asm volatile("st.shared.u32 [%0], %1;" :: "r"(misc + 248), "r"(e + 1) : "memory");
      mbar_arrive(misc + B_EP);
    }
    if (dry) {
    } else if (threadIdx.x == 256) {
      if (has_tile) {
        produce(sW, full, empty, tm, 0, NC);
        mbar_wait(misc + B_ADONE, 0);
      }
      cnt_wait(g_cnt1 + a.b * 64, 126 * get_epoch());
      mbar_expect_tx(misc + B_Q, 32768);
      tma_load_3d(base, &tm.Q, misc + B_Q, a.h * 64, qt * 256, a.b);
#pragma unroll 1
      for (int i = 0; i < NSTG; i++) att_load(a, i, 0);
    } else if (threadIdx.x == 384) {
      if (has_tile) mbar_wait(misc + B_ADONE, 0);
      cnt_wait(g_cnt1 + a.b * 64 + 32, 126 * get_epoch());
#pragma unroll 1
      for (int i = 0; i < NSTG; i++) att_load(a, i, 1);
    } else if (has_tile && threadIdx.x >= 288 && threadIdx.x < 296) {
      const int w = threadIdx.x - 288;
      mbar_wait(misc + B_X, 0);
      const uint32_t bytes = wp.bytes[w], per = ((bytes / NTILE) + 127) & ~127u, off = per * tile;
      if (off < bytes) l2_prefetch((const uint8_t*)wp.p[w] + off, min(per, bytes - off));
    } else if (has_tile && threadIdx.x >= 416) {
      mbar_wait(full, 0);
      const int t = threadIdx.x - 416;
#pragma unroll 2
      for (int i = t; i < 2048; i += 96) g_att[tile * 2048 + i] = make_uint4(~0u, ~0u, ~0u, ~0u);
      g_halo[tile * 128 + t] = make_uint4(~0u, ~0u, ~0u, ~0u);
      if (t < 32) g_halo[tile * 128 + 96 + t] = make_uint4(~0u, ~0u, ~0u, ~0u);
    }
    __syncwarp();
    bar_sync(5 + wg, 384);
    asm volatile("setmaxnreg.inc.sync.aligned.u32 128;");
  } else {
    asm volatile("setmaxnreg.inc.sync.aligned.u32 232;");
    if (has_tile) {
      const Ctx c = make_ctx(base, dry);
      if (c.wg == 1) turn_end(c);
      float own[64];
      float a0, b0, a1, b1;
      PROF_MARK(0, 0);
      mbar_wait(misc + B_X, dry);
      PROF_MARK(0, 1);
      load_half(c, c.sX, own);
      ln_stats(c, own, 0.5f, a0, b0, a1, b1);
      store_half(c, c.sA, own, a0, b0, a1, b1);
      fence_async_smem();
      bar_sync(1, 256);
      PROF_MARK(0, 2);
      ff_block(c, 0, own);
      PROF_MARK(0, 3);
      ln_stats(c, own, 1.f, a0, b0, a1, b1);
      store_half(c, c.sA, own, a0, b0, a1, b1);
      fence_async_smem();
      bar_sync(1, 256);
      PROF_MARK(0, 4);
#pragma unroll 1
      for (int cc = dry ? 2 : 0; cc < 3; cc++) {
        float acc[64];
        const int j = 2 * cc + c.wg;
        gemm256<1>(c, acc, 32 + 2 * j);
        const float sc = (cc == 0) ? 0.125f * 1.4426950408889634f : 1.f;
        if (c.tid == 0 && !dry) {
          if (cc == 2) {
            mbar_arrive(misc + B_ADONE);
            bulk_wait_all();
            if (tile <= 62) cnt_signal(g_cnt1);
            if (tile >= 62) cnt_signal(g_cnt1 + 64);
          } else bulk_wait_read();
        }
        bar_sync(3 + c.wg, 128);
        store_half(c, c.sX, acc, sc, 0.f, sc, 0.f);
        fence_async_smem();
        bar_sync(3 + c.wg, 128);
        if (c.tid == 0 && !dry) { tma_store_3d(&tm.QKVst, c.sX + c.wg * 16384, 0, tile * 64, 2 * j); bulk_commit(); }
      }
      PROF_MARK(0, 5);
      if (c.tid == 0) bulk_wait_read();
      bar_sync(3 + c.wg, 128);
      store_half_raw(c, c.sX, own);
    }
    else bar_sync(3 + wg, 128);
    asm volatile("setmaxnreg.dec.sync.aligned.u32 128;");
    bar_arrive(7, 384); bar_arrive(8, 384);
    if (has_tile && !dry && (threadIdx.x & 127) == 0) {
      bulk_wait_all();
      if (tile <= 62) cnt_signal(g_cnt1 + 32);
      if (tile >= 62) cnt_signal(g_cnt1 + 96);
    }
    __syncwarp();
    PROF_MARK(0, 6);
  }

  if (blockIdx.x == 128) return;
  if (blockIdx.x != 130) {
    const int lane = threadIdx.x & 31, wq = (threadIdx.x >> 5) & 3;
    const uint32_t dQ = dlo(base + wg * 8192, 16);
    float O[32], l0, l1;
    PROF_MARK(1, 1);
    mbar_wait(misc + B_Q, dry);
    PROF_MARK(1, 2);
    att_pass<false>(a, dQ, O, l0, l1);
    PROF_MARK(1, 3);
    float z = 0.f;
#pragma unroll
    for (int i = 0; i < 32; i++) z = fmaf(O[i], 0.f, z);
    const bool ok = (l0 >= 0x1p-80f) && (l0 <= 0x1p100f) && (l1 >= 0x1p-80f) && (l1 <= 0x1p100f) && (z == 0.f);
    const bool warp_bad = !__all_sync(0xffffffff, ok) && !dry;
    auto store_out = [&]() {
      const float i0 = 1.f / l0, i1 = 1.f / l1;
      const int row = qt * 256 + wg * 64 + wq * 16;
      if (row < T_ && !dry) {
        const int slab = (a.b * T_ + row) / 16;
        uint4* op = g_att + (slab * 16 + a.h * 4) * 32 + lane;
#pragma unroll
        for (int j = 0; j < 4; j++)
          asm volatile("st.relaxed.gpu.global.v4.u32 [%0], {%1,%2,%3,%4};" :: "l"(op + j * 32),
                       "r"(pack_bf16(O[8 * j] * i0, O[8 * j + 1] * i0)), "r"(pack_bf16(O[8 * j + 2] * i1, O[8 * j + 3] * i1)),
                       "r"(pack_bf16(O[8 * j + 4] * i0, O[8 * j + 5] * i0)), "r"(pack_bf16(O[8 * j + 6] * i1, O[8 * j + 7] * i1)) : "memory");
        __syncwarp();
        if (lane == 0) cnt_signal(g_cnt2 + slab);
      }
      PROF_MARK(1, 4);
    };
    if (!warp_bad) store_out();
    if (__syncthreads_or(warp_bad)) {
      if (threadIdx.x == 0) {
        for (int i = 0; i < 3 * NSTG; i++) mbar_inval(a.full + 8 * i);
        att_init_bars(a);
        asm volatile("fence.mbarrier_init.release.cluster;" ::: "memory");
        fence_async_smem();
#pragma unroll 1
        for (int i = 0; i < NSTG; i++) att_load_stage(a, i);
      }
      __syncthreads();
      att_pass<true>(a, dQ, O, l0, l1);
      if (warp_bad) store_out();
      __syncthreads();
    }
    PROF_MARK(1, 5);
  } else {
    __syncthreads();
  }
  if (dry ? blockIdx.x != 130 : !has_tile) return;

  if (wg >= 2) {
    asm volatile("setmaxnreg.dec.sync.aligned.u32 24;");
    if (threadIdx.x == 256 && !dry) produce(base + OFF_W, misc + B_FULL, misc + B_EMPTY, tm, NC, NC + 48);
  } else {
    asm volatile("setmaxnreg.inc.sync.aligned.u32 232;");
    const Ctx c = make_ctx(base, dry);
    if (dry && c.wg == 1) turn_end(c);
    float own[64];
    float a0, b0, a1, b1;
    PROF_MARK(2, 0);
    load_half(c, c.sX, own);
    {
      uint4 af[16];
      const int slab = tile * 4 + (c.tid >> 5);
      const uint4* ap = g_att + slab * 512 + c.lane;
      if (c.lane == 0 && !dry) cnt_wait(g_cnt2 + slab, 4 * get_epoch());
      __syncwarp();
      PROF_MARK(2, 1);
      for (uint32_t n = 0; n < (1u << 24); n++) {
        bool any = false;
#pragma unroll
        for (int i = 0; i < 16; i++)
          asm volatile("ld.relaxed.gpu.global.v4.u32 {%0,%1,%2,%3}, [%4];" : "=r"(af[i].x), "=r"(af[i].y), "=r"(af[i].z), "=r"(af[i].w) : "l"(ap + i * 32) : "memory");
#pragma unroll
        for (int i = 0; i < 16; i++) any |= max(max(af[i].x, af[i].y), max(af[i].z, af[i].w)) == ~0u;
        if (!__any_sync(0xffffffff, any) || dry) break;
      }
      PROF_MARK(2, 2);
      const int n = NC + 2 * c.wg;
      uint32_t b = stage_wait(c, n) + ((16384 >> 4) << 16);
      turn_begin(c);
      wg_fence();
#pragma unroll
      for (int kk = 0; kk < 8; kk++) wg_rs_n128_tb1<1>(own, af[kk].x, af[kk].y, af[kk].z, af[kk].w, b + kk * 128);
      wg_commit();
      b = stage_wait(c, n + 1) + ((16384 >> 4) << 16);
      wg_fence();
#pragma unroll
      for (int kk = 0; kk < 8; kk++) wg_rs_n128_tb1<1>(own, af[8 + kk].x, af[8 + kk].y, af[8 + kk].z, af[8 + kk].w, b + kk * 128);
      wg_commit();
      turn_end(c);
      wg_wait<1>(); stage_release(c, n);
      wg_wait<0>(); stage_release(c, n + 1);
    }
    PROF_MARK(2, 3);
    ln_stats(c, own, 0.5f, a0, b0, a1, b1);
    store_half(c, c.sA, own, a0, b0, a1, b1);
    fence_async_smem();
    bar_sync(1, 256);
    PROF_MARK(2, 4);
    uint4 dwr[5];
#pragma unroll
    for (int i = 0; i < 5; i++) dwr[i] = __ldg(dw + i * 32 + c.lane);
    const bool top = c.tid < 8, pub = (top || c.tid >= 120) && !dry;
    uint32_t* halo_out = (uint32_t*)g_halo + (tile * 4 + (top ? (c.tid >> 2) : ((c.tid >> 2) - 28))) * 128 + c.wg * 64 + (c.lane & 3);
#pragma unroll 1
    for (int q = dry; q < 2; q++) {
      float ab[64];
      gemm256<1>(c, ab, NC + 4 + 4 * q + 2 * c.wg);
#pragma unroll
      for (int j = 0; j < 4; j++) {
        float g[8];
#pragma unroll
        for (int i = 0; i < 8; i++) g[i] = fmaf(ab[8 * j + i], tanh_fast(ab[32 + 8 * j + i]), ab[8 * j + i]);
        const uint32_t p0 = pack_bf16(g[0], g[1]), p1 = pack_bf16(g[2], g[3]), p2 = pack_bf16(g[4], g[5]), p3 = pack_bf16(g[6], g[7]);
        if (pub) {
          uint32_t* hp = halo_out + q * 32 + j * 8;
          asm volatile("st.relaxed.gpu.global.u32 [%0], %1;" :: "l"(hp), "r"(top ? p0 : p1) : "memory");
          asm volatile("st.relaxed.gpu.global.u32 [%0], %1;" :: "l"(hp + 4), "r"(top ? p2 : p3) : "memory");
        }
        stsm_x4(c.sX + (2 * c.wg + q) * 8192 + c.frag + (((j * 2 + c.hi) ^ c.rsw) << 4), p0, p1, p2, p3);
      }
    }
    bar_sync(1, 256);
    PROF_MARK(2, 5);
    {
      const int wi = threadIdx.x >> 5;
      const uint32_t col = (c.lane >> 3) * 8192, ch = c.lane & 7;
      uint4 r[12];
#pragma unroll
      for (int i = 0; i < 12; i++) {
        const int row = (wi * 8 - 2 + i) & 63;
        r[i] = lds128(c.sX + col + row * 128 + ((ch ^ (row & 7)) << 4));
      }
      uint32_t w[5][4];
#pragma unroll
      for (int k = 0; k < 5; k++) {
        w[k][0] = bmul2(dwr[k].x, 0x3F003F00u); w[k][1] = bmul2(dwr[k].y, 0x3F003F00u);
        w[k][2] = bmul2(dwr[k].z, 0x3F003F00u); w[k][3] = bmul2(dwr[k].w, 0x3F003F00u);
      }
      auto conv_row = [&](int i) {
        uint32_t o[4];
#pragma unroll
        for (int q = 0; q < 4; q++) {
          uint32_t acc = bmul2(q == 0 ? r[i].x : q == 1 ? r[i].y : q == 2 ? r[i].z : r[i].w, w[0][q]);
#pragma unroll
          for (int k = 1; k < 5; k++) acc = bfma2(q == 0 ? r[i + k].x : q == 1 ? r[i + k].y : q == 2 ? r[i + k].z : r[i + k].w, w[k][q], acc);
          o[q] = pack_bf16(silu_half(bf_lo(acc)), silu_half(bf_hi(acc)));
        }
        sts128(c.sA + col + (wi * 8 + i) * 128 + ((ch ^ i) << 4), make_uint4(o[0], o[1], o[2], o[3]));
      };
      conv_row(2); conv_row(3); conv_row(4); conv_row(5);
      const int R0 = tile * 64 + wi * 8;
      if ((R0 % T_) == 0) { r[0] = make_uint4(0, 0, 0, 0); r[1] = r[0]; }
      else if (wi == 0 && !dry) { const uint4* sp = g_halo + ((tile - 1) * 4 + 2) * 32 + c.lane; data_poll(sp, r[0]); data_poll(sp + 32, r[1]); }
      if (((R0 + 8) % T_) == 0) { r[10] = make_uint4(0, 0, 0, 0); r[11] = r[10]; }
      else if (wi == 7 && !dry) { const uint4* sp = g_halo + ((tile + 1) * 4) * 32 + c.lane; data_poll(sp, r[10]); data_poll(sp + 32, r[11]); }
      conv_row(0); conv_row(1); conv_row(6); conv_row(7);
    }
    fence_async_smem();
    bar_sync(1, 256);
    PROF_MARK(2, 6);
    gemm256<0>(c, own, NC + 12 + 2 * c.wg);
    PROF_MARK(2, 7);
    ln_stats(c, own, 0.5f, a0, b0, a1, b1);
    store_half(c, c.sA, own, a0, b0, a1, b1);
    fence_async_smem();
    bar_sync(1, 256);
    PROF_MARK(2, 8);
    ff_block(c, NC + 16, own);
    PROF_MARK(2, 9);
    ln_stats(c, own, 1.f, a0, b0, a1, b1);
    store_half(c, c.sX, own, a0, b0, a1, b1);
    fence_async_smem();
    bar_sync(3 + c.wg, 128);
    if (c.tid == 0 && !dry) { tma_store_3d(&tm.Out, c.sX + c.wg * 16384, 0, tile * 64, 2 * c.wg); bulk_commit(); PROF_MARK(2, 10); bulk_wait_all(); }
    PROF_MARK(2, 11);
  }
}

typedef CUresult (*EncodeFn)(CUtensorMap*, CUtensorMapDataType, cuuint32_t, void*, const cuuint64_t*, const cuuint64_t*, const cuuint32_t*,
                             const cuuint32_t*, CUtensorMapInterleave, CUtensorMapSwizzle, CUtensorMapL2promotion, CUtensorMapFloatOOBfill);

CUtensorMap make_map(EncodeFn enc, const void* p, uint64_t d0, uint64_t d1, uint64_t d2, uint64_t s1, uint64_t s2, uint32_t b1, uint32_t b2) {
  CUtensorMap tm;
  cuuint64_t dims[3] = {d0, d1, d2};
  cuuint64_t strides[2] = {s1, s2};
  cuuint32_t box[3] = {64, b1, b2};
  cuuint32_t es[3] = {1, 1, 1};
  enc(&tm, CU_TENSOR_MAP_DATA_TYPE_BFLOAT16, 3, const_cast<void*>(p), dims, strides, box, es, CU_TENSOR_MAP_INTERLEAVE_NONE,
      CU_TENSOR_MAP_SWIZZLE_128B, CU_TENSOR_MAP_L2_PROMOTION_L2_256B, CU_TENSOR_MAP_FLOAT_OOB_FILL_NONE);
  return tm;
}
CUtensorMap blk_map(EncodeFn enc, const void* p, uint64_t rows, uint64_t cols, uint32_t boxrows, uint32_t boxblks) {
  return make_map(enc, p, 64, rows, cols / 64, cols * 2, 128, boxrows, boxblks);
}
CUtensorMap seq_map(EncodeFn enc, const void* p, uint64_t cols, uint32_t boxrows) {
  return make_map(enc, p, cols, T_, 2, cols * 2, cols * 2 * T_, boxrows, 1);
}

}

extern "C" void kernel_launch(void* const* d_in, const int* in_sizes, int n_in, void* d_out, int out_size) {
  (void)in_sizes; (void)n_in; (void)out_size;
  const void *x = d_in[0], *w1a = d_in[1], *w1b = d_in[2], *wqkv = d_in[3], *wo = d_in[4], *pw1 = d_in[5], *dw = d_in[6], *pw2 = d_in[7],
             *w2a = d_in[8], *w2b = d_in[9];
  void* fn = nullptr;
  cudaDriverEntryPointQueryResult qr;
  cudaGetDriverEntryPoint("cuTensorMapEncodeTiled", &fn, cudaEnableDefault, &qr);
  EncodeFn enc = (EncodeFn)fn;
  void* qkv;
  cudaGetSymbolAddress(&qkv, g_qkv);
  cudaFuncSetAttribute(conformer_kernel, cudaFuncAttributeMaxDynamicSharedMemorySize, SMEM_BYTES);

  Wptrs wp;
  const void* ws[8] = {w1a, w1b, wqkv, wo, pw1, pw2, w2a, w2b};
  const uint32_t wb[8] = {524288, 524288, 393216, 131072, 262144, 131072, 524288, 524288};
  for (int i = 0; i < 8; i++) { wp.p[i] = ws[i]; wp.bytes[i] = wb[i]; }
  Maps tm;
  tm.X = blk_map(enc, x, ROWS, 256, 64, 4);
  tm.W1a = blk_map(enc, w1a, 256, 1024, 256, 1);
  tm.W1b = blk_map(enc, w1b, 1024, 256, 64, 4);
  tm.Wqkv = blk_map(enc, wqkv, 256, 768, 128, 2);
  tm.QKVst = blk_map(enc, qkv, ROWS, 768, 64, 2);
  tm.Q = seq_map(enc, qkv, 768, 256);
  tm.KV = seq_map(enc, qkv, 768, 160);
  tm.Wo = blk_map(enc, wo, 256, 256, 128, 2);
  tm.Pw1 = make_map(enc, pw1, 256, 256, 2, 1024, 512, 128, 2);
  tm.Pw2 = blk_map(enc, pw2, 256, 256, 128, 2);
  tm.W2a = blk_map(enc, w2a, 256, 1024, 256, 1);
  tm.W2b = blk_map(enc, w2b, 1024, 256, 64, 4);
  tm.Out = blk_map(enc, d_out, ROWS, 256, 64, 2);
  conformer_kernel<<<NCTA, 512, SMEM_BYTES, cudaStreamPerThread>>>(tm, wp, (const uint4*)dw);
}
```

```cpp
#include <cuda_runtime.h>
#include <cuda_bf16.h>
#include <cuda.h>
#include <stdint.h>

namespace {

constexpr int T_ = 4000;
constexpr int ROWS = 8000;
constexpr int NTILE = 125;
constexpr int NCTA = 131;

__device__ __nv_bfloat16 g_qkv[ROWS * 768];
__device__ uint4 g_att[(ROWS / 16) * 16 * 32];
__device__ uint4 g_halo[NTILE * 4 * 32];
__device__ uint32_t g_start;
__device__ uint32_t g_cnt1[4 * 32];
__device__ uint32_t g_cnt2[ROWS / 16];

#define PROF_MARK(k, i) do {} while (0)
#define PROF_STG(n, i) do {} while (0)

__device__ __forceinline__ uint32_t smem_u32(const void* p) { return (uint32_t)__cvta_generic_to_shared(p); }
__device__ __forceinline__ void mbar_init(uint32_t bar, uint32_t cnt) { asm volatile("mbarrier.init.shared::cta.b64 [%0], %1;" :: "r"(bar), "r"(cnt) : "memory"); }
__device__ __forceinline__ void mbar_inval(uint32_t bar) { asm volatile("mbarrier.inval.shared::cta.b64 [%0];" :: "r"(bar) : "memory"); }
__device__ __forceinline__ void mbar_expect_tx(uint32_t bar, uint32_t bytes) { asm volatile("mbarrier.arrive.expect_tx.shared::cta.b64 _, [%0], %1;" :: "r"(bar), "r"(bytes) : "memory"); }
__device__ __forceinline__ void mbar_arrive(uint32_t bar) { asm volatile("mbarrier.arrive.shared::cta.b64 _, [%0];" :: "r"(bar) : "memory"); }
__device__ __forceinline__ void mbar_wait(uint32_t bar, uint32_t parity) {
  asm volatile("{\n.reg .pred p;\n.reg .u32 n;\n"
               "mbarrier.try_wait.parity.shared::cta.b64 p, [%0], %1;\n@p bra DONE_%=;\nmov.u32 n, 0;\n"
               "LOOP_%=:\nmbarrier.try_wait.parity.shared::cta.b64 p, [%0], %1;\n@p bra DONE_%=;\n"
               "add.u32 n, n, 1;\nsetp.lt.u32 p, n, 262144;\n@p bra LOOP_%=;\ntrap;\nDONE_%=:\n}\n" :: "r"(bar), "r"(parity) : "memory");
}
__device__ __forceinline__ void data_poll(const uint4* p, uint4& v) {
  asm volatile("{\n.reg .pred p;\n.reg .u32 n, t;\nmov.u32 n, 0;\n"
               "LOOP_%=:\nld.relaxed.gpu.global.v4.u32 {%0,%1,%2,%3}, [%4];\n"
               "max.u32 t, %0, %1;\nmax.u32 t, t, %2;\nmax.u32 t, t, %3;\nsetp.ne.u32 p, t, 0xFFFFFFFF;\n@p bra DONE_%=;\n"
               "add.u32 n, n, 1;\nsetp.lt.u32 p, n, 262144;\n@p bra LOOP_%=;\ntrap;\nDONE_%=:\n}\n"
               : "=&r"(v.x), "=&r"(v.y), "=&r"(v.z), "=&r"(v.w) : "l"(p) : "memory");
}
__device__ __forceinline__ void cnt_wait(const uint32_t* p, uint32_t target) {
  asm volatile("{\n.reg .pred p;\n.reg .u32 n, v;\nmov.u32 n, 0;\n"
               "LOOP_%=:\nld.relaxed.gpu.global.u32 v, [%0];\nsub.u32 v, v, %1;\nsetp.ge.s32 p, v, 0;\n@p bra DONE_%=;\n"
               "nanosleep.u32 40;\nadd.u32 n, n, 1;\nsetp.lt.u32 p, n, 262144;\n@p bra LOOP_%=;\ntrap;\nDONE_%=:\n}\n" :: "l"(p), "r"(target) : "memory");
}
__device__ __forceinline__ void cnt_signal(uint32_t* p) {
  asm volatile("red.relaxed.gpu.global.add.u32 [%0], 1;" :: "l"(p) : "memory");
}
__device__ __forceinline__ void tma_load_3d(uint32_t dst, const CUtensorMap* tm, uint32_t bar, int c0, int c1, int c2) {
  asm volatile("cp.async.bulk.tensor.3d.shared::cluster.global.mbarrier::complete_tx::bytes [%0], [%1, {%3, %4, %5}], [%2];"
    :: "r"(dst), "l"(tm), "r"(bar), "r"(c0), "r"(c1), "r"(c2) : "memory");
}
__device__ __forceinline__ void tma_store_3d(const CUtensorMap* tm, uint32_t src, int c0, int c1, int c2) {
  asm volatile("cp.async.bulk.tensor.3d.global.shared::cta.bulk_group [%0, {%2, %3, %4}], [%1];" :: "l"(tm), "r"(src), "r"(c0), "r"(c1), "r"(c2) : "memory");
}
__device__ __forceinline__ void bulk_commit() { asm volatile("cp.async.bulk.commit_group;" ::: "memory"); }
__device__ __forceinline__ void bulk_wait_read() { asm volatile("cp.async.bulk.wait_group.read 0;" ::: "memory"); }
__device__ __forceinline__ void bulk_wait_all() { asm volatile("cp.async.bulk.wait_group 0;" ::: "memory"); }
__device__ __forceinline__ void l2_prefetch(const void* p, uint32_t bytes) { asm volatile("cp.async.bulk.prefetch.L2.global [%0], %1;" :: "l"(p), "r"(bytes) : "memory"); }
__device__ __forceinline__ void prefetch_tmap(const CUtensorMap* tm) { asm volatile("prefetch.tensormap [%0];" :: "l"(tm) : "memory"); }
__device__ __forceinline__ void fence_async_smem() { asm volatile("fence.proxy.async.shared::cta;" ::: "memory"); }
__device__ __forceinline__ void wg_fence() { asm volatile("wgmma.fence.sync.aligned;" ::: "memory"); }
__device__ __forceinline__ void wg_commit() { asm volatile("wgmma.commit_group.sync.aligned;" ::: "memory"); }
template<int N> __device__ __forceinline__ void wg_wait() { asm volatile("wgmma.wait_group.sync.aligned %0;" :: "n"(N) : "memory"); }
__device__ __forceinline__ void bar_sync(int id, int n) { asm volatile("bar.sync %0, %1;" :: "r"(id), "r"(n) : "memory"); }
__device__ __forceinline__ void bar_arrive(int id, int n) { asm volatile("bar.arrive %0, %1;" :: "r"(id), "r"(n) : "memory"); }
__device__ __forceinline__ float ex2(float x) { float y; asm("ex2.approx.ftz.f32 %0, %1;" : "=f"(y) : "f"(x)); return y; }
__device__ __forceinline__ float tanh_fast(float x) { float y; asm("tanh.approx.f32 %0, %1;" : "=f"(y) : "f"(x)); return y; }
__device__ __forceinline__ uint32_t pack_bf16(float lo, float hi) { uint32_t r; asm("cvt.rn.bf16x2.f32 %0, %1, %2;" : "=r"(r) : "f"(hi), "f"(lo)); return r; }
__device__ __forceinline__ uint32_t bmul2(uint32_t a, uint32_t b) { uint32_t d; asm("mul.rn.bf16x2 %0, %1, %2;" : "=r"(d) : "r"(a), "r"(b)); return d; }
__device__ __forceinline__ uint32_t bfma2(uint32_t a, uint32_t b, uint32_t c) { uint32_t d; asm("fma.rn.bf16x2 %0, %1, %2, %3;" : "=r"(d) : "r"(a), "r"(b), "r"(c)); return d; }
__device__ __forceinline__ float bf_lo(uint32_t u) { return __uint_as_float(u << 16); }
__device__ __forceinline__ float bf_hi(uint32_t u) { return __uint_as_float(u & 0xffff0000u); }
__device__ __forceinline__ void ldsm_x4(uint32_t addr, uint32_t& r0, uint32_t& r1, uint32_t& r2, uint32_t& r3) {
  asm volatile("ldmatrix.sync.aligned.m8n8.x4.shared.b16 {%0,%1,%2,%3}, [%4];" : "=r"(r0), "=r"(r1), "=r"(r2), "=r"(r3) : "r"(addr) : "memory");
}
__device__ __forceinline__ void stsm_x4(uint32_t addr, uint32_t r0, uint32_t r1, uint32_t r2, uint32_t r3) {
  asm volatile("stmatrix.sync.aligned.m8n8.x4.shared.b16 [%0], {%1,%2,%3,%4};" :: "r"(addr), "r"(r0), "r"(r1), "r"(r2), "r"(r3) : "memory");
}
__device__ __forceinline__ void sts128(uint32_t addr, uint4 v) { asm volatile("st.shared.v4.b32 [%0], {%1,%2,%3,%4};" :: "r"(addr), "r"(v.x), "r"(v.y), "r"(v.z), "r"(v.w) : "memory"); }
__device__ __forceinline__ uint4 lds128(uint32_t addr) { uint4 v; asm volatile("ld.shared.v4.b32 {%0,%1,%2,%3}, [%4];" : "=r"(v.x), "=r"(v.y), "=r"(v.z), "=r"(v.w) : "r"(addr) : "memory"); return v; }
__device__ __forceinline__ void sts64f(uint32_t addr, float a, float b) { asm volatile("st.shared.v2.f32 [%0], {%1,%2};" :: "r"(addr), "f"(a), "f"(b) : "memory"); }
__device__ __forceinline__ float2 lds64f(uint32_t addr) { float2 v; asm volatile("ld.shared.v2.f32 {%0,%1}, [%2];" : "=f"(v.x), "=f"(v.y) : "r"(addr) : "memory"); return v; }
__device__ __forceinline__ uint32_t dlo(uint32_t addr, uint32_t lbo) { return ((addr & 0x3FFFF) >> 4) | ((lbo >> 4) << 16); }

template<int SD> __device__ __forceinline__ void wg_ss_n128_tb1(float (&d)[64], uint32_t da, uint32_t db) {
  asm volatile("{\n.reg .b64 da, db;\nmov.b64 da, {%64, 0x40000040};\nmov.b64 db, {%65, 0x40000040};\n"
    "wgmma.mma_async.sync.aligned.m64n128k16.f32.bf16.bf16 {%0, %1, %2, %3, %4, %5, %6, %7, %8, %9, %10, %11, %12, %13, %14, %15, %16, %17, %18, %19, %20, %21, %22, %23, %24, %25, %26, %27, %28, %29, %30, %31, %32, %33, %34, %35, %36, %37, %38, %39, %40, %41, %42, %43, %44, %45, %46, %47, %48, %49, %50, %51, %52, %53, %54, %55, %56, %57, %58, %59, %60, %61, %62, %63}, da, db, %66, 1, 1, 0, 1;\n}\n"
    : "+f"(d[0]), "+f"(d[1]), "+f"(d[2]), "+f"(d[3]), "+f"(d[4]), "+f"(d[5]), "+f"(d[6]), "+f"(d[7]), "+f"(d[8]), "+f"(d[9]), "+f"(d[10]), "+f"(d[11]), "+f"(d[12]), "+f"(d[13]), "+f"(d[14]), "+f"(d[15]), "+f"(d[16]), "+f"(d[17]), "+f"(d[18]), "+f"(d[19]), "+f"(d[20]), "+f"(d[21]), "+f"(d[22]), "+f"(d[23]), "+f"(d[24]), "+f"(d[25]), "+f"(d[26]), "+f"(d[27]), "+f"(d[28]), "+f"(d[29]), "+f"(d[30]), "+f"(d[31]), "+f"(d[32]), "+f"(d[33]), "+f"(d[34]), "+f"(d[35]), "+f"(d[36]), "+f"(d[37]), "+f"(d[38]), "+f"(d[39]), "+f"(d[40]), "+f"(d[41]), "+f"(d[42]), "+f"(d[43]), "+f"(d[44]), "+f"(d[45]), "+f"(d[46]), "+f"(d[47]), "+f"(d[48]), "+f"(d[49]), "+f"(d[50]), "+f"(d[51]), "+f"(d[52]), "+f"(d[53]), "+f"(d[54]), "+f"(d[55]), "+f"(d[56]), "+f"(d[57]), "+f"(d[58]), "+f"(d[59]), "+f"(d[60]), "+f"(d[61]), "+f"(d[62]), "+f"(d[63])
    : "r"(da), "r"(db), "n"(SD));
}
template<int SD> __device__ __forceinline__ void wg_rs_n128_tb1(float (&d)[64], uint32_t a0, uint32_t a1, uint32_t a2, uint32_t a3, uint32_t db) {
  asm volatile("{\n.reg .b64 db;\nmov.b64 db, {%68, 0x40000040};\n"
    "wgmma.mma_async.sync.aligned.m64n128k16.f32.bf16.bf16 {%0, %1, %2, %3, %4, %5, %6, %7, %8, %9, %10, %11, %12, %13, %14, %15, %16, %17, %18, %19, %20, %21, %22, %23, %24, %25, %26, %27, %28, %29, %30, %31, %32, %33, %34, %35, %36, %37, %38, %39, %40, %41, %42, %43, %44, %45, %46, %47, %48, %49, %50, %51, %52, %53, %54, %55, %56, %57, %58, %59, %60, %61, %62, %63}, {%64, %65, %66, %67}, db, %69, 1, 1, 1;\n}\n"
    : "+f"(d[0]), "+f"(d[1]), "+f"(d[2]), "+f"(d[3]), "+f"(d[4]), "+f"(d[5]), "+f"(d[6]), "+f"(d[7]), "+f"(d[8]), "+f"(d[9]), "+f"(d[10]), "+f"(d[11]), "+f"(d[12]), "+f"(d[13]), "+f"(d[14]), "+f"(d[15]), "+f"(d[16]), "+f"(d[17]), "+f"(d[18]), "+f"(d[19]), "+f"(d[20]), "+f"(d[21]), "+f"(d[22]), "+f"(d[23]), "+f"(d[24]), "+f"(d[25]), "+f"(d[26]), "+f"(d[27]), "+f"(d[28]), "+f"(d[29]), "+f"(d[30]), "+f"(d[31]), "+f"(d[32]), "+f"(d[33]), "+f"(d[34]), "+f"(d[35]), "+f"(d[36]), "+f"(d[37]), "+f"(d[38]), "+f"(d[39]), "+f"(d[40]), "+f"(d[41]), "+f"(d[42]), "+f"(d[43]), "+f"(d[44]), "+f"(d[45]), "+f"(d[46]), "+f"(d[47]), "+f"(d[48]), "+f"(d[49]), "+f"(d[50]), "+f"(d[51]), "+f"(d[52]), "+f"(d[53]), "+f"(d[54]), "+f"(d[55]), "+f"(d[56]), "+f"(d[57]), "+f"(d[58]), "+f"(d[59]), "+f"(d[60]), "+f"(d[61]), "+f"(d[62]), "+f"(d[63])
    : "r"(a0), "r"(a1), "r"(a2), "r"(a3), "r"(db), "n"(SD));
}
template<int SD> __device__ __forceinline__ void wg_ss_n64_tb1(float (&d)[32], uint32_t da, uint32_t db) {
  asm volatile("{\n.reg .b64 da, db;\nmov.b64 da, {%32, 0x40000040};\nmov.b64 db, {%33, 0x40000040};\n"
    "wgmma.mma_async.sync.aligned.m64n64k16.f32.bf16.bf16 {%0, %1, %2, %3, %4, %5, %6, %7, %8, %9, %10, %11, %12, %13, %14, %15, %16, %17, %18, %19, %20, %21, %22, %23, %24, %25, %26, %27, %28, %29, %30, %31}, da, db, %34, 1, 1, 0, 1;\n}\n"
    : "+f"(d[0]), "+f"(d[1]), "+f"(d[2]), "+f"(d[3]), "+f"(d[4]), "+f"(d[5]), "+f"(d[6]), "+f"(d[7]), "+f"(d[8]), "+f"(d[9]), "+f"(d[10]), "+f"(d[11]), "+f"(d[12]), "+f"(d[13]), "+f"(d[14]), "+f"(d[15]), "+f"(d[16]), "+f"(d[17]), "+f"(d[18]), "+f"(d[19]), "+f"(d[20]), "+f"(d[21]), "+f"(d[22]), "+f"(d[23]), "+f"(d[24]), "+f"(d[25]), "+f"(d[26]), "+f"(d[27]), "+f"(d[28]), "+f"(d[29]), "+f"(d[30]), "+f"(d[31])
    : "r"(da), "r"(db), "n"(SD));
}
template<int SD> __device__ __forceinline__ void wg_ss_n80_tb0(float (&d)[40], uint32_t da, uint32_t db) {
  asm volatile("{\n.reg .b64 da, db;\nmov.b64 da, {%40, 0x40000040};\nmov.b64 db, {%41, 0x40000040};\n"
    "wgmma.mma_async.sync.aligned.m64n80k16.f32.bf16.bf16 {%0, %1, %2, %3, %4, %5, %6, %7, %8, %9, %10, %11, %12, %13, %14, %15, %16, %17, %18, %19, %20, %21, %22, %23, %24, %25, %26, %27, %28, %29, %30, %31, %32, %33, %34, %35, %36, %37, %38, %39}, da, db, %42, 1, 1, 0, 0;\n}\n"
    : "+f"(d[0]), "+f"(d[1]), "+f"(d[2]), "+f"(d[3]), "+f"(d[4]), "+f"(d[5]), "+f"(d[6]), "+f"(d[7]), "+f"(d[8]), "+f"(d[9]), "+f"(d[10]), "+f"(d[11]), "+f"(d[12]), "+f"(d[13]), "+f"(d[14]), "+f"(d[15]), "+f"(d[16]), "+f"(d[17]), "+f"(d[18]), "+f"(d[19]), "+f"(d[20]), "+f"(d[21]), "+f"(d[22]), "+f"(d[23]), "+f"(d[24]), "+f"(d[25]), "+f"(d[26]), "+f"(d[27]), "+f"(d[28]), "+f"(d[29]), "+f"(d[30]), "+f"(d[31]), "+f"(d[32]), "+f"(d[33]), "+f"(d[34]), "+f"(d[35]), "+f"(d[36]), "+f"(d[37]), "+f"(d[38]), "+f"(d[39])
    : "r"(da), "r"(db), "n"(SD));
}
template<int SD> __device__ __forceinline__ void wg_rs_n64_tb1(float (&d)[32], uint32_t a0, uint32_t a1, uint32_t a2, uint32_t a3, uint32_t db) {
  asm volatile("{\n.reg .b64 db;\nmov.b64 db, {%36, 0x40000040};\n"
    "wgmma.mma_async.sync.aligned.m64n64k16.f32.bf16.bf16 {%0, %1, %2, %3, %4, %5, %6, %7, %8, %9, %10, %11, %12, %13, %14, %15, %16, %17, %18, %19, %20, %21, %22, %23, %24, %25, %26, %27, %28, %29, %30, %31}, {%32, %33, %34, %35}, db, %37, 1, 1, 1;\n}\n"
    : "+f"(d[0]), "+f"(d[1]), "+f"(d[2]), "+f"(d[3]), "+f"(d[4]), "+f"(d[5]), "+f"(d[6]), "+f"(d[7]), "+f"(d[8]), "+f"(d[9]), "+f"(d[10]), "+f"(d[11]), "+f"(d[12]), "+f"(d[13]), "+f"(d[14]), "+f"(d[15]), "+f"(d[16]), "+f"(d[17]), "+f"(d[18]), "+f"(d[19]), "+f"(d[20]), "+f"(d[21]), "+f"(d[22]), "+f"(d[23]), "+f"(d[24]), "+f"(d[25]), "+f"(d[26]), "+f"(d[27]), "+f"(d[28]), "+f"(d[29]), "+f"(d[30]), "+f"(d[31])
    : "r"(a0), "r"(a1), "r"(a2), "r"(a3), "r"(db), "n"(SD));
}

constexpr int RING = 5;
constexpr uint32_t STAGE = 32768;
constexpr uint32_t OFF_X = 32768, OFF_W = 65536, OFF_MISC = OFF_W + RING * STAGE;
constexpr int SMEM_BYTES = OFF_MISC + 256 + 1024 + 1024;

struct Ctx {
  uint32_t sA, sX, sW, full, empty, stats;
  uint32_t frag;
  uint32_t rsw;
  uint32_t hi;
  int wg, tid, lane;
  int pk;
  uint32_t dry;
};
__device__ __forceinline__ uint32_t stage_wait(const Ctx& c, int n) {
  const int q = n / RING, s = n - q * RING;
  if (c.tid == 0) PROF_STG(n + c.pk, 1);
  mbar_wait(c.full + 8 * s, (q | c.dry) & 1);
  if (c.tid == 0) PROF_STG(n + c.pk, 2);
  return dlo(c.sW + s * STAGE, 0);
}
__device__ __forceinline__ void stage_release(const Ctx& c, int n) {
  const int s = n % RING;
  if (c.tid == 0) { mbar_arrive(c.empty + 8 * s); PROF_STG(n + c.pk, 3); }
}
__device__ __forceinline__ void turn_begin(const Ctx& c) { bar_sync(5 + c.wg, 256); }
__device__ __forceinline__ void turn_end(const Ctx& c) { bar_arrive(5 + (c.wg ^ 1), 256); }
template<int FIRST> __device__ __forceinline__ void piece_ss(float (&acc)[64], uint32_t dA, uint32_t dB) {
  dB += (16384 >> 4) << 16;
  wg_ss_n128_tb1<FIRST ? 0 : 1>(acc, dA, dB);
#pragma unroll
  for (int kk = 1; kk < 8; kk++) wg_ss_n128_tb1<1>(acc, dA + (kk >> 2) * 512 + (kk & 3) * 2, dB + kk * 128);
}
__device__ __forceinline__ void ff_g1(float (&h)[32], uint32_t dA, uint32_t dB) {
  wg_ss_n64_tb1<0>(h, dA, dB);
#pragma unroll
  for (int kk = 1; kk < 16; kk++) wg_ss_n64_tb1<1>(h, dA + (kk >> 2) * 512 + (kk & 3) * 2, dB + kk * 128);
}
__device__ __forceinline__ void ff_g2(float (&acc)[64], const uint32_t (&P)[16], uint32_t dB, int half) {
  dB += ((8192 >> 4) << 16) + half * 1024;
#pragma unroll
  for (int kk = 0; kk < 4; kk++) wg_rs_n128_tb1<1>(acc, P[4 * kk], P[4 * kk + 1], P[4 * kk + 2], P[4 * kk + 3], dB + kk * 128);
}
template<int FIRST> __device__ __forceinline__ void gemm256(const Ctx& c, float (&acc)[64], int n) {
  const uint32_t dA = dlo(c.sA, 16);
  uint32_t b = stage_wait(c, n);
  turn_begin(c);
  wg_fence(); piece_ss<FIRST>(acc, dA, b); wg_commit();
  b = stage_wait(c, n + 1);
  wg_fence(); piece_ss<0>(acc, dA + 1024, b); wg_commit();
  turn_end(c);
  wg_wait<1>(); stage_release(c, n);
  wg_wait<0>(); stage_release(c, n + 1);
}
__device__ __forceinline__ uint32_t frag_addr(const Ctx& c, uint32_t tile, int j) {
  return tile + (2 * c.wg + (j >> 2)) * 8192 + c.frag + ((((j & 3) * 2 + c.hi) ^ c.rsw) << 4);
}
__device__ __forceinline__ void load_half(const Ctx& c, uint32_t tile, float (&v)[64]) {
#pragma unroll
  for (int j = 0; j < 8; j++) {
    uint32_t r0, r1, r2, r3;
    ldsm_x4(frag_addr(c, tile, j), r0, r1, r2, r3);
    v[8 * j] = bf_lo(r0); v[8 * j + 1] = bf_hi(r0); v[8 * j + 2] = bf_lo(r1); v[8 * j + 3] = bf_hi(r1);
    v[8 * j + 4] = bf_lo(r2); v[8 * j + 5] = bf_hi(r2); v[8 * j + 6] = bf_lo(r3); v[8 * j + 7] = bf_hi(r3);
  }
}
__device__ __forceinline__ void store_half(const Ctx& c, uint32_t tile, const float (&v)[64], float a0, float b0, float a1, float b1) {
#pragma unroll
  for (int j = 0; j < 8; j++)
    stsm_x4(frag_addr(c, tile, j),
            pack_bf16(fmaf(v[8 * j], a0, b0), fmaf(v[8 * j + 1], a0, b0)), pack_bf16(fmaf(v[8 * j + 2], a1, b1), fmaf(v[8 * j + 3], a1, b1)),
            pack_bf16(fmaf(v[8 * j + 4], a0, b0), fmaf(v[8 * j + 5], a0, b0)), pack_bf16(fmaf(v[8 * j + 6], a1, b1), fmaf(v[8 * j + 7], a1, b1)));
}
__device__ __forceinline__ void store_half_raw(const Ctx& c, uint32_t tile, const float (&v)[64]) {
#pragma unroll
  for (int j = 0; j < 8; j++)
    stsm_x4(frag_addr(c, tile, j), pack_bf16(v[8 * j], v[8 * j + 1]), pack_bf16(v[8 * j + 2], v[8 * j + 3]),
            pack_bf16(v[8 * j + 4], v[8 * j + 5]), pack_bf16(v[8 * j + 6], v[8 * j + 7]));
}
__device__ __forceinline__ void ln_stats(const Ctx& c, const float (&v)[64], float scale, float& a0, float& b0, float& a1, float& b1) {
  float s0 = 0.f, s1 = 0.f, q0 = 0.f, q1 = 0.f, s2 = 0.f, s3 = 0.f, q2 = 0.f, q3 = 0.f;
#pragma unroll
  for (int i = 0; i < 16; i++) {
    s0 += v[4 * i]; q0 = fmaf(v[4 * i], v[4 * i], q0);
    s2 += v[4 * i + 1]; q2 = fmaf(v[4 * i + 1], v[4 * i + 1], q2);
    s1 += v[4 * i + 2]; q1 = fmaf(v[4 * i + 2], v[4 * i + 2], q1);
    s3 += v[4 * i + 3]; q3 = fmaf(v[4 * i + 3], v[4 * i + 3], q3);
  }
  s0 += s2; q0 += q2; s1 += s3; q1 += q3;
  s0 += __shfl_xor_sync(0xffffffff, s0, 1); q0 += __shfl_xor_sync(0xffffffff, q0, 1);
  s1 += __shfl_xor_sync(0xffffffff, s1, 1); q1 += __shfl_xor_sync(0xffffffff, q1, 1);
  s0 += __shfl_xor_sync(0xffffffff, s0, 2); q0 += __shfl_xor_sync(0xffffffff, q0, 2);
  s1 += __shfl_xor_sync(0xffffffff, s1, 2); q1 += __shfl_xor_sync(0xffffffff, q1, 2);
  const uint32_t row = (c.tid >> 5) * 16 + (c.lane >> 2);
  if ((c.lane & 3) == 0) {
    sts64f(c.stats + c.wg * 512 + row * 8, s0, q0);
    sts64f(c.stats + c.wg * 512 + (row + 8) * 8, s1, q1);
  }
  bar_sync(1, 256);
  const float2 o0 = lds64f(c.stats + (c.wg ^ 1) * 512 + row * 8), o1 = lds64f(c.stats + (c.wg ^ 1) * 512 + (row + 8) * 8);
  const float m0 = (s0 + o0.x) * (1.f / 256.f), m1 = (s1 + o1.x) * (1.f / 256.f);
  const float var0 = fmaxf(fmaf(-m0, m0, (q0 + o0.y) * (1.f / 256.f)), 0.f), var1 = fmaxf(fmaf(-m1, m1, (q1 + o1.y) * (1.f / 256.f)), 0.f);
  a0 = rsqrtf(var0 + 1e-5f) * scale; a1 = rsqrtf(var1 + 1e-5f) * scale;
  b0 = -m0 * a0; b1 = -m1 * a1;
}
__device__ __forceinline__ float silu_half(float h) { return fmaf(h, tanh_fast(h), h); }
__device__ __forceinline__ float silu_quarter(float h) { const float q = 0.5f * h; return fmaf(q, tanh_fast(h), q); }
__device__ __forceinline__ void silu_pack(const float (&acc)[32], uint32_t (&P)[16]) {
#pragma unroll
  for (int i = 0; i < 16; i++) P[i] = pack_bf16(silu_quarter(acc[2 * i]), silu_quarter(acc[2 * i + 1]));
}
__device__ __forceinline__ void ff_block(const Ctx& c, int n0, float (&own)[64]) {
  float oth[64], h[32];
  uint32_t P[16];
#pragma unroll
  for (int i = 0; i < 64; i++) oth[i] = 0.f;
  const uint32_t dA = dlo(c.sA, 16);
  {
    const uint32_t b = stage_wait(c, n0 + c.wg);
    turn_begin(c);
    wg_fence(); ff_g1(h, dA, b); wg_commit();
    turn_end(c);
    wg_wait<0>(); stage_release(c, n0 + c.wg);
    silu_pack(h, P);
  }
#pragma unroll 1
  for (int it = c.dry ? 7 : 1; it < 8; it++) {
    const int n = n0 + 4 * it - 2 + 2 * c.wg;
    uint32_t b = stage_wait(c, n);
    turn_begin(c);
    wg_fence(); ff_g2(own, P, b, c.wg); ff_g2(oth, P, b, c.wg ^ 1); wg_commit();
    b = stage_wait(c, n + 1);
    wg_fence(); ff_g1(h, dA, b); wg_commit();
    turn_end(c);
    wg_wait<1>(); stage_release(c, n);
    wg_wait<0>(); stage_release(c, n + 1);
    silu_pack(h, P);
  }
  if (c.wg == 0) bar_arrive(2, 256);
  {
    const int n = n0 + 30 + c.wg;
    const uint32_t b = stage_wait(c, n);
    turn_begin(c);
    wg_fence(); ff_g2(oth, P, b, c.wg ^ 1); wg_commit();
    ff_g2(own, P, b, c.wg); wg_commit();
    turn_end(c);
    wg_wait<1>();
    if (c.wg == 1) bar_sync(2, 256);
    const uint32_t e = (c.wg == 0 ? c.sX : c.sA) + c.tid * 16;
#pragma unroll
    for (int i = 0; i < 16; i++)
      sts128(e + i * 2048, make_uint4(__float_as_uint(oth[4 * i]), __float_as_uint(oth[4 * i + 1]), __float_as_uint(oth[4 * i + 2]), __float_as_uint(oth[4 * i + 3])));
    wg_wait<0>(); stage_release(c, n);
  }
  bar_sync(1, 256);
  const uint32_t e = (c.wg == 0 ? c.sA : c.sX) + c.tid * 16;
#pragma unroll
  for (int i = 0; i < 16; i++) {
    const uint4 u = lds128(e + i * 2048);
    own[4 * i] += __uint_as_float(u.x); own[4 * i + 1] += __uint_as_float(u.y);
    own[4 * i + 2] += __uint_as_float(u.z); own[4 * i + 3] += __uint_as_float(u.w);
  }
}
struct Maps { CUtensorMap X, W1a, W1b, Wqkv, QKVst, Q, KV, Wo, Pw1, Pw2, W2a, W2b, Out; };
constexpr int NC = 44;
__constant__ uint16_t c_stage[92] = {0x1, 0x11, 0x2, 0x21, 0x102, 0x31, 0x202, 0x41, 0x302, 0x51, 0x402, 0x61, 0x502, 0x71, 0x602, 0x81, 0x702, 0x91, 0x802, 0xa1, 0x902, 0xb1, 0xa02, 0xc1, 0xb02, 0xd1, 0xc02, 0xe1, 0xd02, 0xf1, 0xe02, 0xf02, 0x3, 0x203, 0x23, 0x223, 0x43, 0x243, 0x63, 0x263, 0x83, 0x283, 0xa3, 0x2a3, 0x7, 0x207, 0x27, 0x227, 0x8, 0x208, 0x2008, 0x2208, 0x1008, 0x1208, 0x3008, 0x3208, 0x9, 0x209, 0x29, 0x229, 0xa, 0x1a, 0xb, 0x2a, 0x10b, 0x3a, 0x20b, 0x4a, 0x30b, 0x5a, 0x40b, 0x6a, 0x50b, 0x7a, 0x60b, 0x8a, 0x70b, 0x9a, 0x80b, 0xaa, 0x90b, 0xba, 0xa0b, 0xca, 0xb0b, 0xda, 0xc0b, 0xea, 0xd0b, 0xfa, 0xe0b, 0xf0b};
__device__ __forceinline__ void load_stage(uint32_t dst, uint32_t bar, const Maps& tm, int n) {
  const uint32_t e = c_stage[n];
  mbar_expect_tx(bar, STAGE);
  tma_load_3d(dst, &tm.X + (e & 15), bar, (e >> 12) * 64, ((e >> 8) & 15) * 64, (e >> 4) & 15);
}
__device__ __forceinline__ void produce(uint32_t sW, uint32_t full, const Maps& tm, int n0, int n1) {
  uint32_t s = n0 % RING, ph = ((n0 / RING) & 1) ^ 1;
#pragma unroll 1
  for (int n = n0; n < n1; n++) {
    mbar_wait(full + 8 * RING + 8 * s, ph);
    PROF_STG(n, 0);
    load_stage(sW + s * STAGE, full + 8 * s, tm, n);
    if (++s == RING) { s = 0; ph ^= 1; }
  }
}
__device__ __forceinline__ Ctx make_ctx(uint32_t base, uint32_t dry, int pk = 0) {
  Ctx c; c.pk = pk; c.dry = dry;
  c.sA = base; c.sX = base + OFF_X; c.sW = base + OFF_W;
  c.full = base + OFF_MISC; c.empty = c.full + 8 * RING; c.stats = base + OFF_MISC + 256;
  c.wg = __shfl_sync(0xffffffff, (int)(threadIdx.x >> 7), 0);
  c.tid = threadIdx.x & 127; c.lane = threadIdx.x & 31;
  const uint32_t r = (c.tid >> 5) * 16 + (c.lane & 7) + ((c.lane >> 3) & 1) * 8;
  c.frag = r * 128; c.rsw = r & 7; c.hi = c.lane >> 4;
  return c;
}

constexpr int NSTG = 4;
constexpr int KVB = 160 * 128;
constexpr int NKV = T_ / 160;
static_assert(NSTG * 2 * KVB == RING * STAGE, "the K/V ring reuses the weight ring");

struct AttCtx { uint32_t sKV, full, empty, dry; const CUtensorMap* tmKV; int h, b, wg; };
__device__ __forceinline__ void att_load(const AttCtx& a, int i, int v) {
  const int s = i & (NSTG - 1);
  mbar_expect_tx(a.full + 8 * (s + v * NSTG), KVB);
  tma_load_3d(a.sKV + s * 2 * KVB + v * KVB, a.tmKV, a.full + 8 * (s + v * NSTG), 256 + v * 256 + a.h * 64, i * 160, a.b);
}
__device__ __forceinline__ void att_load_stage(const AttCtx& a, int i) { att_load(a, i, 0); att_load(a, i, 1); }
__device__ __forceinline__ void att_init_bars(const AttCtx& a) {
  for (int i = 0; i < NSTG; i++) { mbar_init(a.full + 8 * i, 1); mbar_init(a.full + 8 * (NSTG + i), 1); mbar_init(a.empty + 8 * i, 4); }
}
__device__ __forceinline__ void att_qk(float (&S)[40], uint32_t dQ, uint32_t kd) {
  wg_ss_n80_tb0<0>(S, dQ, kd);
#pragma unroll
  for (int kk = 1; kk < 4; kk++) wg_ss_n80_tb0<1>(S, dQ + kk * 2, kd + kk * 2);
}
__device__ __forceinline__ void att_pv(float (&O)[32], const uint32_t (&P)[20], uint32_t vd) {
#pragma unroll
  for (int kk = 0; kk < 5; kk++) wg_rs_n64_tb1<1>(O, P[kk * 4], P[kk * 4 + 1], P[kk * 4 + 2], P[kk * 4 + 3], vd + kk * 128);
}
template<bool SAFE>
__device__ __forceinline__ void att_softmax(const float (&S)[40], uint32_t (&P)[20], float (&O)[32], float& m0, float& m1, float& l0, float& l1) {
  if (SAFE) {
    float x0 = fmaxf(S[0], S[1]), x1 = fmaxf(S[2], S[3]);
#pragma unroll
    for (int i = 1; i < 10; i++) { x0 = fmaxf(x0, fmaxf(S[4 * i], S[4 * i + 1])); x1 = fmaxf(x1, fmaxf(S[4 * i + 2], S[4 * i + 3])); }
    x0 = fmaxf(x0, __shfl_xor_sync(0xffffffff, x0, 1)); x1 = fmaxf(x1, __shfl_xor_sync(0xffffffff, x1, 1));
    x0 = fmaxf(x0, __shfl_xor_sync(0xffffffff, x0, 2)); x1 = fmaxf(x1, __shfl_xor_sync(0xffffffff, x1, 2));
    const float n0 = fmaxf(m0, x0), n1 = fmaxf(m1, x1);
    const float f0 = ex2(m0 - n0), f1 = ex2(m1 - n1);
    m0 = n0; m1 = n1; l0 *= f0; l1 *= f1;
#pragma unroll
    for (int i = 0; i < 8; i++) { O[4 * i] *= f0; O[4 * i + 1] *= f0; O[4 * i + 2] *= f1; O[4 * i + 3] *= f1; }
  }
#pragma unroll
  for (int i = 0; i < 10; i++) {
    float p0, p1, p2, p3;
    if (SAFE) { p0 = ex2(S[4 * i] - m0); p1 = ex2(S[4 * i + 1] - m0); p2 = ex2(S[4 * i + 2] - m1); p3 = ex2(S[4 * i + 3] - m1); }
    else { p0 = ex2(S[4 * i]); p1 = ex2(S[4 * i + 1]); p2 = ex2(S[4 * i + 2]); p3 = ex2(S[4 * i + 3]); }
    l0 += p0 + p1; l1 += p2 + p3;
    P[2 * i] = pack_bf16(p0, p1); P[2 * i + 1] = pack_bf16(p2, p3);
  }
}
__device__ __forceinline__ void att_refill(const AttCtx& a, int it) {
  if ((threadIdx.x & 127) == 0) {
    mbar_arrive(a.empty + 8 * (it & 3));
    if (a.wg == (it & 3) && it >= 1 && it - 1 + NSTG < NKV && !a.dry) {
      mbar_wait(a.empty + 8 * ((it - 1) & 3), ((it - 1) >> 2) & 1);
      att_load_stage(a, it - 1 + NSTG);
    }
  }
  __syncwarp();
}
constexpr uint32_t KV_STG = 2 * KVB / 16, KV_VOFF = KVB / 16, KV_HALF = 80 * 128 / 16;
template<bool SAFE>
__device__ __forceinline__ void att_pass(const AttCtx& a, uint32_t dQ, float (&O)[32], float& l0, float& l1) {
  float S[40];
  uint32_t P[20];
  float m0 = -INFINITY, m1 = -INFINITY;
  l0 = 0.f; l1 = 0.f;
#pragma unroll
  for (int i = 0; i < 32; i++) O[i] = 0.f;
  const uint32_t dKV = dlo(a.sKV, 16);
  if (SAFE) {
#pragma unroll 1
    for (int j = 0; j < 2 * NKV; j++) {
      const int it = j >> 1, s = it & 3;
      const uint32_t kb = dKV + s * KV_STG + (j & 1) * KV_HALF;
      mbar_wait(a.full + 8 * s, (it >> 2) & 1);
      wg_fence(); att_qk(S, dQ, kb); wg_commit(); wg_wait<0>();
      att_softmax<true>(S, P, O, m0, m1, l0, l1);
      mbar_wait(a.full + 8 * (NSTG + s), (it >> 2) & 1);
      wg_fence(); att_pv(O, P, kb + KV_VOFF); wg_commit(); wg_wait<0>();
      if (j & 1) att_refill(a, it);
    }
  } else {
    mbar_wait(a.full, a.dry);
    wg_fence(); att_qk(S, dQ, dKV); wg_commit(); wg_wait<0>();
    att_softmax<false>(S, P, O, m0, m1, l0, l1);
    mbar_wait(a.full + 8 * NSTG, a.dry);
    wg_fence(); att_pv(O, P, dKV + KV_VOFF); att_qk(S, dQ, dKV + KV_HALF); wg_commit(); wg_wait<0>();
#pragma unroll 1
    for (int it = a.dry ? NKV - 2 : 0; it < NKV - 1; it++) {
      const int s = it & 3, sn = (it + 1) & 3;
      const uint32_t kb = dKV + s * KV_STG, kn = dKV + sn * KV_STG, par = (((it + 1) >> 2) | a.dry) & 1;
      att_softmax<false>(S, P, O, m0, m1, l0, l1);
      mbar_wait(a.full + 8 * sn, par);
      wg_fence(); att_pv(O, P, kb + KV_VOFF + KV_HALF); att_qk(S, dQ, kn); wg_commit(); wg_wait<0>();
      att_refill(a, it);
      att_softmax<false>(S, P, O, m0, m1, l0, l1);
      mbar_wait(a.full + 8 * (NSTG + sn), par);
      wg_fence(); att_pv(O, P, kn + KV_VOFF); att_qk(S, dQ, kn + KV_HALF); wg_commit(); wg_wait<0>();
    }
    att_softmax<false>(S, P, O, m0, m1, l0, l1);
    wg_fence(); att_pv(O, P, dKV + ((NKV - 1) & 3) * KV_STG + KV_VOFF + KV_HALF); wg_commit(); wg_wait<0>();
  }
  l0 += __shfl_xor_sync(0xffffffff, l0, 1); l1 += __shfl_xor_sync(0xffffffff, l1, 1);
  l0 += __shfl_xor_sync(0xffffffff, l0, 2); l1 += __shfl_xor_sync(0xffffffff, l1, 2);
}

struct Wptrs { const void* p[8]; uint32_t bytes[8]; };

constexpr uint32_t B_FULL = 0, B_EMPTY = 8 * RING, B_X = 16 * RING, B_ADONE = B_X + 8, B_Q = B_X + 16, B_EP = B_X + 24, B_ATT = B_X + 32;

__global__ void __launch_bounds__(512, 1) conformer_kernel(const __grid_constant__ Maps tm, const __grid_constant__ Wptrs wp, const uint4* __restrict__ dw) {
  extern __shared__ uint8_t smem_raw[];
  const uint32_t base = (smem_u32(smem_raw) + 1023) & ~1023u, misc = base + OFF_MISC;
  const uint32_t dry = blockIdx.x >= 128;
  const int tile = dry ? 0 : blockIdx.x;
  const bool has_tile = dry ? blockIdx.x == 128 : tile < NTILE;
  const int wg = __shfl_sync(0xffffffff, (int)(threadIdx.x >> 7), 0);
  AttCtx a;
  a.sKV = base + OFF_W; a.full = misc + B_ATT; a.empty = a.full + 16 * NSTG; a.tmKV = &tm.KV;
  a.h = (blockIdx.x >> 4) & 3; a.b = (blockIdx.x >> 6) & 1; a.wg = wg; a.dry = dry;
  const int qt = blockIdx.x & 15;

  if (threadIdx.x == 256) {
    mbar_init(misc + B_X, 1);
    for (int i = 0; i < RING; i++) { mbar_init(misc + B_FULL + 8 * i, 1); mbar_init(misc + B_EMPTY + 8 * i, 1); }
    asm volatile("fence.mbarrier_init.release.cluster;" ::: "memory");
    if (has_tile && !dry) {
      mbar_expect_tx(misc + B_X, 32768);
      tma_load_3d(base + OFF_X, &tm.X, misc + B_X, 0, tile * 64, 0);
#pragma unroll 1
      for (int i = 0; i < RING; i++) load_stage(base + OFF_W + i * STAGE, misc + B_FULL + 8 * i, tm, i);
    }
  } else if (threadIdx.x == 288) {
    mbar_init(misc + B_ADONE, 2);
    mbar_init(misc + B_Q, 1);
    mbar_init(misc + B_EP, 1);
    att_init_bars(a);
    asm volatile("fence.mbarrier_init.release.cluster;" ::: "memory");
  } else if (threadIdx.x >= 320 && threadIdx.x < 333) {
    prefetch_tmap(&tm.X + (threadIdx.x - 320));
  }
  __syncthreads();
  auto get_epoch = [&]() {
    uint32_t e;
    mbar_wait(misc + B_EP, 0);
    asm volatile("ld.shared.u32 %0, [%1];" : "=r"(e) : "r"(misc + 248) : "memory");
    return e;
  };

  if (wg >= 2) {
    asm volatile("setmaxnreg.dec.sync.aligned.u32 24;");
    const uint32_t full = misc + B_FULL;
    if (threadIdx.x == 320) {
      const uint32_t e = atomicAdd(&g_start, 1) / NCTA;
      asm volatile("st.shared.u32 [%0], %1;" :: "r"(misc + 248), "r"(e + 1) : "memory");
      mbar_arrive(misc + B_EP);
    }
    if (dry) {
    } else if (threadIdx.x == 256) {
      if (has_tile) {
        produce(base + OFF_W, full, tm, RING, NC);
        mbar_wait(misc + B_ADONE, 0);
      }
      cnt_wait(g_cnt1 + a.b * 64, 126 * get_epoch());
      mbar_expect_tx(misc + B_Q, 32768);
      tma_load_3d(base, &tm.Q, misc + B_Q, a.h * 64, qt * 256, a.b);
#pragma unroll 1
      for (int i = 0; i < NSTG; i++) att_load(a, i, 0);
    } else if ((threadIdx.x >> 5) == 12) {
      if (has_tile) bar_sync(9, 288);
      if (threadIdx.x == 384) {
        cnt_wait(g_cnt1 + a.b * 64 + 32, 126 * get_epoch());
#pragma unroll 1
        for (int i = 0; i < NSTG; i++) att_load(a, i, 1);
      }
    } else if (has_tile && threadIdx.x >= 288 && threadIdx.x < 296) {
      const int w = threadIdx.x - 288;
      mbar_wait(misc + B_X, 0);
      const uint32_t bytes = wp.bytes[w], per = ((bytes / NTILE) + 127) & ~127u, off = per * tile;
      if (off < bytes) l2_prefetch((const uint8_t*)wp.p[w] + off, min(per, bytes - off));
    } else if (has_tile && threadIdx.x >= 416) {
      mbar_wait(full, 0);
      const int t = threadIdx.x - 416;
#pragma unroll 2
      for (int i = t; i < 2048; i += 96) g_att[tile * 2048 + i] = make_uint4(~0u, ~0u, ~0u, ~0u);
      g_halo[tile * 128 + t] = make_uint4(~0u, ~0u, ~0u, ~0u);
      if (t < 32) g_halo[tile * 128 + 96 + t] = make_uint4(~0u, ~0u, ~0u, ~0u);
    }
    __syncwarp();
    bar_sync(5 + wg, 384);
    asm volatile("setmaxnreg.inc.sync.aligned.u32 128;");
  } else {
    asm volatile("setmaxnreg.inc.sync.aligned.u32 232;");
    if (has_tile) {
      const Ctx c = make_ctx(base, dry);
      if (c.wg == 1) turn_end(c);
      float own[64];
      float a0, b0, a1, b1;
      PROF_MARK(0, 0);
      mbar_wait(misc + B_X, dry);
      PROF_MARK(0, 1);
      load_half(c, c.sX, own);
      ln_stats(c, own, 0.5f, a0, b0, a1, b1);
      store_half(c, c.sA, own, a0, b0, a1, b1);
      fence_async_smem();
      bar_sync(1, 256);
      PROF_MARK(0, 2);
      ff_block(c, 0, own);
      PROF_MARK(0, 3);
      ln_stats(c, own, 1.f, a0, b0, a1, b1);
      store_half(c, c.sA, own, a0, b0, a1, b1);
      fence_async_smem();
      bar_sync(1, 256);
      PROF_MARK(0, 4);
#pragma unroll 1
      for (int cc = dry ? 2 : 0; cc < 3; cc++) {
        float acc[64];
        const int j = 2 * cc + c.wg;
        gemm256<1>(c, acc, 32 + 2 * j);
        const float sc = (cc == 0) ? 0.125f * 1.4426950408889634f : 1.f;
        if (cc == 2 && !dry) bar_arrive(9, 288);
        if (c.tid == 0 && !dry) {
          if (cc == 2) {
            mbar_arrive(misc + B_ADONE);
            bulk_wait_all();
            if (tile <= 62) cnt_signal(g_cnt1);
            if (tile >= 62) cnt_signal(g_cnt1 + 64);
          } else bulk_wait_read();
        }
        bar_sync(3 + c.wg, 128);
        store_half(c, c.sX, acc, sc, 0.f, sc, 0.f);
        fence_async_smem();
        bar_sync(3 + c.wg, 128);
        if (c.tid == 0 && !dry) { tma_store_3d(&tm.QKVst, c.sX + c.wg * 16384, 0, tile * 64, 2 * j); bulk_commit(); }
      }
      PROF_MARK(0, 5);
      if (c.tid == 0) bulk_wait_read();
      bar_sync(3 + c.wg, 128);
      store_half_raw(c, c.sX, own);
    }
    else bar_sync(3 + wg, 128);
    asm volatile("setmaxnreg.dec.sync.aligned.u32 128;");
    bar_arrive(7, 384); bar_arrive(8, 384);
    if (has_tile && !dry && (threadIdx.x & 127) == 0) {
      bulk_wait_all();
      if (tile <= 62) cnt_signal(g_cnt1 + 32);
      if (tile >= 62) cnt_signal(g_cnt1 + 96);
    }
    __syncwarp();
    PROF_MARK(0, 6);
  }

  if (blockIdx.x == 128) return;
  if (blockIdx.x != 130) {
    const int lane = threadIdx.x & 31, wq = (threadIdx.x >> 5) & 3;
    const uint32_t dQ = dlo(base + wg * 8192, 16);
    float O[32], l0, l1;
    PROF_MARK(1, 1);
    mbar_wait(misc + B_Q, dry);
    PROF_MARK(1, 2);
    att_pass<false>(a, dQ, O, l0, l1);
    PROF_MARK(1, 3);
    float z = 0.f;
#pragma unroll
    for (int i = 0; i < 32; i++) z = fmaf(O[i], 0.f, z);
    const bool ok = (l0 >= 0x1p-80f) && (l0 <= 0x1p100f) && (l1 >= 0x1p-80f) && (l1 <= 0x1p100f) && (z == 0.f);
    const bool warp_bad = !__all_sync(0xffffffff, ok) && !dry;
    auto store_out = [&]() {
      const float i0 = 1.f / l0, i1 = 1.f / l1;
      const int row = qt * 256 + wg * 64 + wq * 16;
      if (row < T_ && !dry) {
        const int slab = (a.b * T_ + row) / 16;
        uint4* op = g_att + (slab * 16 + a.h * 4) * 32 + lane;
#pragma unroll
        for (int j = 0; j < 4; j++)
          asm volatile("st.relaxed.gpu.global.v4.u32 [%0], {%1,%2,%3,%4};" :: "l"(op + j * 32),
                       "r"(pack_bf16(O[8 * j] * i0, O[8 * j + 1] * i0)), "r"(pack_bf16(O[8 * j + 2] * i1, O[8 * j + 3] * i1)),
                       "r"(pack_bf16(O[8 * j + 4] * i0, O[8 * j + 5] * i0)), "r"(pack_bf16(O[8 * j + 6] * i1, O[8 * j + 7] * i1)) : "memory");
        __syncwarp();
        if (lane == 0) cnt_signal(g_cnt2 + slab);
      }
      PROF_MARK(1, 4);
    };
    if (!warp_bad) store_out();
    if (__syncthreads_or(warp_bad)) {
      if (threadIdx.x == 0) {
        for (int i = 0; i < 3 * NSTG; i++) mbar_inval(a.full + 8 * i);
        att_init_bars(a);
        asm volatile("fence.mbarrier_init.release.cluster;" ::: "memory");
        fence_async_smem();
#pragma unroll 1
        for (int i = 0; i < NSTG; i++) att_load_stage(a, i);
      }
      __syncthreads();
      att_pass<true>(a, dQ, O, l0, l1);
      if (warp_bad) store_out();
      __syncthreads();
    }
    PROF_MARK(1, 5);
  } else {
    __syncthreads();
  }
  if (dry ? blockIdx.x != 130 : !has_tile) return;

  if (wg >= 2) {
    asm volatile("setmaxnreg.dec.sync.aligned.u32 24;");
    if (threadIdx.x == 256 && !dry) produce(base + OFF_W, misc + B_FULL, tm, NC, NC + 48);
  } else {
    asm volatile("setmaxnreg.inc.sync.aligned.u32 232;");
    const Ctx c = make_ctx(base, dry);
    if (dry && c.wg == 1) turn_end(c);
    float own[64];
    float a0, b0, a1, b1;
    PROF_MARK(2, 0);
    load_half(c, c.sX, own);
    {
      uint4 af[16];
      const int slab = tile * 4 + (c.tid >> 5);
      const uint4* ap = g_att + slab * 512 + c.lane;
      if (c.lane == 0 && !dry) cnt_wait(g_cnt2 + slab, 4 * get_epoch());
      __syncwarp();
      PROF_MARK(2, 1);
      for (uint32_t n = 0; n < (1u << 24); n++) {
        bool any = false;
#pragma unroll
        for (int i = 0; i < 16; i++)
          asm volatile("ld.relaxed.gpu.global.v4.u32 {%0,%1,%2,%3}, [%4];" : "=r"(af[i].x), "=r"(af[i].y), "=r"(af[i].z), "=r"(af[i].w) : "l"(ap + i * 32) : "memory");
#pragma unroll
        for (int i = 0; i < 16; i++) any |= max(max(af[i].x, af[i].y), max(af[i].z, af[i].w)) == ~0u;
        if (!__any_sync(0xffffffff, any) || dry) break;
      }
      PROF_MARK(2, 2);
      const int n = NC + 2 * c.wg;
      uint32_t b = stage_wait(c, n) + ((16384 >> 4) << 16);
      turn_begin(c);
      wg_fence();
#pragma unroll
      for (int kk = 0; kk < 8; kk++) wg_rs_n128_tb1<1>(own, af[kk].x, af[kk].y, af[kk].z, af[kk].w, b + kk * 128);
      wg_commit();
      b = stage_wait(c, n + 1) + ((16384 >> 4) << 16);
      wg_fence();
#pragma unroll
      for (int kk = 0; kk < 8; kk++) wg_rs_n128_tb1<1>(own, af[8 + kk].x, af[8 + kk].y, af[8 + kk].z, af[8 + kk].w, b + kk * 128);
      wg_commit();
      turn_end(c);
      wg_wait<1>(); stage_release(c, n);
      wg_wait<0>(); stage_release(c, n + 1);
    }
    PROF_MARK(2, 3);
    ln_stats(c, own, 0.5f, a0, b0, a1, b1);
    store_half(c, c.sA, own, a0, b0, a1, b1);
    fence_async_smem();
    bar_sync(1, 256);
    PROF_MARK(2, 4);
    uint4 dwr[5];
#pragma unroll
    for (int i = 0; i < 5; i++) dwr[i] = __ldg(dw + i * 32 + c.lane);
    const bool top = c.tid < 8, pub = (top || c.tid >= 120) && !dry;
    uint32_t* halo_out = (uint32_t*)g_halo + (tile * 4 + (top ? (c.tid >> 2) : ((c.tid >> 2) - 28))) * 128 + c.wg * 64 + (c.lane & 3);
#pragma unroll 1
    for (int q = dry; q < 2; q++) {
      float ab[64];
      gemm256<1>(c, ab, NC + 4 + 4 * q + 2 * c.wg);
#pragma unroll
      for (int j = 0; j < 4; j++) {
        float g[8];
#pragma unroll
        for (int i = 0; i < 8; i++) g[i] = fmaf(ab[8 * j + i], tanh_fast(ab[32 + 8 * j + i]), ab[8 * j + i]);
        const uint32_t p0 = pack_bf16(g[0], g[1]), p1 = pack_bf16(g[2], g[3]), p2 = pack_bf16(g[4], g[5]), p3 = pack_bf16(g[6], g[7]);
        if (pub) {
          uint32_t* hp = halo_out + q * 32 + j * 8;
          asm volatile("st.relaxed.gpu.global.u32 [%0], %1;" :: "l"(hp), "r"(top ? p0 : p1) : "memory");
          asm volatile("st.relaxed.gpu.global.u32 [%0], %1;" :: "l"(hp + 4), "r"(top ? p2 : p3) : "memory");
        }
        stsm_x4(c.sX + (2 * c.wg + q) * 8192 + c.frag + (((j * 2 + c.hi) ^ c.rsw) << 4), p0, p1, p2, p3);
      }
    }
    bar_sync(1, 256);
    PROF_MARK(2, 5);
    {
      const int wi = threadIdx.x >> 5;
      const uint32_t col = (c.lane >> 3) * 8192, ch = c.lane & 7;
      uint4 r[12];
#pragma unroll
      for (int i = 0; i < 12; i++) {
        const int row = (wi * 8 - 2 + i) & 63;
        r[i] = lds128(c.sX + col + row * 128 + ((ch ^ (row & 7)) << 4));
      }
      uint32_t w[5][4];
#pragma unroll
      for (int k = 0; k < 5; k++) {
        w[k][0] = bmul2(dwr[k].x, 0x3F003F00u); w[k][1] = bmul2(dwr[k].y, 0x3F003F00u);
        w[k][2] = bmul2(dwr[k].z, 0x3F003F00u); w[k][3] = bmul2(dwr[k].w, 0x3F003F00u);
      }
      auto conv_row = [&](int i) {
        uint32_t o[4];
#pragma unroll
        for (int q = 0; q < 4; q++) {
          uint32_t acc = bmul2(q == 0 ? r[i].x : q == 1 ? r[i].y : q == 2 ? r[i].z : r[i].w, w[0][q]);
#pragma unroll
          for (int k = 1; k < 5; k++) acc = bfma2(q == 0 ? r[i + k].x : q == 1 ? r[i + k].y : q == 2 ? r[i + k].z : r[i + k].w, w[k][q], acc);
          o[q] = pack_bf16(silu_half(bf_lo(acc)), silu_half(bf_hi(acc)));
        }
        sts128(c.sA + col + (wi * 8 + i) * 128 + ((ch ^ i) << 4), make_uint4(o[0], o[1], o[2], o[3]));
      };
      conv_row(2); conv_row(3); conv_row(4); conv_row(5);
      const int R0 = tile * 64 + wi * 8;
      if ((R0 % T_) == 0) { r[0] = make_uint4(0, 0, 0, 0); r[1] = r[0]; }
      else if (wi == 0 && !dry) { const uint4* sp = g_halo + ((tile - 1) * 4 + 2) * 32 + c.lane; data_poll(sp, r[0]); data_poll(sp + 32, r[1]); }
      if (((R0 + 8) % T_) == 0) { r[10] = make_uint4(0, 0, 0, 0); r[11] = r[10]; }
      else if (wi == 7 && !dry) { const uint4* sp = g_halo + ((tile + 1) * 4) * 32 + c.lane; data_poll(sp, r[10]); data_poll(sp + 32, r[11]); }
      conv_row(0); conv_row(1); conv_row(6); conv_row(7);
    }
    fence_async_smem();
    bar_sync(1, 256);
    PROF_MARK(2, 6);
    gemm256<0>(c, own, NC + 12 + 2 * c.wg);
    PROF_MARK(2, 7);
    ln_stats(c, own, 0.5f, a0, b0, a1, b1);
    store_half(c, c.sA, own, a0, b0, a1, b1);
    fence_async_smem();
    bar_sync(1, 256);
    PROF_MARK(2, 8);
    ff_block(c, NC + 16, own);
    PROF_MARK(2, 9);
    ln_stats(c, own, 1.f, a0, b0, a1, b1);
    store_half(c, c.sX, own, a0, b0, a1, b1);
    fence_async_smem();
    bar_sync(3 + c.wg, 128);
    if (c.tid == 0 && !dry) { tma_store_3d(&tm.Out, c.sX + c.wg * 16384, 0, tile * 64, 2 * c.wg); bulk_commit(); PROF_MARK(2, 10); bulk_wait_all(); }
    PROF_MARK(2, 11);
  }
}

typedef CUresult (*EncodeFn)(CUtensorMap*, CUtensorMapDataType, cuuint32_t, void*, const cuuint64_t*, const cuuint64_t*, const cuuint32_t*,
                             const cuuint32_t*, CUtensorMapInterleave, CUtensorMapSwizzle, CUtensorMapL2promotion, CUtensorMapFloatOOBfill);

CUtensorMap make_map(EncodeFn enc, const void* p, uint64_t d0, uint64_t d1, uint64_t d2, uint64_t s1, uint64_t s2, uint32_t b1, uint32_t b2) {
  CUtensorMap tm;
  cuuint64_t dims[3] = {d0, d1, d2};
  cuuint64_t strides[2] = {s1, s2};
  cuuint32_t box[3] = {64, b1, b2};
  cuuint32_t es[3] = {1, 1, 1};
  enc(&tm, CU_TENSOR_MAP_DATA_TYPE_BFLOAT16, 3, const_cast<void*>(p), dims, strides, box, es, CU_TENSOR_MAP_INTERLEAVE_NONE,
      CU_TENSOR_MAP_SWIZZLE_128B, CU_TENSOR_MAP_L2_PROMOTION_L2_256B, CU_TENSOR_MAP_FLOAT_OOB_FILL_NONE);
  return tm;
}
CUtensorMap blk_map(EncodeFn enc, const void* p, uint64_t rows, uint64_t cols, uint32_t boxrows, uint32_t boxblks) {
  return make_map(enc, p, 64, rows, cols / 64, cols * 2, 128, boxrows, boxblks);
}
CUtensorMap seq_map(EncodeFn enc, const void* p, uint64_t cols, uint32_t boxrows) {
  return make_map(enc, p, cols, T_, 2, cols * 2, cols * 2 * T_, boxrows, 1);
}

}

extern "C" void kernel_launch(void* const* d_in, const int* in_sizes, int n_in, void* d_out, int out_size) {
  (void)in_sizes; (void)n_in; (void)out_size;
  const void *x = d_in[0], *w1a = d_in[1], *w1b = d_in[2], *wqkv = d_in[3], *wo = d_in[4], *pw1 = d_in[5], *dw = d_in[6], *pw2 = d_in[7],
             *w2a = d_in[8], *w2b = d_in[9];
  void* fn = nullptr;
  cudaDriverEntryPointQueryResult qr;
  cudaGetDriverEntryPoint("cuTensorMapEncodeTiled", &fn, cudaEnableDefault, &qr);
  EncodeFn enc = (EncodeFn)fn;
  void* qkv;
  cudaGetSymbolAddress(&qkv, g_qkv);
  cudaFuncSetAttribute(conformer_kernel, cudaFuncAttributeMaxDynamicSharedMemorySize, SMEM_BYTES);

  Wptrs wp;
  const void* ws[8] = {w1a, w1b, wqkv, wo, pw1, pw2, w2a, w2b};
  const uint32_t wb[8] = {524288, 524288, 393216, 131072, 262144, 131072, 524288, 524288};
  for (int i = 0; i < 8; i++) { wp.p[i] = ws[i]; wp.bytes[i] = wb[i]; }
  Maps tm;
  tm.X = blk_map(enc, x, ROWS, 256, 64, 4);
  tm.W1a = blk_map(enc, w1a, 256, 1024, 256, 1);
  tm.W1b = blk_map(enc, w1b, 1024, 256, 64, 4);
  tm.Wqkv = blk_map(enc, wqkv, 256, 768, 128, 2);
  tm.QKVst = blk_map(enc, qkv, ROWS, 768, 64, 2);
  tm.Q = seq_map(enc, qkv, 768, 256);
  tm.KV = seq_map(enc, qkv, 768, 160);
  tm.Wo = blk_map(enc, wo, 256, 256, 128, 2);
  tm.Pw1 = make_map(enc, pw1, 256, 256, 2, 1024, 512, 128, 2);
  tm.Pw2 = blk_map(enc, pw2, 256, 256, 128, 2);
  tm.W2a = blk_map(enc, w2a, 256, 1024, 256, 1);
  tm.W2b = blk_map(enc, w2b, 1024, 256, 64, 4);
  tm.Out = blk_map(enc, d_out, ROWS, 256, 64, 2);
  conformer_kernel<<<NCTA, 512, SMEM_BYTES, cudaStreamPerThread>>>(tm, wp, (const uint4*)dw);
}
```

```cpp
#include <cuda_runtime.h>
#include <cuda_bf16.h>
#include <cuda.h>
#include <stdint.h>

namespace {

constexpr int T_ = 4000;
constexpr int ROWS = 8000;
constexpr int NTILE = 125;
constexpr int NCTA = 131;

__device__ __nv_bfloat16 g_qkv[ROWS * 768];
__device__ uint4 g_att[(ROWS / 16) * 16 * 32];
__device__ uint4 g_halo[NTILE * 4 * 32];
__device__ uint32_t g_start;
__device__ uint32_t g_cnt1[4 * 32];
__device__ uint32_t g_cnt2[ROWS / 16 * 32];

#define PROF_MARK(k, i) do {} while (0)
#define PROF_STG(n, i) do {} while (0)

__device__ __forceinline__ uint32_t smem_u32(const void* p) { return (uint32_t)__cvta_generic_to_shared(p); }
__device__ __forceinline__ void mbar_init(uint32_t bar, uint32_t cnt) { asm volatile("mbarrier.init.shared::cta.b64 [%0], %1;" :: "r"(bar), "r"(cnt) : "memory"); }
__device__ __forceinline__ void mbar_inval(uint32_t bar) { asm volatile("mbarrier.inval.shared::cta.b64 [%0];" :: "r"(bar) : "memory"); }
__device__ __forceinline__ void mbar_expect_tx(uint32_t bar, uint32_t bytes) { asm volatile("mbarrier.arrive.expect_tx.shared::cta.b64 _, [%0], %1;" :: "r"(bar), "r"(bytes) : "memory"); }
__device__ __forceinline__ void mbar_arrive(uint32_t bar) { asm volatile("mbarrier.arrive.shared::cta.b64 _, [%0];" :: "r"(bar) : "memory"); }
__device__ __forceinline__ void mbar_wait(uint32_t bar, uint32_t parity) {
  asm volatile("{\n.reg .pred p;\n.reg .u32 n;\n"
               "mbarrier.try_wait.parity.shared::cta.b64 p, [%0], %1;\n@p bra DONE_%=;\nmov.u32 n, 0;\n"
               "LOOP_%=:\nmbarrier.try_wait.parity.shared::cta.b64 p, [%0], %1;\n@p bra DONE_%=;\n"
               "add.u32 n, n, 1;\nsetp.lt.u32 p, n, 262144;\n@p bra LOOP_%=;\ntrap;\nDONE_%=:\n}\n" :: "r"(bar), "r"(parity) : "memory");
}
__device__ __forceinline__ void data_poll(const uint4* p, uint4& v) {
  asm volatile("{\n.reg .pred p;\n.reg .u32 n, t;\nmov.u32 n, 0;\n"
               "LOOP_%=:\nld.relaxed.gpu.global.v4.u32 {%0,%1,%2,%3}, [%4];\n"
               "max.u32 t, %0, %1;\nmax.u32 t, t, %2;\nmax.u32 t, t, %3;\nsetp.ne.u32 p, t, 0xFFFFFFFF;\n@p bra DONE_%=;\n"
               "add.u32 n, n, 1;\nsetp.lt.u32 p, n, 262144;\n@p bra LOOP_%=;\ntrap;\nDONE_%=:\n}\n"
               : "=&r"(v.x), "=&r"(v.y), "=&r"(v.z), "=&r"(v.w) : "l"(p) : "memory");
}
__device__ __forceinline__ void cnt_wait(const uint32_t* p, uint32_t target) {
  asm volatile("{\n.reg .pred p;\n.reg .u32 n, v;\nmov.u32 n, 0;\n"
               "LOOP_%=:\nld.relaxed.gpu.global.u32 v, [%0];\nsub.u32 v, v, %1;\nsetp.ge.s32 p, v, 0;\n@p bra DONE_%=;\n"
               "nanosleep.u32 40;\nadd.u32 n, n, 1;\nsetp.lt.u32 p, n, 262144;\n@p bra LOOP_%=;\ntrap;\nDONE_%=:\n}\n" :: "l"(p), "r"(target) : "memory");
}
__device__ __forceinline__ void cnt_signal(uint32_t* p) {
  asm volatile("red.relaxed.gpu.global.add.u32 [%0], 1;" :: "l"(p) : "memory");
}
__device__ __forceinline__ void tma_load_3d(uint32_t dst, const CUtensorMap* tm, uint32_t bar, int c0, int c1, int c2) {
  asm volatile("cp.async.bulk.tensor.3d.shared::cluster.global.mbarrier::complete_tx::bytes [%0], [%1, {%3, %4, %5}], [%2];"
    :: "r"(dst), "l"(tm), "r"(bar), "r"(c0), "r"(c1), "r"(c2) : "memory");
}
__device__ __forceinline__ void tma_store_3d(const CUtensorMap* tm, uint32_t src, int c0, int c1, int c2) {
  asm volatile("cp.async.bulk.tensor.3d.global.shared::cta.bulk_group [%0, {%2, %3, %4}], [%1];" :: "l"(tm), "r"(src), "r"(c0), "r"(c1), "r"(c2) : "memory");
}
__device__ __forceinline__ void bulk_commit() { asm volatile("cp.async.bulk.commit_group;" ::: "memory"); }
__device__ __forceinline__ void bulk_wait_read() { asm volatile("cp.async.bulk.wait_group.read 0;" ::: "memory"); }
__device__ __forceinline__ void bulk_wait_all() { asm volatile("cp.async.bulk.wait_group 0;" ::: "memory"); }
__device__ __forceinline__ void l2_prefetch(const void* p, uint32_t bytes) { asm volatile("cp.async.bulk.prefetch.L2.global [%0], %1;" :: "l"(p), "r"(bytes) : "memory"); }
__device__ __forceinline__ void prefetch_tmap(const CUtensorMap* tm) { asm volatile("prefetch.tensormap [%0];" :: "l"(tm) : "memory"); }
__device__ __forceinline__ void fence_async_smem() { asm volatile("fence.proxy.async.shared::cta;" ::: "memory"); }
__device__ __forceinline__ void wg_fence() { asm volatile("wgmma.fence.sync.aligned;" ::: "memory"); }
__device__ __forceinline__ void wg_commit() { asm volatile("wgmma.commit_group.sync.aligned;" ::: "memory"); }
template<int N> __device__ __forceinline__ void wg_wait() { asm volatile("wgmma.wait_group.sync.aligned %0;" :: "n"(N) : "memory"); }
__device__ __forceinline__ void bar_sync(int id, int n) { asm volatile("bar.sync %0, %1;" :: "r"(id), "r"(n) : "memory"); }
__device__ __forceinline__ void bar_arrive(int id, int n) { asm volatile("bar.arrive %0, %1;" :: "r"(id), "r"(n) : "memory"); }
__device__ __forceinline__ float ex2(float x) { float y; asm("ex2.approx.ftz.f32 %0, %1;" : "=f"(y) : "f"(x)); return y; }
__device__ __forceinline__ float tanh_fast(float x) { float y; asm("tanh.approx.f32 %0, %1;" : "=f"(y) : "f"(x)); return y; }
__device__ __forceinline__ uint32_t pack_bf16(float lo, float hi) { uint32_t r; asm("cvt.rn.bf16x2.f32 %0, %1, %2;" : "=r"(r) : "f"(hi), "f"(lo)); return r; }
__device__ __forceinline__ uint32_t bmul2(uint32_t a, uint32_t b) { uint32_t d; asm("mul.rn.bf16x2 %0, %1, %2;" : "=r"(d) : "r"(a), "r"(b)); return d; }
__device__ __forceinline__ uint32_t bfma2(uint32_t a, uint32_t b, uint32_t c) { uint32_t d; asm("fma.rn.bf16x2 %0, %1, %2, %3;" : "=r"(d) : "r"(a), "r"(b), "r"(c)); return d; }
__device__ __forceinline__ float bf_lo(uint32_t u) { return __uint_as_float(u << 16); }
__device__ __forceinline__ float bf_hi(uint32_t u) { return __uint_as_float(u & 0xffff0000u); }
__device__ __forceinline__ void ldsm_x4(uint32_t addr, uint32_t& r0, uint32_t& r1, uint32_t& r2, uint32_t& r3) {
  asm volatile("ldmatrix.sync.aligned.m8n8.x4.shared.b16 {%0,%1,%2,%3}, [%4];" : "=r"(r0), "=r"(r1), "=r"(r2), "=r"(r3) : "r"(addr) : "memory");
}
__device__ __forceinline__ void stsm_x4(uint32_t addr, uint32_t r0, uint32_t r1, uint32_t r2, uint32_t r3) {
  asm volatile("stmatrix.sync.aligned.m8n8.x4.shared.b16 [%0], {%1,%2,%3,%4};" :: "r"(addr), "r"(r0), "r"(r1), "r"(r2), "r"(r3) : "memory");
}
__device__ __forceinline__ void sts128(uint32_t addr, uint4 v) { asm volatile("st.shared.v4.b32 [%0], {%1,%2,%3,%4};" :: "r"(addr), "r"(v.x), "r"(v.y), "r"(v.z), "r"(v.w) : "memory"); }
__device__ __forceinline__ uint4 lds128(uint32_t addr) { uint4 v; asm volatile("ld.shared.v4.b32 {%0,%1,%2,%3}, [%4];" : "=r"(v.x), "=r"(v.y), "=r"(v.z), "=r"(v.w) : "r"(addr) : "memory"); return v; }
__device__ __forceinline__ void sts64f(uint32_t addr, float a, float b) { asm volatile("st.shared.v2.f32 [%0], {%1,%2};" :: "r"(addr), "f"(a), "f"(b) : "memory"); }
__device__ __forceinline__ float2 lds64f(uint32_t addr) { float2 v; asm volatile("ld.shared.v2.f32 {%0,%1}, [%2];" : "=f"(v.x), "=f"(v.y) : "r"(addr) : "memory"); return v; }
__device__ __forceinline__ uint32_t dlo(uint32_t addr, uint32_t lbo) { return ((addr & 0x3FFFF) >> 4) | ((lbo >> 4) << 16); }

template<int SD> __device__ __forceinline__ void wg_ss_n128_tb1(float (&d)[64], uint32_t da, uint32_t db) {
  asm volatile("{\n.reg .b64 da, db;\nmov.b64 da, {%64, 0x40000040};\nmov.b64 db, {%65, 0x40000040};\n"
    "wgmma.mma_async.sync.aligned.m64n128k16.f32.bf16.bf16 {%0, %1, %2, %3, %4, %5, %6, %7, %8, %9, %10, %11, %12, %13, %14, %15, %16, %17, %18, %19, %20, %21, %22, %23, %24, %25, %26, %27, %28, %29, %30, %31, %32, %33, %34, %35, %36, %37, %38, %39, %40, %41, %42, %43, %44, %45, %46, %47, %48, %49, %50, %51, %52, %53, %54, %55, %56, %57, %58, %59, %60, %61, %62, %63}, da, db, %66, 1, 1, 0, 1;\n}\n"
    : "+f"(d[0]), "+f"(d[1]), "+f"(d[2]), "+f"(d[3]), "+f"(d[4]), "+f"(d[5]), "+f"(d[6]), "+f"(d[7]), "+f"(d[8]), "+f"(d[9]), "+f"(d[10]), "+f"(d[11]), "+f"(d[12]), "+f"(d[13]), "+f"(d[14]), "+f"(d[15]), "+f"(d[16]), "+f"(d[17]), "+f"(d[18]), "+f"(d[19]), "+f"(d[20]), "+f"(d[21]), "+f"(d[22]), "+f"(d[23]), "+f"(d[24]), "+f"(d[25]), "+f"(d[26]), "+f"(d[27]), "+f"(d[28]), "+f"(d[29]), "+f"(d[30]), "+f"(d[31]), "+f"(d[32]), "+f"(d[33]), "+f"(d[34]), "+f"(d[35]), "+f"(d[36]), "+f"(d[37]), "+f"(d[38]), "+f"(d[39]), "+f"(d[40]), "+f"(d[41]), "+f"(d[42]), "+f"(d[43]), "+f"(d[44]), "+f"(d[45]), "+f"(d[46]), "+f"(d[47]), "+f"(d[48]), "+f"(d[49]), "+f"(d[50]), "+f"(d[51]), "+f"(d[52]), "+f"(d[53]), "+f"(d[54]), "+f"(d[55]), "+f"(d[56]), "+f"(d[57]), "+f"(d[58]), "+f"(d[59]), "+f"(d[60]), "+f"(d[61]), "+f"(d[62]), "+f"(d[63])
    : "r"(da), "r"(db), "n"(SD));
}
template<int SD> __device__ __forceinline__ void wg_rs_n128_tb1(float (&d)[64], uint32_t a0, uint32_t a1, uint32_t a2, uint32_t a3, uint32_t db) {
  asm volatile("{\n.reg .b64 db;\nmov.b64 db, {%68, 0x40000040};\n"
    "wgmma.mma_async.sync.aligned.m64n128k16.f32.bf16.bf16 {%0, %1, %2, %3, %4, %5, %6, %7, %8, %9, %10, %11, %12, %13, %14, %15, %16, %17, %18, %19, %20, %21, %22, %23, %24, %25, %26, %27, %28, %29, %30, %31, %32, %33, %34, %35, %36, %37, %38, %39, %40, %41, %42, %43, %44, %45, %46, %47, %48, %49, %50, %51, %52, %53, %54, %55, %56, %57, %58, %59, %60, %61, %62, %63}, {%64, %65, %66, %67}, db, %69, 1, 1, 1;\n}\n"
    : "+f"(d[0]), "+f"(d[1]), "+f"(d[2]), "+f"(d[3]), "+f"(d[4]), "+f"(d[5]), "+f"(d[6]), "+f"(d[7]), "+f"(d[8]), "+f"(d[9]), "+f"(d[10]), "+f"(d[11]), "+f"(d[12]), "+f"(d[13]), "+f"(d[14]), "+f"(d[15]), "+f"(d[16]), "+f"(d[17]), "+f"(d[18]), "+f"(d[19]), "+f"(d[20]), "+f"(d[21]), "+f"(d[22]), "+f"(d[23]), "+f"(d[24]), "+f"(d[25]), "+f"(d[26]), "+f"(d[27]), "+f"(d[28]), "+f"(d[29]), "+f"(d[30]), "+f"(d[31]), "+f"(d[32]), "+f"(d[33]), "+f"(d[34]), "+f"(d[35]), "+f"(d[36]), "+f"(d[37]), "+f"(d[38]), "+f"(d[39]), "+f"(d[40]), "+f"(d[41]), "+f"(d[42]), "+f"(d[43]), "+f"(d[44]), "+f"(d[45]), "+f"(d[46]), "+f"(d[47]), "+f"(d[48]), "+f"(d[49]), "+f"(d[50]), "+f"(d[51]), "+f"(d[52]), "+f"(d[53]), "+f"(d[54]), "+f"(d[55]), "+f"(d[56]), "+f"(d[57]), "+f"(d[58]), "+f"(d[59]), "+f"(d[60]), "+f"(d[61]), "+f"(d[62]), "+f"(d[63])
    : "r"(a0), "r"(a1), "r"(a2), "r"(a3), "r"(db), "n"(SD));
}
template<int SD> __device__ __forceinline__ void wg_ss_n64_tb1(float (&d)[32], uint32_t da, uint32_t db) {
  asm volatile("{\n.reg .b64 da, db;\nmov.b64 da, {%32, 0x40000040};\nmov.b64 db, {%33, 0x40000040};\n"
    "wgmma.mma_async.sync.aligned.m64n64k16.f32.bf16.bf16 {%0, %1, %2, %3, %4, %5, %6, %7, %8, %9, %10, %11, %12, %13, %14, %15, %16, %17, %18, %19, %20, %21, %22, %23, %24, %25, %26, %27, %28, %29, %30, %31}, da, db, %34, 1, 1, 0, 1;\n}\n"
    : "+f"(d[0]), "+f"(d[1]), "+f"(d[2]), "+f"(d[3]), "+f"(d[4]), "+f"(d[5]), "+f"(d[6]), "+f"(d[7]), "+f"(d[8]), "+f"(d[9]), "+f"(d[10]), "+f"(d[11]), "+f"(d[12]), "+f"(d[13]), "+f"(d[14]), "+f"(d[15]), "+f"(d[16]), "+f"(d[17]), "+f"(d[18]), "+f"(d[19]), "+f"(d[20]), "+f"(d[21]), "+f"(d[22]), "+f"(d[23]), "+f"(d[24]), "+f"(d[25]), "+f"(d[26]), "+f"(d[27]), "+f"(d[28]), "+f"(d[29]), "+f"(d[30]), "+f"(d[31])
    : "r"(da), "r"(db), "n"(SD));
}
template<int SD> __device__ __forceinline__ void wg_ss_n80_tb0(float (&d)[40], uint32_t da, uint32_t db) {
  asm volatile("{\n.reg .b64 da, db;\nmov.b64 da, {%40, 0x40000040};\nmov.b64 db, {%41, 0x40000040};\n"
    "wgmma.mma_async.sync.aligned.m64n80k16.f32.bf16.bf16 {%0, %1, %2, %3, %4, %5, %6, %7, %8, %9, %10, %11, %12, %13, %14, %15, %16, %17, %18, %19, %20, %21, %22, %23, %24, %25, %26, %27, %28, %29, %30, %31, %32, %33, %34, %35, %36, %37, %38, %39}, da, db, %42, 1, 1, 0, 0;\n}\n"
    : "+f"(d[0]), "+f"(d[1]), "+f"(d[2]), "+f"(d[3]), "+f"(d[4]), "+f"(d[5]), "+f"(d[6]), "+f"(d[7]), "+f"(d[8]), "+f"(d[9]), "+f"(d[10]), "+f"(d[11]), "+f"(d[12]), "+f"(d[13]), "+f"(d[14]), "+f"(d[15]), "+f"(d[16]), "+f"(d[17]), "+f"(d[18]), "+f"(d[19]), "+f"(d[20]), "+f"(d[21]), "+f"(d[22]), "+f"(d[23]), "+f"(d[24]), "+f"(d[25]), "+f"(d[26]), "+f"(d[27]), "+f"(d[28]), "+f"(d[29]), "+f"(d[30]), "+f"(d[31]), "+f"(d[32]), "+f"(d[33]), "+f"(d[34]), "+f"(d[35]), "+f"(d[36]), "+f"(d[37]), "+f"(d[38]), "+f"(d[39])
    : "r"(da), "r"(db), "n"(SD));
}
template<int SD> __device__ __forceinline__ void wg_rs_n64_tb1(float (&d)[32], uint32_t a0, uint32_t a1, uint32_t a2, uint32_t a3, uint32_t db) {
  asm volatile("{\n.reg .b64 db;\nmov.b64 db, {%36, 0x40000040};\n"
    "wgmma.mma_async.sync.aligned.m64n64k16.f32.bf16.bf16 {%0, %1, %2, %3, %4, %5, %6, %7, %8, %9, %10, %11, %12, %13, %14, %15, %16, %17, %18, %19, %20, %21, %22, %23, %24, %25, %26, %27, %28, %29, %30, %31}, {%32, %33, %34, %35}, db, %37, 1, 1, 1;\n}\n"
    : "+f"(d[0]), "+f"(d[1]), "+f"(d[2]), "+f"(d[3]), "+f"(d[4]), "+f"(d[5]), "+f"(d[6]), "+f"(d[7]), "+f"(d[8]), "+f"(d[9]), "+f"(d[10]), "+f"(d[11]), "+f"(d[12]), "+f"(d[13]), "+f"(d[14]), "+f"(d[15]), "+f"(d[16]), "+f"(d[17]), "+f"(d[18]), "+f"(d[19]), "+f"(d[20]), "+f"(d[21]), "+f"(d[22]), "+f"(d[23]), "+f"(d[24]), "+f"(d[25]), "+f"(d[26]), "+f"(d[27]), "+f"(d[28]), "+f"(d[29]), "+f"(d[30]), "+f"(d[31])
    : "r"(a0), "r"(a1), "r"(a2), "r"(a3), "r"(db), "n"(SD));
}

constexpr int RING = 5;
constexpr uint32_t STAGE = 32768;
constexpr uint32_t OFF_X = 32768, OFF_W = 65536, OFF_MISC = OFF_W + RING * STAGE;
constexpr int SMEM_BYTES = OFF_MISC + 256 + 1024 + 1024;

struct Ctx {
  uint32_t sA, sX, sW, full, empty, stats;
  uint32_t frag;
  uint32_t rsw;
  uint32_t hi;
  int wg, tid, lane;
  int pk;
  uint32_t dry;
};
__device__ __forceinline__ uint32_t stage_wait(const Ctx& c, int n) {
  const int q = n / RING, s = n - q * RING;
  if (c.tid == 0) PROF_STG(n + c.pk, 1);
  mbar_wait(c.full + 8 * s, (q | c.dry) & 1);
  if (c.tid == 0) PROF_STG(n + c.pk, 2);
  return dlo(c.sW + s * STAGE, 0);
}
__device__ __forceinline__ void stage_release(const Ctx& c, int n) {
  const int s = n % RING;
  if (c.tid == 0) { mbar_arrive(c.empty + 8 * s); PROF_STG(n + c.pk, 3); }
}
__device__ __forceinline__ void turn_begin(const Ctx& c) { bar_sync(5 + c.wg, 256); }
__device__ __forceinline__ void turn_end(const Ctx& c) { bar_arrive(5 + (c.wg ^ 1), 256); }
template<int FIRST> __device__ __forceinline__ void piece_ss(float (&acc)[64], uint32_t dA, uint32_t dB) {
  dB += (16384 >> 4) << 16;
  wg_ss_n128_tb1<FIRST ? 0 : 1>(acc, dA, dB);
#pragma unroll
  for (int kk = 1; kk < 8; kk++) wg_ss_n128_tb1<1>(acc, dA + (kk >> 2) * 512 + (kk & 3) * 2, dB + kk * 128);
}
__device__ __forceinline__ void ff_g1(float (&h)[32], uint32_t dA, uint32_t dB) {
  wg_ss_n64_tb1<0>(h, dA, dB);
#pragma unroll
  for (int kk = 1; kk < 16; kk++) wg_ss_n64_tb1<1>(h, dA + (kk >> 2) * 512 + (kk & 3) * 2, dB + kk * 128);
}
__device__ __forceinline__ void ff_g2(float (&acc)[64], const uint32_t (&P)[16], uint32_t dB, int half) {
  dB += ((8192 >> 4) << 16) + half * 1024;
#pragma unroll
  for (int kk = 0; kk < 4; kk++) wg_rs_n128_tb1<1>(acc, P[4 * kk], P[4 * kk + 1], P[4 * kk + 2], P[4 * kk + 3], dB + kk * 128);
}
template<int FIRST> __device__ __forceinline__ void gemm256(const Ctx& c, float (&acc)[64], int n) {
  const uint32_t dA = dlo(c.sA, 16);
  uint32_t b = stage_wait(c, n);
  turn_begin(c);
  wg_fence(); piece_ss<FIRST>(acc, dA, b); wg_commit();
  b = stage_wait(c, n + 1);
  wg_fence(); piece_ss<0>(acc, dA + 1024, b); wg_commit();
  turn_end(c);
  wg_wait<1>(); stage_release(c, n);
  wg_wait<0>(); stage_release(c, n + 1);
}
__device__ __forceinline__ uint32_t frag_addr(const Ctx& c, uint32_t tile, int j) {
  return tile + (2 * c.wg + (j >> 2)) * 8192 + c.frag + ((((j & 3) * 2 + c.hi) ^ c.rsw) << 4);
}
__device__ __forceinline__ void load_half(const Ctx& c, uint32_t tile, float (&v)[64]) {
#pragma unroll
  for (int j = 0; j < 8; j++) {
    uint32_t r0, r1, r2, r3;
    ldsm_x4(frag_addr(c, tile, j), r0, r1, r2, r3);
    v[8 * j] = bf_lo(r0); v[8 * j + 1] = bf_hi(r0); v[8 * j + 2] = bf_lo(r1); v[8 * j + 3] = bf_hi(r1);
    v[8 * j + 4] = bf_lo(r2); v[8 * j + 5] = bf_hi(r2); v[8 * j + 6] = bf_lo(r3); v[8 * j + 7] = bf_hi(r3);
  }
}
__device__ __forceinline__ void store_half(const Ctx& c, uint32_t tile, const float (&v)[64], float a0, float b0, float a1, float b1) {
#pragma unroll
  for (int j = 0; j < 8; j++)
    stsm_x4(frag_addr(c, tile, j),
            pack_bf16(fmaf(v[8 * j], a0, b0), fmaf(v[8 * j + 1], a0, b0)), pack_bf16(fmaf(v[8 * j + 2], a1, b1), fmaf(v[8 * j + 3], a1, b1)),
            pack_bf16(fmaf(v[8 * j + 4], a0, b0), fmaf(v[8 * j + 5], a0, b0)), pack_bf16(fmaf(v[8 * j + 6], a1, b1), fmaf(v[8 * j + 7], a1, b1)));
}
__device__ __forceinline__ void store_half_raw(const Ctx& c, uint32_t tile, const float (&v)[64]) {
#pragma unroll
  for (int j = 0; j < 8; j++)
    stsm_x4(frag_addr(c, tile, j), pack_bf16(v[8 * j], v[8 * j + 1]), pack_bf16(v[8 * j + 2], v[8 * j + 3]),
            pack_bf16(v[8 * j + 4], v[8 * j + 5]), pack_bf16(v[8 * j + 6], v[8 * j + 7]));
}
__device__ __forceinline__ void ln_stats(const Ctx& c, const float (&v)[64], float scale, float& a0, float& b0, float& a1, float& b1) {
  float s0 = 0.f, s1 = 0.f, q0 = 0.f, q1 = 0.f, s2 = 0.f, s3 = 0.f, q2 = 0.f, q3 = 0.f;
#pragma unroll
  for (int i = 0; i < 16; i++) {
    s0 += v[4 * i]; q0 = fmaf(v[4 * i], v[4 * i], q0);
    s2 += v[4 * i + 1]; q2 = fmaf(v[4 * i + 1], v[4 * i + 1], q2);
    s1 += v[4 * i + 2]; q1 = fmaf(v[4 * i + 2], v[4 * i + 2], q1);
    s3 += v[4 * i + 3]; q3 = fmaf(v[4 * i + 3], v[4 * i + 3], q3);
  }
  s0 += s2; q0 += q2; s1 += s3; q1 += q3;
  s0 += __shfl_xor_sync(0xffffffff, s0, 1); q0 += __shfl_xor_sync(0xffffffff, q0, 1);
  s1 += __shfl_xor_sync(0xffffffff, s1, 1); q1 += __shfl_xor_sync(0xffffffff, q1, 1);
  s0 += __shfl_xor_sync(0xffffffff, s0, 2); q0 += __shfl_xor_sync(0xffffffff, q0, 2);
  s1 += __shfl_xor_sync(0xffffffff, s1, 2); q1 += __shfl_xor_sync(0xffffffff, q1, 2);
  const uint32_t row = (c.tid >> 5) * 16 + (c.lane >> 2);
  if ((c.lane & 3) == 0) {
    sts64f(c.stats + c.wg * 512 + row * 8, s0, q0);
    sts64f(c.stats + c.wg * 512 + (row + 8) * 8, s1, q1);
  }
  bar_sync(1, 256);
  const float2 o0 = lds64f(c.stats + (c.wg ^ 1) * 512 + row * 8), o1 = lds64f(c.stats + (c.wg ^ 1) * 512 + (row + 8) * 8);
  const float m0 = (s0 + o0.x) * (1.f / 256.f), m1 = (s1 + o1.x) * (1.f / 256.f);
  const float var0 = fmaxf(fmaf(-m0, m0, (q0 + o0.y) * (1.f / 256.f)), 0.f), var1 = fmaxf(fmaf(-m1, m1, (q1 + o1.y) * (1.f / 256.f)), 0.f);
  a0 = rsqrtf(var0 + 1e-5f) * scale; a1 = rsqrtf(var1 + 1e-5f) * scale;
  b0 = -m0 * a0; b1 = -m1 * a1;
}
__device__ __forceinline__ float silu_half(float h) { return fmaf(h, tanh_fast(h), h); }
__device__ __forceinline__ float silu_quarter(float h) { const float q = 0.5f * h; return fmaf(q, tanh_fast(h), q); }
__device__ __forceinline__ void silu_pack(const float (&acc)[32], uint32_t (&P)[16]) {
#pragma unroll
  for (int i = 0; i < 16; i++) P[i] = pack_bf16(silu_quarter(acc[2 * i]), silu_quarter(acc[2 * i + 1]));
}
__device__ __forceinline__ void ff_block(const Ctx& c, int n0, float (&own)[64]) {
  float oth[64], h[32];
  uint32_t P[16];
#pragma unroll
  for (int i = 0; i < 64; i++) oth[i] = 0.f;
  const uint32_t dA = dlo(c.sA, 16);
  {
    const uint32_t b = stage_wait(c, n0 + c.wg);
    turn_begin(c);
    wg_fence(); ff_g1(h, dA, b); wg_commit();
    turn_end(c);
    wg_wait<0>(); stage_release(c, n0 + c.wg);
    silu_pack(h, P);
  }
#pragma unroll 1
  for (int it = c.dry ? 7 : 1; it < 8; it++) {
    const int n = n0 + 4 * it - 2 + 2 * c.wg;
    uint32_t b = stage_wait(c, n);
    turn_begin(c);
    wg_fence(); ff_g2(own, P, b, c.wg); ff_g2(oth, P, b, c.wg ^ 1); wg_commit();
    b = stage_wait(c, n + 1);
    wg_fence(); ff_g1(h, dA, b); wg_commit();
    turn_end(c);
    wg_wait<1>(); stage_release(c, n);
    wg_wait<0>(); stage_release(c, n + 1);
    silu_pack(h, P);
  }
  if (c.wg == 0) bar_arrive(2, 256);
  {
    const int n = n0 + 30 + c.wg;
    const uint32_t b = stage_wait(c, n);
    turn_begin(c);
    wg_fence(); ff_g2(oth, P, b, c.wg ^ 1); wg_commit();
    ff_g2(own, P, b, c.wg); wg_commit();
    turn_end(c);
    wg_wait<1>();
    if (c.wg == 1) bar_sync(2, 256);
    const uint32_t e = (c.wg == 0 ? c.sX : c.sA) + c.tid * 16;
#pragma unroll
    for (int i = 0; i < 16; i++)
      sts128(e + i * 2048, make_uint4(__float_as_uint(oth[4 * i]), __float_as_uint(oth[4 * i + 1]), __float_as_uint(oth[4 * i + 2]), __float_as_uint(oth[4 * i + 3])));
    wg_wait<0>(); stage_release(c, n);
  }
  bar_sync(1, 256);
  const uint32_t e = (c.wg == 0 ? c.sA : c.sX) + c.tid * 16;
#pragma unroll
  for (int i = 0; i < 16; i++) {
    const uint4 u = lds128(e + i * 2048);
    own[4 * i] += __uint_as_float(u.x); own[4 * i + 1] += __uint_as_float(u.y);
    own[4 * i + 2] += __uint_as_float(u.z); own[4 * i + 3] += __uint_as_float(u.w);
  }
}
struct Maps { CUtensorMap X, W1a, W1b, Wqkv, QKVst, Q, KV, Wo, Pw1, Pw2, W2a, W2b, Out; };
constexpr int NA = 44;
constexpr int NC = 45;
__constant__ uint16_t c_stage[92] = {0x1, 0x11, 0x2, 0x21, 0x102, 0x31, 0x202, 0x41, 0x302, 0x51, 0x402, 0x61, 0x502, 0x71, 0x602, 0x81, 0x702, 0x91, 0x802, 0xa1, 0x902, 0xb1, 0xa02, 0xc1, 0xb02, 0xd1, 0xc02, 0xe1, 0xd02, 0xf1, 0xe02, 0xf02, 0x3, 0x203, 0x23, 0x223, 0x43, 0x243, 0x63, 0x263, 0x83, 0x283, 0xa3, 0x2a3, 0x7, 0x207, 0x27, 0x227, 0x8, 0x208, 0x2008, 0x2208, 0x1008, 0x1208, 0x3008, 0x3208, 0x9, 0x209, 0x29, 0x229, 0xa, 0x1a, 0xb, 0x2a, 0x10b, 0x3a, 0x20b, 0x4a, 0x30b, 0x5a, 0x40b, 0x6a, 0x50b, 0x7a, 0x60b, 0x8a, 0x70b, 0x9a, 0x80b, 0xaa, 0x90b, 0xba, 0xa0b, 0xca, 0xb0b, 0xda, 0xc0b, 0xea, 0xd0b, 0xfa, 0xe0b, 0xf0b};
__device__ __forceinline__ void load_stage(uint32_t dst, uint32_t bar, const Maps& tm, int n) {
  const uint32_t e = c_stage[n - (n > NA)];
  mbar_expect_tx(bar, STAGE);
  tma_load_3d(dst, &tm.X + (e & 15), bar, (e >> 12) * 64, ((e >> 8) & 15) * 64, (e >> 4) & 15);
}
__device__ __forceinline__ void produce(uint32_t sW, uint32_t full, const Maps& tm, int n0, int n1) {
  uint32_t s = n0 % RING, ph = ((n0 / RING) & 1) ^ 1;
#pragma unroll 1
  for (int n = n0; n < n1; n++) {
    mbar_wait(full + 8 * RING + 8 * s, ph);
    PROF_STG(n, 0);
    load_stage(sW + s * STAGE, full + 8 * s, tm, n);
    if (++s == RING) { s = 0; ph ^= 1; }
  }
}
__device__ __forceinline__ Ctx make_ctx(uint32_t base, uint32_t dry, int pk = 0) {
  Ctx c; c.pk = pk; c.dry = dry;
  c.sA = base; c.sX = base + OFF_X; c.sW = base + OFF_W;
  c.full = base + OFF_MISC; c.empty = c.full + 8 * RING; c.stats = base + OFF_MISC + 256;
  c.wg = __shfl_sync(0xffffffff, (int)(threadIdx.x >> 7), 0);
  c.tid = threadIdx.x & 127; c.lane = threadIdx.x & 31;
  const uint32_t r = (c.tid >> 5) * 16 + (c.lane & 7) + ((c.lane >> 3) & 1) * 8;
  c.frag = r * 128; c.rsw = r & 7; c.hi = c.lane >> 4;
  return c;
}

constexpr int NSTG = 4;
constexpr int KVB = 160 * 128;
constexpr int NKV = T_ / 160;
static_assert(NSTG * 2 * KVB == RING * STAGE, "the K/V ring reuses the weight ring");

struct AttCtx { uint32_t sKV, full, empty, dry, wfull; const Maps* tm; int h, b, wg; };
__device__ __forceinline__ int kv_slot(int i) { return (i + 3) & 3; }
__device__ __forceinline__ void att_load(const AttCtx& a, int i, int v) {
  const int s = i & 3;
  mbar_expect_tx(a.full + 8 * (s + v * NSTG), KVB);
  tma_load_3d(a.sKV + kv_slot(i) * 2 * KVB + v * KVB, &a.tm->KV, a.full + 8 * (s + v * NSTG), 256 + v * 256 + a.h * 64, i * 160, a.b);
}
__device__ __forceinline__ void att_load_stage(const AttCtx& a, int i) { att_load(a, i, 0); att_load(a, i, 1); }
__device__ __forceinline__ void att_init_bars(const AttCtx& a) {
  for (int i = 0; i < NSTG; i++) { mbar_init(a.full + 8 * i, 1); mbar_init(a.full + 8 * (NSTG + i), 1); mbar_init(a.empty + 8 * i, 4); }
}
__device__ __forceinline__ void att_qk(float (&S)[40], uint32_t dQ, uint32_t kd) {
  wg_ss_n80_tb0<0>(S, dQ, kd);
#pragma unroll
  for (int kk = 1; kk < 4; kk++) wg_ss_n80_tb0<1>(S, dQ + kk * 2, kd + kk * 2);
}
__device__ __forceinline__ void att_pv(float (&O)[32], const uint32_t (&P)[20], uint32_t vd) {
#pragma unroll
  for (int kk = 0; kk < 5; kk++) wg_rs_n64_tb1<1>(O, P[kk * 4], P[kk * 4 + 1], P[kk * 4 + 2], P[kk * 4 + 3], vd + kk * 128);
}
template<bool SAFE>
__device__ __forceinline__ void att_softmax(const float (&S)[40], uint32_t (&P)[20], float (&O)[32], float& m0, float& m1, float& l0, float& l1) {
  if (SAFE) {
    float x0 = fmaxf(S[0], S[1]), x1 = fmaxf(S[2], S[3]);
#pragma unroll
    for (int i = 1; i < 10; i++) { x0 = fmaxf(x0, fmaxf(S[4 * i], S[4 * i + 1])); x1 = fmaxf(x1, fmaxf(S[4 * i + 2], S[4 * i + 3])); }
    x0 = fmaxf(x0, __shfl_xor_sync(0xffffffff, x0, 1)); x1 = fmaxf(x1, __shfl_xor_sync(0xffffffff, x1, 1));
    x0 = fmaxf(x0, __shfl_xor_sync(0xffffffff, x0, 2)); x1 = fmaxf(x1, __shfl_xor_sync(0xffffffff, x1, 2));
    const float n0 = fmaxf(m0, x0), n1 = fmaxf(m1, x1);
    const float f0 = ex2(m0 - n0), f1 = ex2(m1 - n1);
    m0 = n0; m1 = n1; l0 *= f0; l1 *= f1;
#pragma unroll
    for (int i = 0; i < 8; i++) { O[4 * i] *= f0; O[4 * i + 1] *= f0; O[4 * i + 2] *= f1; O[4 * i + 3] *= f1; }
  }
#pragma unroll
  for (int i = 0; i < 10; i++) {
    float p0, p1, p2, p3;
    if (SAFE) { p0 = ex2(S[4 * i] - m0); p1 = ex2(S[4 * i + 1] - m0); p2 = ex2(S[4 * i + 2] - m1); p3 = ex2(S[4 * i + 3] - m1); }
    else { p0 = ex2(S[4 * i]); p1 = ex2(S[4 * i + 1]); p2 = ex2(S[4 * i + 2]); p3 = ex2(S[4 * i + 3]); }
    l0 += p0 + p1; l1 += p2 + p3;
    P[2 * i] = pack_bf16(p0, p1); P[2 * i + 1] = pack_bf16(p2, p3);
  }
}
template<bool SAFE>
__device__ __forceinline__ void att_refill(const AttCtx& a, int it) {
  if ((threadIdx.x & 127) == 0) {
    mbar_arrive(a.empty + 8 * (it & 3));
    if (a.wg == (it & 3) && it >= 1 && !a.dry) {
      const bool kv = it - 1 + NSTG < NKV;
      if (kv || (!SAFE && a.wfull)) {
        mbar_wait(a.empty + 8 * ((it - 1) & 3), ((it - 1) >> 2) & 1);
        if (kv) att_load_stage(a, it - 1 + NSTG);
        else load_stage(a.sKV + (it - 22) * STAGE, a.wfull + 8 * (it - 22), *a.tm, NC + it - 22);
      }
    }
  }
  __syncwarp();
}
constexpr uint32_t KV_STG = 2 * KVB / 16, KV_VOFF = KVB / 16, KV_HALF = 80 * 128 / 16;
template<bool SAFE>
__device__ __forceinline__ void att_pass(const AttCtx& a, uint32_t dQ, float (&O)[32], float& l0, float& l1) {
  float S[40];
  uint32_t P[20];
  float m0 = -INFINITY, m1 = -INFINITY;
  l0 = 0.f; l1 = 0.f;
#pragma unroll
  for (int i = 0; i < 32; i++) O[i] = 0.f;
  const uint32_t dKV = dlo(a.sKV, 16);
  if (SAFE) {
#pragma unroll 1
    for (int j = 0; j < 2 * NKV; j++) {
      const int it = j >> 1, s = it & 3;
      const uint32_t kb = dKV + kv_slot(it) * KV_STG + (j & 1) * KV_HALF;
      mbar_wait(a.full + 8 * s, (it >> 2) & 1);
      wg_fence(); att_qk(S, dQ, kb); wg_commit(); wg_wait<0>();
      att_softmax<true>(S, P, O, m0, m1, l0, l1);
      mbar_wait(a.full + 8 * (NSTG + s), (it >> 2) & 1);
      wg_fence(); att_pv(O, P, kb + KV_VOFF); wg_commit(); wg_wait<0>();
      if (j & 1) att_refill<true>(a, it);
    }
  } else {
    mbar_wait(a.full, a.dry);
    wg_fence(); att_qk(S, dQ, dKV + 3 * KV_STG); wg_commit(); wg_wait<0>();
    att_softmax<false>(S, P, O, m0, m1, l0, l1);
    mbar_wait(a.full + 8 * NSTG, a.dry);
    wg_fence(); att_pv(O, P, dKV + 3 * KV_STG + KV_VOFF); att_qk(S, dQ, dKV + 3 * KV_STG + KV_HALF); wg_commit(); wg_wait<0>();
#pragma unroll 1
    for (int it = a.dry ? NKV - 2 : 0; it < NKV - 1; it++) {
      const int sn = (it + 1) & 3;
      const uint32_t kb = dKV + kv_slot(it) * KV_STG, kn = dKV + kv_slot(it + 1) * KV_STG, par = (((it + 1) >> 2) | a.dry) & 1;
      att_softmax<false>(S, P, O, m0, m1, l0, l1);
      mbar_wait(a.full + 8 * sn, par);
      wg_fence(); att_pv(O, P, kb + KV_VOFF + KV_HALF); att_qk(S, dQ, kn); wg_commit(); wg_wait<0>();
      att_refill<false>(a, it);
      att_softmax<false>(S, P, O, m0, m1, l0, l1);
      mbar_wait(a.full + 8 * (NSTG + sn), par);
      wg_fence(); att_pv(O, P, kn + KV_VOFF); att_qk(S, dQ, kn + KV_HALF); wg_commit(); wg_wait<0>();
    }
    att_softmax<false>(S, P, O, m0, m1, l0, l1);
    wg_fence(); att_pv(O, P, dKV + 3 * KV_STG + KV_VOFF + KV_HALF); wg_commit(); wg_wait<0>();
  }
  l0 += __shfl_xor_sync(0xffffffff, l0, 1); l1 += __shfl_xor_sync(0xffffffff, l1, 1);
  l0 += __shfl_xor_sync(0xffffffff, l0, 2); l1 += __shfl_xor_sync(0xffffffff, l1, 2);
}

struct Wptrs { const void* p[8]; uint32_t bytes[8]; };

constexpr uint32_t B_FULL = 0, B_EMPTY = 8 * RING, B_X = 16 * RING, B_ADONE = B_X + 8, B_Q = B_X + 16, B_EP = B_X + 24, B_ATT = B_X + 32;

__global__ void __launch_bounds__(512, 1) conformer_kernel(const __grid_constant__ Maps tm, const __grid_constant__ Wptrs wp, const uint4* __restrict__ dw) {
  extern __shared__ uint8_t smem_raw[];
  const uint32_t base = (smem_u32(smem_raw) + 1023) & ~1023u, misc = base + OFF_MISC;
  const uint32_t dry = blockIdx.x >= 128;
  const int tile = dry ? 0 : blockIdx.x;
  const bool has_tile = dry ? blockIdx.x == 128 : tile < NTILE;
  const int wg = __shfl_sync(0xffffffff, (int)(threadIdx.x >> 7), 0);
  AttCtx a;
  a.sKV = base + OFF_W; a.full = misc + B_ATT; a.empty = a.full + 16 * NSTG; a.tm = &tm;
  a.h = (blockIdx.x >> 4) & 3; a.b = (blockIdx.x >> 6) & 1; a.wg = wg; a.dry = dry; a.wfull = has_tile ? misc + B_FULL : 0;
  const int qt = blockIdx.x & 15;

  if (threadIdx.x == 256) {
    mbar_init(misc + B_X, 1);
    for (int i = 0; i < RING; i++) { mbar_init(misc + B_FULL + 8 * i, 1); mbar_init(misc + B_EMPTY + 8 * i, 1); }
    asm volatile("fence.mbarrier_init.release.cluster;" ::: "memory");
    if (has_tile && !dry) {
      mbar_expect_tx(misc + B_X, 32768);
      tma_load_3d(base + OFF_X, &tm.X, misc + B_X, 0, tile * 64, 0);
#pragma unroll 1
      for (int i = 0; i < RING; i++) load_stage(base + OFF_W + i * STAGE, misc + B_FULL + 8 * i, tm, i);
    }
  } else if (threadIdx.x == 288) {
    mbar_init(misc + B_ADONE, 2);
    mbar_init(misc + B_Q, 1);
    mbar_init(misc + B_EP, 1);
    att_init_bars(a);
    asm volatile("fence.mbarrier_init.release.cluster;" ::: "memory");
  } else if (threadIdx.x >= 320 && threadIdx.x < 333) {
    prefetch_tmap(&tm.X + (threadIdx.x - 320));
  }
  __syncthreads();
  auto get_epoch = [&]() {
    uint32_t e;
    mbar_wait(misc + B_EP, 0);
    asm volatile("ld.shared.u32 %0, [%1];" : "=r"(e) : "r"(misc + 248) : "memory");
    return e;
  };

  if (wg >= 2) {
    asm volatile("setmaxnreg.dec.sync.aligned.u32 24;");
    const uint32_t full = misc + B_FULL;
    if (threadIdx.x == 320) {
      const uint32_t e = atomicAdd(&g_start, 1) / NCTA;
      asm volatile("st.shared.u32 [%0], %1;" :: "r"(misc + 248), "r"(e + 1) : "memory");
      mbar_arrive(misc + B_EP);
    }
    if (dry) {
    } else if (threadIdx.x == 256) {
      if (has_tile) {
        produce(base + OFF_W, full, tm, RING, NA);
        mbar_wait(full + 8 * RING + 8 * 4, 1);
        mbar_arrive(full + 8 * 4); mbar_arrive(full + 8 * RING + 8 * 4);
        mbar_wait(misc + B_ADONE, 0);
      }
      cnt_wait(g_cnt1 + a.b * 64, 126 * get_epoch());
      mbar_expect_tx(misc + B_Q, 32768);
      tma_load_3d(base, &tm.Q, misc + B_Q, a.h * 64, qt * 256, a.b);
      att_load(a, 0, 0);
      mbar_wait(misc + B_Q, 0);
#pragma unroll 1
      for (int i = 1; i < NSTG; i++) att_load(a, i, 0);
    } else if ((threadIdx.x >> 5) == 12) {
      if (has_tile) bar_sync(9, 288);
      if (threadIdx.x == 384) {
        cnt_wait(g_cnt1 + a.b * 64 + 32, 126 * get_epoch());
        att_load(a, 0, 1);
        mbar_wait(a.full + 8 * NSTG, 0);
#pragma unroll 1
        for (int i = 1; i < NSTG; i++) att_load(a, i, 1);
      }
    } else if (has_tile && threadIdx.x >= 288 && threadIdx.x < 296) {
      const int w = threadIdx.x - 288;
      mbar_wait(misc + B_X, 0);
      const uint32_t bytes = wp.bytes[w], per = ((bytes / NTILE) + 127) & ~127u, off = per * tile;
      if (off < bytes) l2_prefetch((const uint8_t*)wp.p[w] + off, min(per, bytes - off));
    } else if (has_tile && threadIdx.x >= 416) {
      mbar_wait(full, 0);
      const int t = threadIdx.x - 416;
#pragma unroll 2
      for (int i = t; i < 2048; i += 96) g_att[tile * 2048 + i] = make_uint4(~0u, ~0u, ~0u, ~0u);
      g_halo[tile * 128 + t] = make_uint4(~0u, ~0u, ~0u, ~0u);
      if (t < 32) g_halo[tile * 128 + 96 + t] = make_uint4(~0u, ~0u, ~0u, ~0u);
    }
    __syncwarp();
    bar_sync(5 + wg, 384);
    asm volatile("setmaxnreg.inc.sync.aligned.u32 128;");
  } else {
    asm volatile("setmaxnreg.inc.sync.aligned.u32 232;");
    if (has_tile) {
      const Ctx c = make_ctx(base, dry);
      if (c.wg == 1) turn_end(c);
      float own[64];
      float a0, b0, a1, b1;
      PROF_MARK(0, 0);
      mbar_wait(misc + B_X, dry);
      PROF_MARK(0, 1);
      load_half(c, c.sX, own);
      ln_stats(c, own, 0.5f, a0, b0, a1, b1);
      store_half(c, c.sA, own, a0, b0, a1, b1);
      fence_async_smem();
      bar_sync(1, 256);
      PROF_MARK(0, 2);
      ff_block(c, 0, own);
      PROF_MARK(0, 3);
      ln_stats(c, own, 1.f, a0, b0, a1, b1);
      store_half(c, c.sA, own, a0, b0, a1, b1);
      fence_async_smem();
      bar_sync(1, 256);
      PROF_MARK(0, 4);
#pragma unroll 1
      for (int cc = dry ? 2 : 0; cc < 3; cc++) {
        float acc[64];
        const int j = 2 * cc + c.wg;
        gemm256<1>(c, acc, 32 + 2 * j);
        const float sc = (cc == 0) ? 0.125f * 1.4426950408889634f : 1.f;
        if (cc == 2 && !dry) bar_arrive(9, 288);
        if (c.tid == 0 && !dry) {
          if (cc == 2) {
            mbar_arrive(misc + B_ADONE);
            bulk_wait_all();
            if (tile <= 62) cnt_signal(g_cnt1);
            if (tile >= 62) cnt_signal(g_cnt1 + 64);
          } else bulk_wait_read();
        }
        bar_sync(3 + c.wg, 128);
        store_half(c, c.sX, acc, sc, 0.f, sc, 0.f);
        fence_async_smem();
        bar_sync(3 + c.wg, 128);
        if (c.tid == 0 && !dry) { tma_store_3d(&tm.QKVst, c.sX + c.wg * 16384, 0, tile * 64, 2 * j); bulk_commit(); }
      }
      PROF_MARK(0, 5);
      if (c.tid == 0) bulk_wait_read();
      bar_sync(3 + c.wg, 128);
      store_half_raw(c, c.sX, own);
    }
    else bar_sync(3 + wg, 128);
    asm volatile("setmaxnreg.dec.sync.aligned.u32 128;");
    bar_arrive(7, 384); bar_arrive(8, 384);
    if (has_tile && !dry && (threadIdx.x & 127) == 0) {
      bulk_wait_all();
      if (tile <= 62) cnt_signal(g_cnt1 + 32);
      if (tile >= 62) cnt_signal(g_cnt1 + 96);
    }
    __syncwarp();
    PROF_MARK(0, 6);
  }

  if (blockIdx.x == 128) return;
  if (blockIdx.x != 130) {
    const int lane = threadIdx.x & 31, wq = (threadIdx.x >> 5) & 3;
    const uint32_t dQ = dlo(base + wg * 8192, 16);
    float O[32], l0, l1;
    PROF_MARK(1, 1);
    mbar_wait(misc + B_Q, dry);
    PROF_MARK(1, 2);
    att_pass<false>(a, dQ, O, l0, l1);
    PROF_MARK(1, 3);
    float z = 0.f;
#pragma unroll
    for (int i = 0; i < 32; i++) z = fmaf(O[i], 0.f, z);
    const bool ok = (l0 >= 0x1p-80f) && (l0 <= 0x1p100f) && (l1 >= 0x1p-80f) && (l1 <= 0x1p100f) && (z == 0.f);
    const bool warp_bad = !__all_sync(0xffffffff, ok) && !dry;
    auto store_out = [&]() {
      const float i0 = 1.f / l0, i1 = 1.f / l1;
      const int row = qt * 256 + wg * 64 + wq * 16;
      if (row < T_ && !dry) {
        const int slab = (a.b * T_ + row) / 16;
        uint4* op = g_att + (slab * 16 + a.h * 4) * 32 + lane;
#pragma unroll
        for (int j = 0; j < 4; j++)
          asm volatile("st.relaxed.gpu.global.v4.u32 [%0], {%1,%2,%3,%4};" :: "l"(op + j * 32),
                       "r"(pack_bf16(O[8 * j] * i0, O[8 * j + 1] * i0)), "r"(pack_bf16(O[8 * j + 2] * i1, O[8 * j + 3] * i1)),
                       "r"(pack_bf16(O[8 * j + 4] * i0, O[8 * j + 5] * i0)), "r"(pack_bf16(O[8 * j + 6] * i1, O[8 * j + 7] * i1)) : "memory");
        __syncwarp();
        if (lane == 0) cnt_signal(g_cnt2 + slab * 32);
      }
      PROF_MARK(1, 4);
    };
    if (!warp_bad) store_out();
    if (__syncthreads_or(warp_bad)) {
      if (threadIdx.x == 0) {
        if (has_tile) { mbar_wait(misc + B_FULL, 1); mbar_wait(misc + B_FULL + 8, 1); }
        for (int i = 0; i < 3 * NSTG; i++) mbar_inval(a.full + 8 * i);
        att_init_bars(a);
        asm volatile("fence.mbarrier_init.release.cluster;" ::: "memory");
        fence_async_smem();
#pragma unroll 1
        for (int i = 0; i < NSTG; i++) att_load_stage(a, i);
      }
      __syncthreads();
      att_pass<true>(a, dQ, O, l0, l1);
      if (warp_bad) store_out();
      __syncthreads();
      if (has_tile) {
        if (threadIdx.x == 32) {
          load_stage(base + OFF_W, misc + B_X, tm, NC);
          load_stage(base + OFF_W + STAGE, misc + B_Q, tm, NC + 1);
        }
        mbar_wait(misc + B_X, 1); mbar_wait(misc + B_Q, 1);
      }
    }
    PROF_MARK(1, 5);
  } else {
    __syncthreads();
  }
  if (dry ? blockIdx.x != 130 : !has_tile) return;

  if (wg >= 2) {
    asm volatile("setmaxnreg.dec.sync.aligned.u32 24;");
    if (threadIdx.x == 256 && !dry) produce(base + OFF_W, misc + B_FULL, tm, NC + 2, NC + 48);
  } else {
    asm volatile("setmaxnreg.inc.sync.aligned.u32 232;");
    const Ctx c = make_ctx(base, dry);
    if (dry && c.wg == 1) turn_end(c);
    float own[64];
    float a0, b0, a1, b1;
    PROF_MARK(2, 0);
    load_half(c, c.sX, own);
    {
      uint4 af[16];
      const int slab = tile * 4 + (c.tid >> 5);
      const uint4* ap = g_att + slab * 512 + c.lane;
      if (c.lane == 0 && !dry) cnt_wait(g_cnt2 + slab * 32, 4 * get_epoch());
      __syncwarp();
      PROF_MARK(2, 1);
      for (uint32_t n = 0; n < (1u << 24); n++) {
        bool any = false;
#pragma unroll
        for (int i = 0; i < 16; i++)
          asm volatile("ld.relaxed.gpu.global.v4.u32 {%0,%1,%2,%3}, [%4];" : "=r"(af[i].x), "=r"(af[i].y), "=r"(af[i].z), "=r"(af[i].w) : "l"(ap + i * 32) : "memory");
#pragma unroll
        for (int i = 0; i < 16; i++) any |= max(max(af[i].x, af[i].y), max(af[i].z, af[i].w)) == ~0u;
        if (!__any_sync(0xffffffff, any) || dry) break;
      }
      PROF_MARK(2, 2);
      const int n = NC + 2 * c.wg;
      uint32_t b = stage_wait(c, n) + ((16384 >> 4) << 16);
      turn_begin(c);
      wg_fence();
#pragma unroll
      for (int kk = 0; kk < 8; kk++) wg_rs_n128_tb1<1>(own, af[kk].x, af[kk].y, af[kk].z, af[kk].w, b + kk * 128);
      wg_commit();
      b = stage_wait(c, n + 1) + ((16384 >> 4) << 16);
      wg_fence();
#pragma unroll
      for (int kk = 0; kk < 8; kk++) wg_rs_n128_tb1<1>(own, af[8 + kk].x, af[8 + kk].y, af[8 + kk].z, af[8 + kk].w, b + kk * 128);
      wg_commit();
      turn_end(c);
      wg_wait<1>(); stage_release(c, n);
      wg_wait<0>(); stage_release(c, n + 1);
    }
    PROF_MARK(2, 3);
    ln_stats(c, own, 0.5f, a0, b0, a1, b1);
    store_half(c, c.sA, own, a0, b0, a1, b1);
    fence_async_smem();
    bar_sync(1, 256);
    PROF_MARK(2, 4);
    uint4 dwr[5];
#pragma unroll
    for (int i = 0; i < 5; i++) dwr[i] = __ldg(dw + i * 32 + c.lane);
    const bool top = c.tid < 8, pub = (top || c.tid >= 120) && !dry;
    uint32_t* halo_out = (uint32_t*)g_halo + (tile * 4 + (top ? (c.tid >> 2) : ((c.tid >> 2) - 28))) * 128 + c.wg * 64 + (c.lane & 3);
#pragma unroll 1
    for (int q = dry; q < 2; q++) {
      float ab[64];
      gemm256<1>(c, ab, NC + 4 + 4 * q + 2 * c.wg);
#pragma unroll
      for (int j = 0; j < 4; j++) {
        float g[8];
#pragma unroll
        for (int i = 0; i < 8; i++) g[i] = fmaf(ab[8 * j + i], tanh_fast(ab[32 + 8 * j + i]), ab[8 * j + i]);
        const uint32_t p0 = pack_bf16(g[0], g[1]), p1 = pack_bf16(g[2], g[3]), p2 = pack_bf16(g[4], g[5]), p3 = pack_bf16(g[6], g[7]);
        if (pub) {
          uint32_t* hp = halo_out + q * 32 + j * 8;
          asm volatile("st.relaxed.gpu.global.u32 [%0], %1;" :: "l"(hp), "r"(top ? p0 : p1) : "memory");
          asm volatile("st.relaxed.gpu.global.u32 [%0], %1;" :: "l"(hp + 4), "r"(top ? p2 : p3) : "memory");
        }
        stsm_x4(c.sX + (2 * c.wg + q) * 8192 + c.frag + (((j * 2 + c.hi) ^ c.rsw) << 4), p0, p1, p2, p3);
      }
    }
    bar_sync(1, 256);
    PROF_MARK(2, 5);
    {
      const int wi = threadIdx.x >> 5;
      const uint32_t col = (c.lane >> 3) * 8192, ch = c.lane & 7;
      uint4 r[12];
#pragma unroll
      for (int i = 0; i < 12; i++) {
        const int row = (wi * 8 - 2 + i) & 63;
        r[i] = lds128(c.sX + col + row * 128 + ((ch ^ (row & 7)) << 4));
      }
      uint32_t w[5][4];
#pragma unroll
      for (int k = 0; k < 5; k++) {
        w[k][0] = bmul2(dwr[k].x, 0x3F003F00u); w[k][1] = bmul2(dwr[k].y, 0x3F003F00u);
        w[k][2] = bmul2(dwr[k].z, 0x3F003F00u); w[k][3] = bmul2(dwr[k].w, 0x3F003F00u);
      }
      auto conv_row = [&](int i) {
        uint32_t o[4];
#pragma unroll
        for (int q = 0; q < 4; q++) {
          uint32_t acc = bmul2(q == 0 ? r[i].x : q == 1 ? r[i].y : q == 2 ? r[i].z : r[i].w, w[0][q]);
#pragma unroll
          for (int k = 1; k < 5; k++) acc = bfma2(q == 0 ? r[i + k].x : q == 1 ? r[i + k].y : q == 2 ? r[i + k].z : r[i + k].w, w[k][q], acc);
          o[q] = pack_bf16(silu_half(bf_lo(acc)), silu_half(bf_hi(acc)));
        }
        sts128(c.sA + col + (wi * 8 + i) * 128 + ((ch ^ i) << 4), make_uint4(o[0], o[1], o[2], o[3]));
      };
      conv_row(2); conv_row(3); conv_row(4); conv_row(5);
      const int R0 = tile * 64 + wi * 8;
      if ((R0 % T_) == 0) { r[0] = make_uint4(0, 0, 0, 0); r[1] = r[0]; }
      else if (wi == 0 && !dry) { const uint4* sp = g_halo + ((tile - 1) * 4 + 2) * 32 + c.lane; data_poll(sp, r[0]); data_poll(sp + 32, r[1]); }
      if (((R0 + 8) % T_) == 0) { r[10] = make_uint4(0, 0, 0, 0); r[11] = r[10]; }
      else if (wi == 7 && !dry) { const uint4* sp = g_halo + ((tile + 1) * 4) * 32 + c.lane; data_poll(sp, r[10]); data_poll(sp + 32, r[11]); }
      conv_row(0); conv_row(1); conv_row(6); conv_row(7);
    }
    fence_async_smem();
    bar_sync(1, 256);
    PROF_MARK(2, 6);
    gemm256<0>(c, own, NC + 12 + 2 * c.wg);
    PROF_MARK(2, 7);
    ln_stats(c, own, 0.5f, a0, b0, a1, b1);
    store_half(c, c.sA, own, a0, b0, a1, b1);
    fence_async_smem();
    bar_sync(1, 256);
    PROF_MARK(2, 8);
    ff_block(c, NC + 16, own);
    PROF_MARK(2, 9);
    ln_stats(c, own, 1.f, a0, b0, a1, b1);
    store_half(c, c.sX, own, a0, b0, a1, b1);
    fence_async_smem();
    bar_sync(3 + c.wg, 128);
    if (c.tid == 0 && !dry) { tma_store_3d(&tm.Out, c.sX + c.wg * 16384, 0, tile * 64, 2 * c.wg); bulk_commit(); PROF_MARK(2, 10); bulk_wait_all(); }
    PROF_MARK(2, 11);
  }
}

typedef CUresult (*EncodeFn)(CUtensorMap*, CUtensorMapDataType, cuuint32_t, void*, const cuuint64_t*, const cuuint64_t*, const cuuint32_t*,
                             const cuuint32_t*, CUtensorMapInterleave, CUtensorMapSwizzle, CUtensorMapL2promotion, CUtensorMapFloatOOBfill);

CUtensorMap make_map(EncodeFn enc, const void* p, uint64_t d0, uint64_t d1, uint64_t d2, uint64_t s1, uint64_t s2, uint32_t b1, uint32_t b2) {
  CUtensorMap tm;
  cuuint64_t dims[3] = {d0, d1, d2};
  cuuint64_t strides[2] = {s1, s2};
  cuuint32_t box[3] = {64, b1, b2};
  cuuint32_t es[3] = {1, 1, 1};
  enc(&tm, CU_TENSOR_MAP_DATA_TYPE_BFLOAT16, 3, const_cast<void*>(p), dims, strides, box, es, CU_TENSOR_MAP_INTERLEAVE_NONE,
      CU_TENSOR_MAP_SWIZZLE_128B, CU_TENSOR_MAP_L2_PROMOTION_L2_256B, CU_TENSOR_MAP_FLOAT_OOB_FILL_NONE);
  return tm;
}
CUtensorMap blk_map(EncodeFn enc, const void* p, uint64_t rows, uint64_t cols, uint32_t boxrows, uint32_t boxblks) {
  return make_map(enc, p, 64, rows, cols / 64, cols * 2, 128, boxrows, boxblks);
}
CUtensorMap seq_map(EncodeFn enc, const void* p, uint64_t cols, uint32_t boxrows) {
  return make_map(enc, p, cols, T_, 2, cols * 2, cols * 2 * T_, boxrows, 1);
}

}

extern "C" void kernel_launch(void* const* d_in, const int* in_sizes, int n_in, void* d_out, int out_size) {
  (void)in_sizes; (void)n_in; (void)out_size;
  const void *x = d_in[0], *w1a = d_in[1], *w1b = d_in[2], *wqkv = d_in[3], *wo = d_in[4], *pw1 = d_in[5], *dw = d_in[6], *pw2 = d_in[7],
             *w2a = d_in[8], *w2b = d_in[9];
  void* fn = nullptr;
  cudaDriverEntryPointQueryResult qr;
  cudaGetDriverEntryPoint("cuTensorMapEncodeTiled", &fn, cudaEnableDefault, &qr);
  EncodeFn enc = (EncodeFn)fn;
  void* qkv;
  cudaGetSymbolAddress(&qkv, g_qkv);
  cudaFuncSetAttribute(conformer_kernel, cudaFuncAttributeMaxDynamicSharedMemorySize, SMEM_BYTES);

  Wptrs wp;
  const void* ws[8] = {w1a, w1b, wqkv, wo, pw1, pw2, w2a, w2b};
  const uint32_t wb[8] = {524288, 524288, 393216, 131072, 262144, 131072, 524288, 524288};
  for (int i = 0; i < 8; i++) { wp.p[i] = ws[i]; wp.bytes[i] = wb[i]; }
  Maps tm;
  tm.X = blk_map(enc, x, ROWS, 256, 64, 4);
  tm.W1a = blk_map(enc, w1a, 256, 1024, 256, 1);
  tm.W1b = blk_map(enc, w1b, 1024, 256, 64, 4);
  tm.Wqkv = blk_map(enc, wqkv, 256, 768, 128, 2);
  tm.QKVst = blk_map(enc, qkv, ROWS, 768, 64, 2);
  tm.Q = seq_map(enc, qkv, 768, 256);
  tm.KV = seq_map(enc, qkv, 768, 160);
  tm.Wo = blk_map(enc, wo, 256, 256, 128, 2);
  tm.Pw1 = make_map(enc, pw1, 256, 256, 2, 1024, 512, 128, 2);
  tm.Pw2 = blk_map(enc, pw2, 256, 256, 128, 2);
  tm.W2a = blk_map(enc, w2a, 256, 1024, 256, 1);
  tm.W2b = blk_map(enc, w2b, 1024, 256, 64, 4);
  tm.Out = blk_map(enc, d_out, ROWS, 256, 64, 2);
  conformer_kernel<<<NCTA, 512, SMEM_BYTES, cudaStreamPerThread>>>(tm, wp, (const uint4*)dw);
}
```

```cpp
#include <cuda_runtime.h>
#include <cuda_bf16.h>
#include <cuda.h>
#include <stdint.h>

namespace {

constexpr int T_ = 4000;
constexpr int ROWS = 8000;
constexpr int NTILE = 125;
constexpr int NCTA = 131;

__device__ __nv_bfloat16 g_qkv[ROWS * 768];
__device__ uint4 g_att[(ROWS / 16) * 16 * 32];
__device__ uint4 g_halo[NTILE * 4 * 32];
__device__ uint32_t g_start;
__device__ uint32_t g_cnt1[4 * 32];
__device__ uint32_t g_cnt2[ROWS / 16 * 32];

#define PROF_MARK(k, i) do {} while (0)
#define PROF_STG(n, i) do {} while (0)

__device__ __forceinline__ uint32_t smem_u32(const void* p) { return (uint32_t)__cvta_generic_to_shared(p); }
__device__ __forceinline__ void mbar_init(uint32_t bar, uint32_t cnt) { asm volatile("mbarrier.init.shared::cta.b64 [%0], %1;" :: "r"(bar), "r"(cnt) : "memory"); }
__device__ __forceinline__ void mbar_inval(uint32_t bar) { asm volatile("mbarrier.inval.shared::cta.b64 [%0];" :: "r"(bar) : "memory"); }
__device__ __forceinline__ void mbar_expect_tx(uint32_t bar, uint32_t bytes) { asm volatile("mbarrier.arrive.expect_tx.shared::cta.b64 _, [%0], %1;" :: "r"(bar), "r"(bytes) : "memory"); }
__device__ __forceinline__ void mbar_arrive(uint32_t bar) { asm volatile("mbarrier.arrive.shared::cta.b64 _, [%0];" :: "r"(bar) : "memory"); }
__device__ __forceinline__ void mbar_wait(uint32_t bar, uint32_t parity) {
  asm volatile("{\n.reg .pred p;\n.reg .u32 n;\n"
               "mbarrier.try_wait.parity.shared::cta.b64 p, [%0], %1;\n@p bra DONE_%=;\nmov.u32 n, 0;\n"
               "LOOP_%=:\nmbarrier.try_wait.parity.shared::cta.b64 p, [%0], %1;\n@p bra DONE_%=;\n"
               "add.u32 n, n, 1;\nsetp.lt.u32 p, n, 262144;\n@p bra LOOP_%=;\ntrap;\nDONE_%=:\n}\n" :: "r"(bar), "r"(parity) : "memory");
}
__device__ __forceinline__ void cnt_wait(const uint32_t* p, uint32_t target) {
  asm volatile("{\n.reg .pred p;\n.reg .u32 n, v;\nmov.u32 n, 0;\n"
               "LOOP_%=:\nld.relaxed.gpu.global.u32 v, [%0];\nsub.u32 v, v, %1;\nsetp.ge.s32 p, v, 0;\n@p bra DONE_%=;\n"
               "nanosleep.u32 40;\nadd.u32 n, n, 1;\nsetp.lt.u32 p, n, 262144;\n@p bra LOOP_%=;\ntrap;\nDONE_%=:\n}\n" :: "l"(p), "r"(target) : "memory");
}
__device__ __forceinline__ void cnt_signal(uint32_t* p) {
  asm volatile("red.relaxed.gpu.global.add.u32 [%0], 1;" :: "l"(p) : "memory");
}
__device__ __forceinline__ void tma_load_3d(uint32_t dst, const CUtensorMap* tm, uint32_t bar, int c0, int c1, int c2) {
  asm volatile("cp.async.bulk.tensor.3d.shared::cluster.global.mbarrier::complete_tx::bytes [%0], [%1, {%3, %4, %5}], [%2];"
    :: "r"(dst), "l"(tm), "r"(bar), "r"(c0), "r"(c1), "r"(c2) : "memory");
}
__device__ __forceinline__ void tma_store_3d(const CUtensorMap* tm, uint32_t src, int c0, int c1, int c2) {
  asm volatile("cp.async.bulk.tensor.3d.global.shared::cta.bulk_group [%0, {%2, %3, %4}], [%1];" :: "l"(tm), "r"(src), "r"(c0), "r"(c1), "r"(c2) : "memory");
}
__device__ __forceinline__ void bulk_commit() { asm volatile("cp.async.bulk.commit_group;" ::: "memory"); }
__device__ __forceinline__ void bulk_wait_read() { asm volatile("cp.async.bulk.wait_group.read 0;" ::: "memory"); }
__device__ __forceinline__ void bulk_wait_all() { asm volatile("cp.async.bulk.wait_group 0;" ::: "memory"); }
__device__ __forceinline__ void l2_prefetch(const void* p, uint32_t bytes) { asm volatile("cp.async.bulk.prefetch.L2.global [%0], %1;" :: "l"(p), "r"(bytes) : "memory"); }
__device__ __forceinline__ void prefetch_tmap(const CUtensorMap* tm) { asm volatile("prefetch.tensormap [%0];" :: "l"(tm) : "memory"); }
__device__ __forceinline__ void fence_async_smem() { asm volatile("fence.proxy.async.shared::cta;" ::: "memory"); }
__device__ __forceinline__ void wg_fence() { asm volatile("wgmma.fence.sync.aligned;" ::: "memory"); }
__device__ __forceinline__ void wg_commit() { asm volatile("wgmma.commit_group.sync.aligned;" ::: "memory"); }
template<int N> __device__ __forceinline__ void wg_wait() { asm volatile("wgmma.wait_group.sync.aligned %0;" :: "n"(N) : "memory"); }
__device__ __forceinline__ void bar_sync(int id, int n) { asm volatile("bar.sync %0, %1;" :: "r"(id), "r"(n) : "memory"); }
__device__ __forceinline__ void bar_arrive(int id, int n) { asm volatile("bar.arrive %0, %1;" :: "r"(id), "r"(n) : "memory"); }
__device__ __forceinline__ float ex2(float x) { float y; asm("ex2.approx.ftz.f32 %0, %1;" : "=f"(y) : "f"(x)); return y; }
__device__ __forceinline__ float tanh_fast(float x) { float y; asm("tanh.approx.f32 %0, %1;" : "=f"(y) : "f"(x)); return y; }
__device__ __forceinline__ uint32_t pack_bf16(float lo, float hi) { uint32_t r; asm("cvt.rn.bf16x2.f32 %0, %1, %2;" : "=r"(r) : "f"(hi), "f"(lo)); return r; }
__device__ __forceinline__ uint32_t bmul2(uint32_t a, uint32_t b) { uint32_t d; asm("mul.rn.bf16x2 %0, %1, %2;" : "=r"(d) : "r"(a), "r"(b)); return d; }
__device__ __forceinline__ uint32_t bfma2(uint32_t a, uint32_t b, uint32_t c) { uint32_t d; asm("fma.rn.bf16x2 %0, %1, %2, %3;" : "=r"(d) : "r"(a), "r"(b), "r"(c)); return d; }
__device__ __forceinline__ float bf_lo(uint32_t u) { return __uint_as_float(u << 16); }
__device__ __forceinline__ float bf_hi(uint32_t u) { return __uint_as_float(u & 0xffff0000u); }
__device__ __forceinline__ void ldsm_x4(uint32_t addr, uint32_t& r0, uint32_t& r1, uint32_t& r2, uint32_t& r3) {
  asm volatile("ldmatrix.sync.aligned.m8n8.x4.shared.b16 {%0,%1,%2,%3}, [%4];" : "=r"(r0), "=r"(r1), "=r"(r2), "=r"(r3) : "r"(addr) : "memory");
}
__device__ __forceinline__ void stsm_x4(uint32_t addr, uint32_t r0, uint32_t r1, uint32_t r2, uint32_t r3) {
  asm volatile("stmatrix.sync.aligned.m8n8.x4.shared.b16 [%0], {%1,%2,%3,%4};" :: "r"(addr), "r"(r0), "r"(r1), "r"(r2), "r"(r3) : "memory");
}
__device__ __forceinline__ void sts128(uint32_t addr, uint4 v) { asm volatile("st.shared.v4.b32 [%0], {%1,%2,%3,%4};" :: "r"(addr), "r"(v.x), "r"(v.y), "r"(v.z), "r"(v.w) : "memory"); }
__device__ __forceinline__ uint4 lds128(uint32_t addr) { uint4 v; asm volatile("ld.shared.v4.b32 {%0,%1,%2,%3}, [%4];" : "=r"(v.x), "=r"(v.y), "=r"(v.z), "=r"(v.w) : "r"(addr) : "memory"); return v; }
__device__ __forceinline__ void sts64f(uint32_t addr, float a, float b) { asm volatile("st.shared.v2.f32 [%0], {%1,%2};" :: "r"(addr), "f"(a), "f"(b) : "memory"); }
__device__ __forceinline__ float2 lds64f(uint32_t addr) { float2 v; asm volatile("ld.shared.v2.f32 {%0,%1}, [%2];" : "=f"(v.x), "=f"(v.y) : "r"(addr) : "memory"); return v; }
__device__ __forceinline__ uint32_t dlo(uint32_t addr, uint32_t lbo) { return ((addr & 0x3FFFF) >> 4) | ((lbo >> 4) << 16); }

template<int SD> __device__ __forceinline__ void wg_ss_n128_tb1(float (&d)[64], uint32_t da, uint32_t db) {
  asm volatile("{\n.reg .b64 da, db;\nmov.b64 da, {%64, 0x40000040};\nmov.b64 db, {%65, 0x40000040};\n"
    "wgmma.mma_async.sync.aligned.m64n128k16.f32.bf16.bf16 {%0, %1, %2, %3, %4, %5, %6, %7, %8, %9, %10, %11, %12, %13, %14, %15, %16, %17, %18, %19, %20, %21, %22, %23, %24, %25, %26, %27, %28, %29, %30, %31, %32, %33, %34, %35, %36, %37, %38, %39, %40, %41, %42, %43, %44, %45, %46, %47, %48, %49, %50, %51, %52, %53, %54, %55, %56, %57, %58, %59, %60, %61, %62, %63}, da, db, %66, 1, 1, 0, 1;\n}\n"
    : "+f"(d[0]), "+f"(d[1]), "+f"(d[2]), "+f"(d[3]), "+f"(d[4]), "+f"(d[5]), "+f"(d[6]), "+f"(d[7]), "+f"(d[8]), "+f"(d[9]), "+f"(d[10]), "+f"(d[11]), "+f"(d[12]), "+f"(d[13]), "+f"(d[14]), "+f"(d[15]), "+f"(d[16]), "+f"(d[17]), "+f"(d[18]), "+f"(d[19]), "+f"(d[20]), "+f"(d[21]), "+f"(d[22]), "+f"(d[23]), "+f"(d[24]), "+f"(d[25]), "+f"(d[26]), "+f"(d[27]), "+f"(d[28]), "+f"(d[29]), "+f"(d[30]), "+f"(d[31]), "+f"(d[32]), "+f"(d[33]), "+f"(d[34]), "+f"(d[35]), "+f"(d[36]), "+f"(d[37]), "+f"(d[38]), "+f"(d[39]), "+f"(d[40]), "+f"(d[41]), "+f"(d[42]), "+f"(d[43]), "+f"(d[44]), "+f"(d[45]), "+f"(d[46]), "+f"(d[47]), "+f"(d[48]), "+f"(d[49]), "+f"(d[50]), "+f"(d[51]), "+f"(d[52]), "+f"(d[53]), "+f"(d[54]), "+f"(d[55]), "+f"(d[56]), "+f"(d[57]), "+f"(d[58]), "+f"(d[59]), "+f"(d[60]), "+f"(d[61]), "+f"(d[62]), "+f"(d[63])
    : "r"(da), "r"(db), "n"(SD));
}
template<int SD> __device__ __forceinline__ void wg_rs_n128_tb1(float (&d)[64], uint32_t a0, uint32_t a1, uint32_t a2, uint32_t a3, uint32_t db) {
  asm volatile("{\n.reg .b64 db;\nmov.b64 db, {%68, 0x40000040};\n"
    "wgmma.mma_async.sync.aligned.m64n128k16.f32.bf16.bf16 {%0, %1, %2, %3, %4, %5, %6, %7, %8, %9, %10, %11, %12, %13, %14, %15, %16, %17, %18, %19, %20, %21, %22, %23, %24, %25, %26, %27, %28, %29, %30, %31, %32, %33, %34, %35, %36, %37, %38, %39, %40, %41, %42, %43, %44, %45, %46, %47, %48, %49, %50, %51, %52, %53, %54, %55, %56, %57, %58, %59, %60, %61, %62, %63}, {%64, %65, %66, %67}, db, %69, 1, 1, 1;\n}\n"
    : "+f"(d[0]), "+f"(d[1]), "+f"(d[2]), "+f"(d[3]), "+f"(d[4]), "+f"(d[5]), "+f"(d[6]), "+f"(d[7]), "+f"(d[8]), "+f"(d[9]), "+f"(d[10]), "+f"(d[11]), "+f"(d[12]), "+f"(d[13]), "+f"(d[14]), "+f"(d[15]), "+f"(d[16]), "+f"(d[17]), "+f"(d[18]), "+f"(d[19]), "+f"(d[20]), "+f"(d[21]), "+f"(d[22]), "+f"(d[23]), "+f"(d[24]), "+f"(d[25]), "+f"(d[26]), "+f"(d[27]), "+f"(d[28]), "+f"(d[29]), "+f"(d[30]), "+f"(d[31]), "+f"(d[32]), "+f"(d[33]), "+f"(d[34]), "+f"(d[35]), "+f"(d[36]), "+f"(d[37]), "+f"(d[38]), "+f"(d[39]), "+f"(d[40]), "+f"(d[41]), "+f"(d[42]), "+f"(d[43]), "+f"(d[44]), "+f"(d[45]), "+f"(d[46]), "+f"(d[47]), "+f"(d[48]), "+f"(d[49]), "+f"(d[50]), "+f"(d[51]), "+f"(d[52]), "+f"(d[53]), "+f"(d[54]), "+f"(d[55]), "+f"(d[56]), "+f"(d[57]), "+f"(d[58]), "+f"(d[59]), "+f"(d[60]), "+f"(d[61]), "+f"(d[62]), "+f"(d[63])
    : "r"(a0), "r"(a1), "r"(a2), "r"(a3), "r"(db), "n"(SD));
}
template<int SD> __device__ __forceinline__ void wg_ss_n64_tb1(float (&d)[32], uint32_t da, uint32_t db) {
  asm volatile("{\n.reg .b64 da, db;\nmov.b64 da, {%32, 0x40000040};\nmov.b64 db, {%33, 0x40000040};\n"
    "wgmma.mma_async.sync.aligned.m64n64k16.f32.bf16.bf16 {%0, %1, %2, %3, %4, %5, %6, %7, %8, %9, %10, %11, %12, %13, %14, %15, %16, %17, %18, %19, %20, %21, %22, %23, %24, %25, %26, %27, %28, %29, %30, %31}, da, db, %34, 1, 1, 0, 1;\n}\n"
    : "+f"(d[0]), "+f"(d[1]), "+f"(d[2]), "+f"(d[3]), "+f"(d[4]), "+f"(d[5]), "+f"(d[6]), "+f"(d[7]), "+f"(d[8]), "+f"(d[9]), "+f"(d[10]), "+f"(d[11]), "+f"(d[12]), "+f"(d[13]), "+f"(d[14]), "+f"(d[15]), "+f"(d[16]), "+f"(d[17]), "+f"(d[18]), "+f"(d[19]), "+f"(d[20]), "+f"(d[21]), "+f"(d[22]), "+f"(d[23]), "+f"(d[24]), "+f"(d[25]), "+f"(d[26]), "+f"(d[27]), "+f"(d[28]), "+f"(d[29]), "+f"(d[30]), "+f"(d[31])
    : "r"(da), "r"(db), "n"(SD));
}
template<int SD> __device__ __forceinline__ void wg_ss_n80_tb0(float (&d)[40], uint32_t da, uint32_t db) {
  asm volatile("{\n.reg .b64 da, db;\nmov.b64 da, {%40, 0x40000040};\nmov.b64 db, {%41, 0x40000040};\n"
    "wgmma.mma_async.sync.aligned.m64n80k16.f32.bf16.bf16 {%0, %1, %2, %3, %4, %5, %6, %7, %8, %9, %10, %11, %12, %13, %14, %15, %16, %17, %18, %19, %20, %21, %22, %23, %24, %25, %26, %27, %28, %29, %30, %31, %32, %33, %34, %35, %36, %37, %38, %39}, da, db, %42, 1, 1, 0, 0;\n}\n"
    : "+f"(d[0]), "+f"(d[1]), "+f"(d[2]), "+f"(d[3]), "+f"(d[4]), "+f"(d[5]), "+f"(d[6]), "+f"(d[7]), "+f"(d[8]), "+f"(d[9]), "+f"(d[10]), "+f"(d[11]), "+f"(d[12]), "+f"(d[13]), "+f"(d[14]), "+f"(d[15]), "+f"(d[16]), "+f"(d[17]), "+f"(d[18]), "+f"(d[19]), "+f"(d[20]), "+f"(d[21]), "+f"(d[22]), "+f"(d[23]), "+f"(d[24]), "+f"(d[25]), "+f"(d[26]), "+f"(d[27]), "+f"(d[28]), "+f"(d[29]), "+f"(d[30]), "+f"(d[31]), "+f"(d[32]), "+f"(d[33]), "+f"(d[34]), "+f"(d[35]), "+f"(d[36]), "+f"(d[37]), "+f"(d[38]), "+f"(d[39])
    : "r"(da), "r"(db), "n"(SD));
}
template<int SD> __device__ __forceinline__ void wg_rs_n64_tb1(float (&d)[32], uint32_t a0, uint32_t a1, uint32_t a2, uint32_t a3, uint32_t db) {
  asm volatile("{\n.reg .b64 db;\nmov.b64 db, {%36, 0x40000040};\n"
    "wgmma.mma_async.sync.aligned.m64n64k16.f32.bf16.bf16 {%0, %1, %2, %3, %4, %5, %6, %7, %8, %9, %10, %11, %12, %13, %14, %15, %16, %17, %18, %19, %20, %21, %22, %23, %24, %25, %26, %27, %28, %29, %30, %31}, {%32, %33, %34, %35}, db, %37, 1, 1, 1;\n}\n"
    : "+f"(d[0]), "+f"(d[1]), "+f"(d[2]), "+f"(d[3]), "+f"(d[4]), "+f"(d[5]), "+f"(d[6]), "+f"(d[7]), "+f"(d[8]), "+f"(d[9]), "+f"(d[10]), "+f"(d[11]), "+f"(d[12]), "+f"(d[13]), "+f"(d[14]), "+f"(d[15]), "+f"(d[16]), "+f"(d[17]), "+f"(d[18]), "+f"(d[19]), "+f"(d[20]), "+f"(d[21]), "+f"(d[22]), "+f"(d[23]), "+f"(d[24]), "+f"(d[25]), "+f"(d[26]), "+f"(d[27]), "+f"(d[28]), "+f"(d[29]), "+f"(d[30]), "+f"(d[31])
    : "r"(a0), "r"(a1), "r"(a2), "r"(a3), "r"(db), "n"(SD));
}

constexpr int RING = 5;
constexpr uint32_t STAGE = 32768;
constexpr uint32_t OFF_X = 32768, OFF_W = 65536, OFF_MISC = OFF_W + RING * STAGE;
constexpr int SMEM_BYTES = OFF_MISC + 256 + 1024 + 1024;

struct Ctx {
  uint32_t sA, sX, sW, full, empty, stats;
  uint32_t frag;
  uint32_t rsw;
  uint32_t hi;
  int wg, tid, lane;
  int pk;
  uint32_t dry;
};
__device__ __forceinline__ uint32_t stage_wait(const Ctx& c, int n) {
  const int q = n / RING, s = n - q * RING;
  if (c.tid == 0) PROF_STG(n + c.pk, 1);
  mbar_wait(c.full + 8 * s, (q | c.dry) & 1);
  if (c.tid == 0) PROF_STG(n + c.pk, 2);
  return dlo(c.sW + s * STAGE, 0);
}
__device__ __forceinline__ void stage_release(const Ctx& c, int n) {
  const int s = n % RING;
  if (c.tid == 0) { mbar_arrive(c.empty + 8 * s); PROF_STG(n + c.pk, 3); }
}
__device__ __forceinline__ void turn_begin(const Ctx& c) { bar_sync(5 + c.wg, 256); }
__device__ __forceinline__ void turn_end(const Ctx& c) { bar_arrive(5 + (c.wg ^ 1), 256); }
template<int FIRST> __device__ __forceinline__ void piece_ss(float (&acc)[64], uint32_t dA, uint32_t dB) {
  dB += (16384 >> 4) << 16;
  wg_ss_n128_tb1<FIRST ? 0 : 1>(acc, dA, dB);
#pragma unroll
  for (int kk = 1; kk < 8; kk++) wg_ss_n128_tb1<1>(acc, dA + (kk >> 2) * 512 + (kk & 3) * 2, dB + kk * 128);
}
__device__ __forceinline__ void ff_g1(float (&h)[32], uint32_t dA, uint32_t dB) {
  wg_ss_n64_tb1<0>(h, dA, dB);
#pragma unroll
  for (int kk = 1; kk < 16; kk++) wg_ss_n64_tb1<1>(h, dA + (kk >> 2) * 512 + (kk & 3) * 2, dB + kk * 128);
}
__device__ __forceinline__ void ff_g2(float (&acc)[64], const uint32_t (&P)[16], uint32_t dB, int half) {
  dB += ((8192 >> 4) << 16) + half * 1024;
#pragma unroll
  for (int kk = 0; kk < 4; kk++) wg_rs_n128_tb1<1>(acc, P[4 * kk], P[4 * kk + 1], P[4 * kk + 2], P[4 * kk + 3], dB + kk * 128);
}
template<int FIRST> __device__ __forceinline__ void gemm256(const Ctx& c, float (&acc)[64], int n) {
  const uint32_t dA = dlo(c.sA, 16);
  uint32_t b = stage_wait(c, n);
  turn_begin(c);
  wg_fence(); piece_ss<FIRST>(acc, dA, b); wg_commit();
  b = stage_wait(c, n + 1);
  wg_fence(); piece_ss<0>(acc, dA + 1024, b); wg_commit();
  turn_end(c);
  wg_wait<1>(); stage_release(c, n);
  wg_wait<0>(); stage_release(c, n + 1);
}
__device__ __forceinline__ uint32_t frag_addr(const Ctx& c, uint32_t tile, int j) {
  return tile + (2 * c.wg + (j >> 2)) * 8192 + c.frag + ((((j & 3) * 2 + c.hi) ^ c.rsw) << 4);
}
__device__ __forceinline__ void load_half(const Ctx& c, uint32_t tile, float (&v)[64]) {
#pragma unroll
  for (int j = 0; j < 8; j++) {
    uint32_t r0, r1, r2, r3;
    ldsm_x4(frag_addr(c, tile, j), r0, r1, r2, r3);
    v[8 * j] = bf_lo(r0); v[8 * j + 1] = bf_hi(r0); v[8 * j + 2] = bf_lo(r1); v[8 * j + 3] = bf_hi(r1);
    v[8 * j + 4] = bf_lo(r2); v[8 * j + 5] = bf_hi(r2); v[8 * j + 6] = bf_lo(r3); v[8 * j + 7] = bf_hi(r3);
  }
}
__device__ __forceinline__ void store_half(const Ctx& c, uint32_t tile, const float (&v)[64], float a0, float b0, float a1, float b1) {
#pragma unroll
  for (int j = 0; j < 8; j++)
    stsm_x4(frag_addr(c, tile, j),
            pack_bf16(fmaf(v[8 * j], a0, b0), fmaf(v[8 * j + 1], a0, b0)), pack_bf16(fmaf(v[8 * j + 2], a1, b1), fmaf(v[8 * j + 3], a1, b1)),
            pack_bf16(fmaf(v[8 * j + 4], a0, b0), fmaf(v[8 * j + 5], a0, b0)), pack_bf16(fmaf(v[8 * j + 6], a1, b1), fmaf(v[8 * j + 7], a1, b1)));
}
__device__ __forceinline__ void store_half_raw(const Ctx& c, uint32_t tile, const float (&v)[64]) {
#pragma unroll
  for (int j = 0; j < 8; j++)
    stsm_x4(frag_addr(c, tile, j), pack_bf16(v[8 * j], v[8 * j + 1]), pack_bf16(v[8 * j + 2], v[8 * j + 3]),
            pack_bf16(v[8 * j + 4], v[8 * j + 5]), pack_bf16(v[8 * j + 6], v[8 * j + 7]));
}
__device__ __forceinline__ void ln_stats(const Ctx& c, const float (&v)[64], float scale, float& a0, float& b0, float& a1, float& b1) {
  float s0 = 0.f, s1 = 0.f, q0 = 0.f, q1 = 0.f, s2 = 0.f, s3 = 0.f, q2 = 0.f, q3 = 0.f;
#pragma unroll
  for (int i = 0; i < 16; i++) {
    s0 += v[4 * i]; q0 = fmaf(v[4 * i], v[4 * i], q0);
    s2 += v[4 * i + 1]; q2 = fmaf(v[4 * i + 1], v[4 * i + 1], q2);
    s1 += v[4 * i + 2]; q1 = fmaf(v[4 * i + 2], v[4 * i + 2], q1);
    s3 += v[4 * i + 3]; q3 = fmaf(v[4 * i + 3], v[4 * i + 3], q3);
  }
  s0 += s2; q0 += q2; s1 += s3; q1 += q3;
  s0 += __shfl_xor_sync(0xffffffff, s0, 1); q0 += __shfl_xor_sync(0xffffffff, q0, 1);
  s1 += __shfl_xor_sync(0xffffffff, s1, 1); q1 += __shfl_xor_sync(0xffffffff, q1, 1);
  s0 += __shfl_xor_sync(0xffffffff, s0, 2); q0 += __shfl_xor_sync(0xffffffff, q0, 2);
  s1 += __shfl_xor_sync(0xffffffff, s1, 2); q1 += __shfl_xor_sync(0xffffffff, q1, 2);
  const uint32_t row = (c.tid >> 5) * 16 + (c.lane >> 2);
  if ((c.lane & 3) == 0) {
    sts64f(c.stats + c.wg * 512 + row * 8, s0, q0);
    sts64f(c.stats + c.wg * 512 + (row + 8) * 8, s1, q1);
  }
  bar_sync(1, 256);
  const float2 o0 = lds64f(c.stats + (c.wg ^ 1) * 512 + row * 8), o1 = lds64f(c.stats + (c.wg ^ 1) * 512 + (row + 8) * 8);
  const float m0 = (s0 + o0.x) * (1.f / 256.f), m1 = (s1 + o1.x) * (1.f / 256.f);
  const float var0 = fmaxf(fmaf(-m0, m0, (q0 + o0.y) * (1.f / 256.f)), 0.f), var1 = fmaxf(fmaf(-m1, m1, (q1 + o1.y) * (1.f / 256.f)), 0.f);
  a0 = rsqrtf(var0 + 1e-5f) * scale; a1 = rsqrtf(var1 + 1e-5f) * scale;
  b0 = -m0 * a0; b1 = -m1 * a1;
}
__device__ __forceinline__ float silu_half(float h) { return fmaf(h, tanh_fast(h), h); }
__device__ __forceinline__ float silu_quarter(float h) { const float q = 0.5f * h; return fmaf(q, tanh_fast(h), q); }
__device__ __forceinline__ void silu_pack(const float (&acc)[32], uint32_t (&P)[16]) {
#pragma unroll
  for (int i = 0; i < 16; i++) P[i] = pack_bf16(silu_quarter(acc[2 * i]), silu_quarter(acc[2 * i + 1]));
}
__device__ __forceinline__ void ff_block(const Ctx& c, int n0, float (&own)[64]) {
  float oth[64], h[32];
  uint32_t P[16];
#pragma unroll
  for (int i = 0; i < 64; i++) oth[i] = 0.f;
  const uint32_t dA = dlo(c.sA, 16);
  {
    const uint32_t b = stage_wait(c, n0 + c.wg);
    turn_begin(c);
    wg_fence(); ff_g1(h, dA, b); wg_commit();
    turn_end(c);
    wg_wait<0>(); stage_release(c, n0 + c.wg);
    silu_pack(h, P);
  }
#pragma unroll 1
  for (int it = c.dry ? 7 : 1; it < 8; it++) {
    const int n = n0 + 4 * it - 2 + 2 * c.wg;
    uint32_t b = stage_wait(c, n);
    turn_begin(c);
    wg_fence(); ff_g2(own, P, b, c.wg); ff_g2(oth, P, b, c.wg ^ 1); wg_commit();
    b = stage_wait(c, n + 1);
    wg_fence(); ff_g1(h, dA, b); wg_commit();
    turn_end(c);
    wg_wait<1>(); stage_release(c, n);
    wg_wait<0>(); stage_release(c, n + 1);
    silu_pack(h, P);
  }
  if (c.wg == 0) bar_arrive(2, 256);
  {
    const int n = n0 + 30 + c.wg;
    const uint32_t b = stage_wait(c, n);
    turn_begin(c);
    wg_fence(); ff_g2(oth, P, b, c.wg ^ 1); wg_commit();
    ff_g2(own, P, b, c.wg); wg_commit();
    turn_end(c);
    wg_wait<1>();
    if (c.wg == 1) bar_sync(2, 256);
    const uint32_t e = (c.wg == 0 ? c.sX : c.sA) + c.tid * 16;
#pragma unroll
    for (int i = 0; i < 16; i++)
      sts128(e + i * 2048, make_uint4(__float_as_uint(oth[4 * i]), __float_as_uint(oth[4 * i + 1]), __float_as_uint(oth[4 * i + 2]), __float_as_uint(oth[4 * i + 3])));
    wg_wait<0>(); stage_release(c, n);
  }
  bar_sync(1, 256);
  const uint32_t e = (c.wg == 0 ? c.sA : c.sX) + c.tid * 16;
#pragma unroll
  for (int i = 0; i < 16; i++) {
    const uint4 u = lds128(e + i * 2048);
    own[4 * i] += __uint_as_float(u.x); own[4 * i + 1] += __uint_as_float(u.y);
    own[4 * i + 2] += __uint_as_float(u.z); own[4 * i + 3] += __uint_as_float(u.w);
  }
}
struct Maps { CUtensorMap X, W1a, W1b, Wqkv, QKVst, Q, KV, Wo, Pw1, Pw2, W2a, W2b, Out; };
constexpr int NA = 44;
constexpr int NC = 45;
__constant__ uint16_t c_stage[92] = {0x1, 0x11, 0x2, 0x21, 0x102, 0x31, 0x202, 0x41, 0x302, 0x51, 0x402, 0x61, 0x502, 0x71, 0x602, 0x81, 0x702, 0x91, 0x802, 0xa1, 0x902, 0xb1, 0xa02, 0xc1, 0xb02, 0xd1, 0xc02, 0xe1, 0xd02, 0xf1, 0xe02, 0xf02, 0x3, 0x203, 0x23, 0x223, 0x43, 0x243, 0x63, 0x263, 0x83, 0x283, 0xa3, 0x2a3, 0x7, 0x207, 0x27, 0x227, 0x8, 0x208, 0x2008, 0x2208, 0x1008, 0x1208, 0x3008, 0x3208, 0x9, 0x209, 0x29, 0x229, 0xa, 0x1a, 0xb, 0x2a, 0x10b, 0x3a, 0x20b, 0x4a, 0x30b, 0x5a, 0x40b, 0x6a, 0x50b, 0x7a, 0x60b, 0x8a, 0x70b, 0x9a, 0x80b, 0xaa, 0x90b, 0xba, 0xa0b, 0xca, 0xb0b, 0xda, 0xc0b, 0xea, 0xd0b, 0xfa, 0xe0b, 0xf0b};
__device__ __forceinline__ void load_stage(uint32_t dst, uint32_t bar, const Maps& tm, int n) {
  const uint32_t e = c_stage[n - (n > NA)];
  mbar_expect_tx(bar, STAGE);
  tma_load_3d(dst, &tm.X + (e & 15), bar, (e >> 12) * 64, ((e >> 8) & 15) * 64, (e >> 4) & 15);
}
__device__ __forceinline__ void produce(uint32_t sW, uint32_t full, const Maps& tm, int n0, int n1) {
  uint32_t s = n0 % RING, ph = ((n0 / RING) & 1) ^ 1;
#pragma unroll 1
  for (int n = n0; n < n1; n++) {
    mbar_wait(full + 8 * RING + 8 * s, ph);
    PROF_STG(n, 0);
    load_stage(sW + s * STAGE, full + 8 * s, tm, n);
    if (++s == RING) { s = 0; ph ^= 1; }
  }
}
__device__ __forceinline__ Ctx make_ctx(uint32_t base, uint32_t dry, int pk = 0) {
  Ctx c; c.pk = pk; c.dry = dry;
  c.sA = base; c.sX = base + OFF_X; c.sW = base + OFF_W;
  c.full = base + OFF_MISC; c.empty = c.full + 8 * RING; c.stats = base + OFF_MISC + 256;
  c.wg = __shfl_sync(0xffffffff, (int)(threadIdx.x >> 7), 0);
  c.tid = threadIdx.x & 127; c.lane = threadIdx.x & 31;
  const uint32_t r = (c.tid >> 5) * 16 + (c.lane & 7) + ((c.lane >> 3) & 1) * 8;
  c.frag = r * 128; c.rsw = r & 7; c.hi = c.lane >> 4;
  return c;
}

constexpr int NSTG = 4;
constexpr int KVB = 160 * 128;
constexpr int NKV = T_ / 160;
static_assert(NSTG * 2 * KVB == RING * STAGE, "the K/V ring reuses the weight ring");

struct AttCtx { uint32_t sKV, full, empty, dry, wfull; const Maps* tm; int h, b, wg; };
__device__ __forceinline__ int kv_slot(int i) { return (i + 3) & 3; }
__device__ __forceinline__ void att_load(const AttCtx& a, int i, int v) {
  const int s = i & 3;
  mbar_expect_tx(a.full + 8 * (s + v * NSTG), KVB);
  tma_load_3d(a.sKV + kv_slot(i) * 2 * KVB + v * KVB, &a.tm->KV, a.full + 8 * (s + v * NSTG), 256 + v * 256 + a.h * 64, i * 160, a.b);
}
__device__ __forceinline__ void att_load_stage(const AttCtx& a, int i) { att_load(a, i, 0); att_load(a, i, 1); }
__device__ __forceinline__ void att_init_bars(const AttCtx& a) {
  for (int i = 0; i < NSTG; i++) { mbar_init(a.full + 8 * i, 1); mbar_init(a.full + 8 * (NSTG + i), 1); mbar_init(a.empty + 8 * i, 4); }
}
__device__ __forceinline__ void att_qk(float (&S)[40], uint32_t dQ, uint32_t kd) {
  wg_ss_n80_tb0<0>(S, dQ, kd);
#pragma unroll
  for (int kk = 1; kk < 4; kk++) wg_ss_n80_tb0<1>(S, dQ + kk * 2, kd + kk * 2);
}
__device__ __forceinline__ void att_pv(float (&O)[32], const uint32_t (&P)[20], uint32_t vd) {
#pragma unroll
  for (int kk = 0; kk < 5; kk++) wg_rs_n64_tb1<1>(O, P[kk * 4], P[kk * 4 + 1], P[kk * 4 + 2], P[kk * 4 + 3], vd + kk * 128);
}
template<bool SAFE>
__device__ __forceinline__ void att_softmax(const float (&S)[40], uint32_t (&P)[20], float (&O)[32], float& m0, float& m1, float& l0, float& l1) {
  if (SAFE) {
    float x0 = fmaxf(S[0], S[1]), x1 = fmaxf(S[2], S[3]);
#pragma unroll
    for (int i = 1; i < 10; i++) { x0 = fmaxf(x0, fmaxf(S[4 * i], S[4 * i + 1])); x1 = fmaxf(x1, fmaxf(S[4 * i + 2], S[4 * i + 3])); }
    x0 = fmaxf(x0, __shfl_xor_sync(0xffffffff, x0, 1)); x1 = fmaxf(x1, __shfl_xor_sync(0xffffffff, x1, 1));
    x0 = fmaxf(x0, __shfl_xor_sync(0xffffffff, x0, 2)); x1 = fmaxf(x1, __shfl_xor_sync(0xffffffff, x1, 2));
    const float n0 = fmaxf(m0, x0), n1 = fmaxf(m1, x1);
    const float f0 = ex2(m0 - n0), f1 = ex2(m1 - n1);
    m0 = n0; m1 = n1; l0 *= f0; l1 *= f1;
#pragma unroll
    for (int i = 0; i < 8; i++) { O[4 * i] *= f0; O[4 * i + 1] *= f0; O[4 * i + 2] *= f1; O[4 * i + 3] *= f1; }
  }
#pragma unroll
  for (int i = 0; i < 10; i++) {
    float p0, p1, p2, p3;
    if (SAFE) { p0 = ex2(S[4 * i] - m0); p1 = ex2(S[4 * i + 1] - m0); p2 = ex2(S[4 * i + 2] - m1); p3 = ex2(S[4 * i + 3] - m1); }
    else { p0 = ex2(S[4 * i]); p1 = ex2(S[4 * i + 1]); p2 = ex2(S[4 * i + 2]); p3 = ex2(S[4 * i + 3]); }
    l0 += p0 + p1; l1 += p2 + p3;
    P[2 * i] = pack_bf16(p0, p1); P[2 * i + 1] = pack_bf16(p2, p3);
  }
}
template<bool SAFE>
__device__ __forceinline__ void att_refill(const AttCtx& a, int it) {
  if ((threadIdx.x & 127) == 0) {
    mbar_arrive(a.empty + 8 * (it & 3));
    if (a.wg == (it & 3) && it >= 1 && !a.dry) {
      const bool kv = it - 1 + NSTG < NKV;
      if (kv || (!SAFE && a.wfull)) {
        mbar_wait(a.empty + 8 * ((it - 1) & 3), ((it - 1) >> 2) & 1);
        if (kv) att_load_stage(a, it - 1 + NSTG);
        else load_stage(a.sKV + (it - 22) * STAGE, a.wfull + 8 * (it - 22), *a.tm, NC + it - 22);
      }
    }
  }
  __syncwarp();
}
constexpr uint32_t KV_STG = 2 * KVB / 16, KV_VOFF = KVB / 16, KV_HALF = 80 * 128 / 16;
template<bool SAFE>
__device__ __forceinline__ void att_pass(const AttCtx& a, uint32_t dQ, float (&O)[32], float& l0, float& l1) {
  float S[40];
  uint32_t P[20];
  float m0 = -INFINITY, m1 = -INFINITY;
  l0 = 0.f; l1 = 0.f;
#pragma unroll
  for (int i = 0; i < 32; i++) O[i] = 0.f;
  const uint32_t dKV = dlo(a.sKV, 16);
  if (SAFE) {
#pragma unroll 1
    for (int j = 0; j < 2 * NKV; j++) {
      const int it = j >> 1, s = it & 3;
      const uint32_t kb = dKV + kv_slot(it) * KV_STG + (j & 1) * KV_HALF;
      mbar_wait(a.full + 8 * s, (it >> 2) & 1);
      wg_fence(); att_qk(S, dQ, kb); wg_commit(); wg_wait<0>();
      att_softmax<true>(S, P, O, m0, m1, l0, l1);
      mbar_wait(a.full + 8 * (NSTG + s), (it >> 2) & 1);
      wg_fence(); att_pv(O, P, kb + KV_VOFF); wg_commit(); wg_wait<0>();
      if (j & 1) att_refill<true>(a, it);
    }
  } else {
    mbar_wait(a.full, a.dry);
    wg_fence(); att_qk(S, dQ, dKV + 3 * KV_STG); wg_commit(); wg_wait<0>();
    att_softmax<false>(S, P, O, m0, m1, l0, l1);
    mbar_wait(a.full + 8 * NSTG, a.dry);
    wg_fence(); att_pv(O, P, dKV + 3 * KV_STG + KV_VOFF); att_qk(S, dQ, dKV + 3 * KV_STG + KV_HALF); wg_commit(); wg_wait<0>();
#pragma unroll 1
    for (int it = a.dry ? NKV - 2 : 0; it < NKV - 1; it++) {
      const int sn = (it + 1) & 3;
      const uint32_t kb = dKV + kv_slot(it) * KV_STG, kn = dKV + kv_slot(it + 1) * KV_STG, par = (((it + 1) >> 2) | a.dry) & 1;
      att_softmax<false>(S, P, O, m0, m1, l0, l1);
      mbar_wait(a.full + 8 * sn, par);
      wg_fence(); att_pv(O, P, kb + KV_VOFF + KV_HALF); att_qk(S, dQ, kn); wg_commit(); wg_wait<0>();
      att_refill<false>(a, it);
      att_softmax<false>(S, P, O, m0, m1, l0, l1);
      mbar_wait(a.full + 8 * (NSTG + sn), par);
      wg_fence(); att_pv(O, P, kn + KV_VOFF); att_qk(S, dQ, kn + KV_HALF); wg_commit(); wg_wait<0>();
    }
    att_softmax<false>(S, P, O, m0, m1, l0, l1);
    wg_fence(); att_pv(O, P, dKV + 3 * KV_STG + KV_VOFF + KV_HALF); wg_commit(); wg_wait<0>();
  }
  l0 += __shfl_xor_sync(0xffffffff, l0, 1); l1 += __shfl_xor_sync(0xffffffff, l1, 1);
  l0 += __shfl_xor_sync(0xffffffff, l0, 2); l1 += __shfl_xor_sync(0xffffffff, l1, 2);
}

struct Wptrs { const void* p[8]; uint32_t bytes[8]; };

constexpr uint32_t B_FULL = 0, B_EMPTY = 8 * RING, B_X = 16 * RING, B_ADONE = B_X + 8, B_Q = B_X + 16, B_EP = B_X + 24, B_ATT = B_X + 32;

__global__ void __launch_bounds__(512, 1) conformer_kernel(const __grid_constant__ Maps tm, const __grid_constant__ Wptrs wp, const uint4* __restrict__ dw) {
  extern __shared__ uint8_t smem_raw[];
  const uint32_t base = (smem_u32(smem_raw) + 1023) & ~1023u, misc = base + OFF_MISC;
  const uint32_t dry = blockIdx.x >= 128;
  const int tile = dry ? 0 : blockIdx.x;
  const bool has_tile = dry ? blockIdx.x == 128 : tile < NTILE;
  const int wg = __shfl_sync(0xffffffff, (int)(threadIdx.x >> 7), 0);
  AttCtx a;
  a.sKV = base + OFF_W; a.full = misc + B_ATT; a.empty = a.full + 16 * NSTG; a.tm = &tm;
  a.h = (blockIdx.x >> 4) & 3; a.b = (blockIdx.x >> 6) & 1; a.wg = wg; a.dry = dry; a.wfull = has_tile ? misc + B_FULL : 0;
  const int qt = blockIdx.x & 15;

  if (threadIdx.x == 256) {
    mbar_init(misc + B_X, 1);
    for (int i = 0; i < RING; i++) { mbar_init(misc + B_FULL + 8 * i, 1); mbar_init(misc + B_EMPTY + 8 * i, 1); }
    asm volatile("fence.mbarrier_init.release.cluster;" ::: "memory");
    if (has_tile && !dry) {
      mbar_expect_tx(misc + B_X, 32768);
      tma_load_3d(base + OFF_X, &tm.X, misc + B_X, 0, tile * 64, 0);
#pragma unroll 1
      for (int i = 0; i < RING; i++) load_stage(base + OFF_W + i * STAGE, misc + B_FULL + 8 * i, tm, i);
    }
  } else if (threadIdx.x == 288) {
    mbar_init(misc + B_ADONE, 2);
    mbar_init(misc + B_Q, 1);
    mbar_init(misc + B_EP, 1);
    att_init_bars(a);
    asm volatile("fence.mbarrier_init.release.cluster;" ::: "memory");
  } else if (threadIdx.x >= 320 && threadIdx.x < 333) {
    prefetch_tmap(&tm.X + (threadIdx.x - 320));
  }
  __syncthreads();
  auto get_epoch = [&]() {
    uint32_t e;
    mbar_wait(misc + B_EP, 0);
    asm volatile("ld.shared.u32 %0, [%1];" : "=r"(e) : "r"(misc + 248) : "memory");
    return e;
  };

  if (wg >= 2) {
    asm volatile("setmaxnreg.dec.sync.aligned.u32 24;");
    const uint32_t full = misc + B_FULL;
    if (threadIdx.x == 320) {
      const uint32_t e = atomicAdd(&g_start, 1) / NCTA;
      asm volatile("st.shared.u32 [%0], %1;" :: "r"(misc + 248), "r"(e + 1) : "memory");
      mbar_arrive(misc + B_EP);
    }
    if (dry) {
    } else if (threadIdx.x == 256) {
      if (has_tile) {
        produce(base + OFF_W, full, tm, RING, NA);
        mbar_wait(full + 8 * RING + 8 * 4, 1);
        mbar_arrive(full + 8 * 4); mbar_arrive(full + 8 * RING + 8 * 4);
        mbar_wait(misc + B_ADONE, 0);
      }
      cnt_wait(g_cnt1 + a.b * 64, 126 * get_epoch());
      mbar_expect_tx(misc + B_Q, 32768);
      tma_load_3d(base, &tm.Q, misc + B_Q, a.h * 64, qt * 256, a.b);
      att_load(a, 0, 0);
      mbar_wait(misc + B_Q, 0);
#pragma unroll 1
      for (int i = 1; i < NSTG; i++) att_load(a, i, 0);
    } else if ((threadIdx.x >> 5) == 12) {
      if (has_tile) bar_sync(9, 288);
      if (threadIdx.x == 384) {
        cnt_wait(g_cnt1 + a.b * 64 + 32, 126 * get_epoch());
        att_load(a, 0, 1);
        mbar_wait(a.full + 8 * NSTG, 0);
#pragma unroll 1
        for (int i = 1; i < NSTG; i++) att_load(a, i, 1);
      }
    } else if (has_tile && threadIdx.x >= 288 && threadIdx.x < 296) {
      const int w = threadIdx.x - 288;
      mbar_wait(misc + B_X, 0);
      const uint32_t bytes = wp.bytes[w], per = ((bytes / NTILE) + 127) & ~127u, off = per * tile;
      if (off < bytes) l2_prefetch((const uint8_t*)wp.p[w] + off, min(per, bytes - off));
    } else if (has_tile && threadIdx.x >= 416) {
      mbar_wait(full, 0);
      const int t = threadIdx.x - 416;
#pragma unroll 2
      for (int i = t; i < 2048; i += 96) g_att[tile * 2048 + i] = make_uint4(~0u, ~0u, ~0u, ~0u);
      g_halo[tile * 128 + t] = make_uint4(~0u, ~0u, ~0u, ~0u);
      if (t < 32) g_halo[tile * 128 + 96 + t] = make_uint4(~0u, ~0u, ~0u, ~0u);
    }
    __syncwarp();
    bar_sync(5 + wg, 384);
    asm volatile("setmaxnreg.inc.sync.aligned.u32 128;");
  } else {
    asm volatile("setmaxnreg.inc.sync.aligned.u32 232;");
    if (has_tile) {
      const Ctx c = make_ctx(base, dry);
      if (c.wg == 1) turn_end(c);
      float own[64];
      float a0, b0, a1, b1;
      PROF_MARK(0, 0);
      mbar_wait(misc + B_X, dry);
      PROF_MARK(0, 1);
      load_half(c, c.sX, own);
      ln_stats(c, own, 0.5f, a0, b0, a1, b1);
      store_half(c, c.sA, own, a0, b0, a1, b1);
      fence_async_smem();
      bar_sync(1, 256);
      PROF_MARK(0, 2);
      ff_block(c, 0, own);
      PROF_MARK(0, 3);
      ln_stats(c, own, 1.f, a0, b0, a1, b1);
      store_half(c, c.sA, own, a0, b0, a1, b1);
      fence_async_smem();
      bar_sync(1, 256);
      PROF_MARK(0, 4);
#pragma unroll 1
      for (int cc = dry ? 2 : 0; cc < 3; cc++) {
        float acc[64];
        const int j = 2 * cc + c.wg;
        gemm256<1>(c, acc, 32 + 2 * j);
        const float sc = (cc == 0) ? 0.125f * 1.4426950408889634f : 1.f;
        if (cc == 2 && !dry) bar_arrive(9, 288);
        if (c.tid == 0 && !dry) {
          if (cc == 2) {
            mbar_arrive(misc + B_ADONE);
            bulk_wait_all();
            if (tile <= 62) cnt_signal(g_cnt1);
            if (tile >= 62) cnt_signal(g_cnt1 + 64);
          } else bulk_wait_read();
        }
        bar_sync(3 + c.wg, 128);
        store_half(c, c.sX, acc, sc, 0.f, sc, 0.f);
        fence_async_smem();
        bar_sync(3 + c.wg, 128);
        if (c.tid == 0 && !dry) { tma_store_3d(&tm.QKVst, c.sX + c.wg * 16384, 0, tile * 64, 2 * j); bulk_commit(); }
      }
      PROF_MARK(0, 5);
      if (c.tid == 0) bulk_wait_read();
      bar_sync(3 + c.wg, 128);
      store_half_raw(c, c.sX, own);
    }
    else bar_sync(3 + wg, 128);
    asm volatile("setmaxnreg.dec.sync.aligned.u32 128;");
    bar_arrive(7, 384); bar_arrive(8, 384);
    if (has_tile && !dry && (threadIdx.x & 127) == 0) {
      bulk_wait_all();
      if (tile <= 62) cnt_signal(g_cnt1 + 32);
      if (tile >= 62) cnt_signal(g_cnt1 + 96);
    }
    __syncwarp();
    PROF_MARK(0, 6);
  }

  if (blockIdx.x == 128) return;
  if (blockIdx.x != 130) {
    const int lane = threadIdx.x & 31, wq = (threadIdx.x >> 5) & 3;
    const uint32_t dQ = dlo(base + wg * 8192, 16);
    float O[32], l0, l1;
    PROF_MARK(1, 1);
    mbar_wait(misc + B_Q, dry);
    PROF_MARK(1, 2);
    att_pass<false>(a, dQ, O, l0, l1);
    PROF_MARK(1, 3);
    float z = 0.f;
#pragma unroll
    for (int i = 0; i < 32; i++) z = fmaf(O[i], 0.f, z);
    const bool ok = (l0 >= 0x1p-80f) && (l0 <= 0x1p100f) && (l1 >= 0x1p-80f) && (l1 <= 0x1p100f) && (z == 0.f);
    const bool warp_bad = !__all_sync(0xffffffff, ok) && !dry;
    auto store_out = [&]() {
      const float i0 = 1.f / l0, i1 = 1.f / l1;
      const int row = qt * 256 + wg * 64 + wq * 16;
      if (row < T_ && !dry) {
        const int slab = (a.b * T_ + row) / 16;
        uint4* op = g_att + (slab * 16 + a.h * 4) * 32 + lane;
#pragma unroll
        for (int j = 0; j < 4; j++)
          asm volatile("st.relaxed.gpu.global.v4.u32 [%0], {%1,%2,%3,%4};" :: "l"(op + j * 32),
                       "r"(pack_bf16(O[8 * j] * i0, O[8 * j + 1] * i0)), "r"(pack_bf16(O[8 * j + 2] * i1, O[8 * j + 3] * i1)),
                       "r"(pack_bf16(O[8 * j + 4] * i0, O[8 * j + 5] * i0)), "r"(pack_bf16(O[8 * j + 6] * i1, O[8 * j + 7] * i1)) : "memory");
        __syncwarp();
        if (lane == 0) cnt_signal(g_cnt2 + slab * 32);
      }
      PROF_MARK(1, 4);
    };
    if (!warp_bad) store_out();
    if (__syncthreads_or(warp_bad)) {
      if (threadIdx.x == 0) {
        if (has_tile) { mbar_wait(misc + B_FULL, 1); mbar_wait(misc + B_FULL + 8, 1); }
        for (int i = 0; i < 3 * NSTG; i++) mbar_inval(a.full + 8 * i);
        att_init_bars(a);
        asm volatile("fence.mbarrier_init.release.cluster;" ::: "memory");
        fence_async_smem();
#pragma unroll 1
        for (int i = 0; i < NSTG; i++) att_load_stage(a, i);
      }
      __syncthreads();
      att_pass<true>(a, dQ, O, l0, l1);
      if (warp_bad) store_out();
      __syncthreads();
      if (has_tile) {
        if (threadIdx.x == 32) {
          load_stage(base + OFF_W, misc + B_X, tm, NC);
          load_stage(base + OFF_W + STAGE, misc + B_Q, tm, NC + 1);
        }
        mbar_wait(misc + B_X, 1); mbar_wait(misc + B_Q, 1);
      }
    }
    PROF_MARK(1, 5);
  } else {
    __syncthreads();
  }
  if (dry ? blockIdx.x != 130 : !has_tile) return;

  if (wg >= 2) {
    asm volatile("setmaxnreg.dec.sync.aligned.u32 24;");
    if (threadIdx.x == 256 && !dry) produce(base + OFF_W, misc + B_FULL, tm, NC + 2, NC + 48);
  } else {
    asm volatile("setmaxnreg.inc.sync.aligned.u32 232;");
    const Ctx c = make_ctx(base, dry);
    if (dry && c.wg == 1) turn_end(c);
    float own[64];
    float a0, b0, a1, b1;
    PROF_MARK(2, 0);
    {
      uint4 af[16];
      const int slab = tile * 4 + (c.tid >> 5);
      const uint4* ap = g_att + slab * 512 + c.lane;
      if (c.wg == 1) load_half(c, c.sX, own);
      for (uint32_t n = 0; n < (1u << 18); n++) {
        bool any = false;
#pragma unroll
        for (int i = 0; i < 16; i++)
          asm volatile("ld.relaxed.gpu.global.v4.u32 {%0,%1,%2,%3}, [%4];" : "=r"(af[i].x), "=r"(af[i].y), "=r"(af[i].z), "=r"(af[i].w) : "l"(ap + i * 32) : "memory");
        if (n == 0 && c.wg == 0) load_half(c, c.sX, own);
#pragma unroll
        for (int i = 0; i < 16; i++) any |= max(max(af[i].x, af[i].y), max(af[i].z, af[i].w)) == ~0u;
        if (!__any_sync(0xffffffff, any) || dry) break;
        if (c.lane == 0) cnt_wait(g_cnt2 + slab * 32, 4 * get_epoch());
        __syncwarp();
      }
      PROF_MARK(2, 2);
      const int n = NC + 2 * c.wg;
      uint32_t b = stage_wait(c, n) + ((16384 >> 4) << 16);
      turn_begin(c);
      wg_fence();
#pragma unroll
      for (int kk = 0; kk < 8; kk++) wg_rs_n128_tb1<1>(own, af[kk].x, af[kk].y, af[kk].z, af[kk].w, b + kk * 128);
      wg_commit();
      b = stage_wait(c, n + 1) + ((16384 >> 4) << 16);
      wg_fence();
#pragma unroll
      for (int kk = 0; kk < 8; kk++) wg_rs_n128_tb1<1>(own, af[8 + kk].x, af[8 + kk].y, af[8 + kk].z, af[8 + kk].w, b + kk * 128);
      wg_commit();
      turn_end(c);
      wg_wait<1>(); stage_release(c, n);
      wg_wait<0>(); stage_release(c, n + 1);
    }
    PROF_MARK(2, 3);
    ln_stats(c, own, 0.5f, a0, b0, a1, b1);
    store_half(c, c.sA, own, a0, b0, a1, b1);
    fence_async_smem();
    bar_sync(1, 256);
    PROF_MARK(2, 4);
    uint4 dwr[5];
#pragma unroll
    for (int i = 0; i < 5; i++) dwr[i] = __ldg(dw + i * 32 + c.lane);
    const bool top = c.tid < 8, pub = (top || c.tid >= 120) && !dry;
    uint32_t* halo_out = (uint32_t*)g_halo + (tile * 4 + (top ? (c.tid >> 2) : ((c.tid >> 2) - 28))) * 128 + c.wg * 64 + (c.lane & 3);
#pragma unroll 1
    for (int q = dry; q < 2; q++) {
      float ab[64];
      gemm256<1>(c, ab, NC + 4 + 4 * q + 2 * c.wg);
#pragma unroll
      for (int j = 0; j < 4; j++) {
        float g[8];
#pragma unroll
        for (int i = 0; i < 8; i++) g[i] = fmaf(ab[8 * j + i], tanh_fast(ab[32 + 8 * j + i]), ab[8 * j + i]);
        const uint32_t p0 = pack_bf16(g[0], g[1]), p1 = pack_bf16(g[2], g[3]), p2 = pack_bf16(g[4], g[5]), p3 = pack_bf16(g[6], g[7]);
        if (pub) {
          uint32_t* hp = halo_out + q * 32 + j * 8;
          asm volatile("st.relaxed.gpu.global.u32 [%0], %1;" :: "l"(hp), "r"(top ? p0 : p1) : "memory");
          asm volatile("st.relaxed.gpu.global.u32 [%0], %1;" :: "l"(hp + 4), "r"(top ? p2 : p3) : "memory");
        }
        stsm_x4(c.sX + (2 * c.wg + q) * 8192 + c.frag + (((j * 2 + c.hi) ^ c.rsw) << 4), p0, p1, p2, p3);
      }
    }
    bar_sync(1, 256);
    PROF_MARK(2, 5);
    {
      const int wi = threadIdx.x >> 5;
      const uint32_t col = (c.lane >> 3) * 8192, ch = c.lane & 7;
      uint4 r[12];
      const int R0 = tile * 64 + wi * 8;
      const bool first = (R0 % T_) == 0, last = ((R0 + 8) % T_) == 0;
      const bool far = ((wi == 0 && !first) || (wi == 7 && !last)) && !dry;
      const uint4* sp = g_halo + (wi == 0 ? (tile - 1) * 4 + 2 : (tile + 1) * 4) * 32 + c.lane;
      uint4 h0 = make_uint4(0, 0, 0, 0), h1 = h0;
      auto ld_halo = [&]() {
        asm volatile("ld.relaxed.gpu.global.v4.u32 {%0,%1,%2,%3}, [%4];" : "=r"(h0.x), "=r"(h0.y), "=r"(h0.z), "=r"(h0.w) : "l"(sp) : "memory");
        asm volatile("ld.relaxed.gpu.global.v4.u32 {%0,%1,%2,%3}, [%4];" : "=r"(h1.x), "=r"(h1.y), "=r"(h1.z), "=r"(h1.w) : "l"(sp + 32) : "memory");
      };
      if (far) ld_halo();
#pragma unroll
      for (int i = 0; i < 12; i++) {
        const int row = (wi * 8 - 2 + i) & 63;
        r[i] = lds128(c.sX + col + row * 128 + ((ch ^ (row & 7)) << 4));
      }
      uint32_t w[5][4];
#pragma unroll
      for (int k = 0; k < 5; k++) {
        w[k][0] = bmul2(dwr[k].x, 0x3F003F00u); w[k][1] = bmul2(dwr[k].y, 0x3F003F00u);
        w[k][2] = bmul2(dwr[k].z, 0x3F003F00u); w[k][3] = bmul2(dwr[k].w, 0x3F003F00u);
      }
      auto conv_row = [&](int i) {
        uint32_t o[4];
#pragma unroll
        for (int q = 0; q < 4; q++) {
          uint32_t acc = bmul2(q == 0 ? r[i].x : q == 1 ? r[i].y : q == 2 ? r[i].z : r[i].w, w[0][q]);
#pragma unroll
          for (int k = 1; k < 5; k++) acc = bfma2(q == 0 ? r[i + k].x : q == 1 ? r[i + k].y : q == 2 ? r[i + k].z : r[i + k].w, w[k][q], acc);
          o[q] = pack_bf16(silu_half(bf_lo(acc)), silu_half(bf_hi(acc)));
        }
        sts128(c.sA + col + (wi * 8 + i) * 128 + ((ch ^ i) << 4), make_uint4(o[0], o[1], o[2], o[3]));
      };
      conv_row(2); conv_row(3); conv_row(4); conv_row(5);
      if (far) {
        for (uint32_t n = 0; n < (1u << 18); n++) {
          const uint32_t mx = max(max(max(h0.x, h0.y), max(h0.z, h0.w)), max(max(h1.x, h1.y), max(h1.z, h1.w)));
          if (!__any_sync(0xffffffff, mx == ~0u)) break;
          ld_halo();
        }
      }
      if (first || (far && wi == 0)) { r[0] = h0; r[1] = h1; }
      if (last || (far && wi == 7)) { r[10] = h0; r[11] = h1; }
      conv_row(0); conv_row(1); conv_row(6); conv_row(7);
    }
    fence_async_smem();
    bar_sync(1, 256);
    PROF_MARK(2, 6);
    gemm256<0>(c, own, NC + 12 + 2 * c.wg);
    PROF_MARK(2, 7);
    ln_stats(c, own, 0.5f, a0, b0, a1, b1);
    store_half(c, c.sA, own, a0, b0, a1, b1);
    fence_async_smem();
    bar_sync(1, 256);
    PROF_MARK(2, 8);
    ff_block(c, NC + 16, own);
    PROF_MARK(2, 9);
    ln_stats(c, own, 1.f, a0, b0, a1, b1);
    store_half(c, c.sX, own, a0, b0, a1, b1);
    fence_async_smem();
    bar_sync(3 + c.wg, 128);
    if (c.tid == 0 && !dry) { tma_store_3d(&tm.Out, c.sX + c.wg * 16384, 0, tile * 64, 2 * c.wg); bulk_commit(); PROF_MARK(2, 10); bulk_wait_all(); }
    PROF_MARK(2, 11);
  }
}

typedef CUresult (*EncodeFn)(CUtensorMap*, CUtensorMapDataType, cuuint32_t, void*, const cuuint64_t*, const cuuint64_t*, const cuuint32_t*,
                             const cuuint32_t*, CUtensorMapInterleave, CUtensorMapSwizzle, CUtensorMapL2promotion, CUtensorMapFloatOOBfill);

CUtensorMap make_map(EncodeFn enc, const void* p, uint64_t d0, uint64_t d1, uint64_t d2, uint64_t s1, uint64_t s2, uint32_t b1, uint32_t b2) {
  CUtensorMap tm;
  cuuint64_t dims[3] = {d0, d1, d2};
  cuuint64_t strides[2] = {s1, s2};
  cuuint32_t box[3] = {64, b1, b2};
  cuuint32_t es[3] = {1, 1, 1};
  enc(&tm, CU_TENSOR_MAP_DATA_TYPE_BFLOAT16, 3, const_cast<void*>(p), dims, strides, box, es, CU_TENSOR_MAP_INTERLEAVE_NONE,
      CU_TENSOR_MAP_SWIZZLE_128B, CU_TENSOR_MAP_L2_PROMOTION_L2_256B, CU_TENSOR_MAP_FLOAT_OOB_FILL_NONE);
  return tm;
}
CUtensorMap blk_map(EncodeFn enc, const void* p, uint64_t rows, uint64_t cols, uint32_t boxrows, uint32_t boxblks) {
  return make_map(enc, p, 64, rows, cols / 64, cols * 2, 128, boxrows, boxblks);
}
CUtensorMap seq_map(EncodeFn enc, const void* p, uint64_t cols, uint32_t boxrows) {
  return make_map(enc, p, cols, T_, 2, cols * 2, cols * 2 * T_, boxrows, 1);
}

}

extern "C" void kernel_launch(void* const* d_in, const int* in_sizes, int n_in, void* d_out, int out_size) {
  (void)in_sizes; (void)n_in; (void)out_size;
  const void *x = d_in[0], *w1a = d_in[1], *w1b = d_in[2], *wqkv = d_in[3], *wo = d_in[4], *pw1 = d_in[5], *dw = d_in[6], *pw2 = d_in[7],
             *w2a = d_in[8], *w2b = d_in[9];
  void* fn = nullptr;
  cudaDriverEntryPointQueryResult qr;
  cudaGetDriverEntryPoint("cuTensorMapEncodeTiled", &fn, cudaEnableDefault, &qr);
  EncodeFn enc = (EncodeFn)fn;
  void* qkv;
  cudaGetSymbolAddress(&qkv, g_qkv);
  cudaFuncSetAttribute(conformer_kernel, cudaFuncAttributeMaxDynamicSharedMemorySize, SMEM_BYTES);

  Wptrs wp;
  const void* ws[8] = {w1a, w1b, wqkv, wo, pw1, pw2, w2a, w2b};
  const uint32_t wb[8] = {524288, 524288, 393216, 131072, 262144, 131072, 524288, 524288};
  for (int i = 0; i < 8; i++) { wp.p[i] = ws[i]; wp.bytes[i] = wb[i]; }
  Maps tm;
  tm.X = blk_map(enc, x, ROWS, 256, 64, 4);
  tm.W1a = blk_map(enc, w1a, 256, 1024, 256, 1);
  tm.W1b = blk_map(enc, w1b, 1024, 256, 64, 4);
  tm.Wqkv = blk_map(enc, wqkv, 256, 768, 128, 2);
  tm.QKVst = blk_map(enc, qkv, ROWS, 768, 64, 2);
  tm.Q = seq_map(enc, qkv, 768, 256);
  tm.KV = seq_map(enc, qkv, 768, 160);
  tm.Wo = blk_map(enc, wo, 256, 256, 128, 2);
  tm.Pw1 = make_map(enc, pw1, 256, 256, 2, 1024, 512, 128, 2);
  tm.Pw2 = blk_map(enc, pw2, 256, 256, 128, 2);
  tm.W2a = blk_map(enc, w2a, 256, 1024, 256, 1);
  tm.W2b = blk_map(enc, w2b, 1024, 256, 64, 4);
  tm.Out = blk_map(enc, d_out, ROWS, 256, 64, 2);
  conformer_kernel<<<NCTA, 512, SMEM_BYTES, cudaStreamPerThread>>>(tm, wp, (const uint4*)dw);
}
```

```cpp
#include <cuda_runtime.h>
#include <cuda_bf16.h>
#include <cuda.h>
#include <stdint.h>

namespace {

constexpr int T_ = 4000;
constexpr int ROWS = 8000;
constexpr int NTILE = 125;
constexpr int NCTA = 131;

__device__ __nv_bfloat16 g_qkv[ROWS * 768];
__device__ uint4 g_att[(ROWS / 16) * 16 * 32];
__device__ uint4 g_halo[NTILE * 4 * 32];
__device__ uint32_t g_start;
__device__ uint32_t g_cnt1[4 * 32];
__device__ uint32_t g_cnt2[ROWS / 16 * 32];

#define PROF_MARK(k, i) do {} while (0)
#define PROF_STG(n, i) do {} while (0)

__device__ __forceinline__ uint32_t smem_u32(const void* p) { return (uint32_t)__cvta_generic_to_shared(p); }
__device__ __forceinline__ void mbar_init(uint32_t bar, uint32_t cnt) { asm volatile("mbarrier.init.shared::cta.b64 [%0], %1;" :: "r"(bar), "r"(cnt) : "memory"); }
__device__ __forceinline__ void mbar_inval(uint32_t bar) { asm volatile("mbarrier.inval.shared::cta.b64 [%0];" :: "r"(bar) : "memory"); }
__device__ __forceinline__ void mbar_expect_tx(uint32_t bar, uint32_t bytes) { asm volatile("mbarrier.arrive.expect_tx.shared::cta.b64 _, [%0], %1;" :: "r"(bar), "r"(bytes) : "memory"); }
__device__ __forceinline__ void mbar_arrive(uint32_t bar) { asm volatile("mbarrier.arrive.shared::cta.b64 _, [%0];" :: "r"(bar) : "memory"); }
__device__ __forceinline__ void mbar_wait(uint32_t bar, uint32_t parity) {
  asm volatile("{\n.reg .pred p;\n.reg .u32 n;\n"
               "mbarrier.try_wait.parity.shared::cta.b64 p, [%0], %1;\n@p bra DONE_%=;\nmov.u32 n, 0;\n"
               "LOOP_%=:\nmbarrier.try_wait.parity.shared::cta.b64 p, [%0], %1;\n@p bra DONE_%=;\n"
               "add.u32 n, n, 1;\nsetp.lt.u32 p, n, 262144;\n@p bra LOOP_%=;\ntrap;\nDONE_%=:\n}\n" :: "r"(bar), "r"(parity) : "memory");
}
__device__ __forceinline__ void cnt_wait(const uint32_t* p, uint32_t target) {
  asm volatile("{\n.reg .pred p;\n.reg .u32 n, v;\nmov.u32 n, 0;\n"
               "LOOP_%=:\nld.relaxed.gpu.global.u32 v, [%0];\nsub.u32 v, v, %1;\nsetp.ge.s32 p, v, 0;\n@p bra DONE_%=;\n"
               "nanosleep.u32 40;\nadd.u32 n, n, 1;\nsetp.lt.u32 p, n, 262144;\n@p bra LOOP_%=;\ntrap;\nDONE_%=:\n}\n" :: "l"(p), "r"(target) : "memory");
}
__device__ __forceinline__ void cnt_signal(uint32_t* p) {
  asm volatile("red.relaxed.gpu.global.add.u32 [%0], 1;" :: "l"(p) : "memory");
}
__device__ __forceinline__ void tma_load_3d(uint32_t dst, const CUtensorMap* tm, uint32_t bar, int c0, int c1, int c2) {
  asm volatile("cp.async.bulk.tensor.3d.shared::cluster.global.mbarrier::complete_tx::bytes [%0], [%1, {%3, %4, %5}], [%2];"
    :: "r"(dst), "l"(tm), "r"(bar), "r"(c0), "r"(c1), "r"(c2) : "memory");
}
__device__ __forceinline__ void tma_store_3d(const CUtensorMap* tm, uint32_t src, int c0, int c1, int c2) {
  asm volatile("cp.async.bulk.tensor.3d.global.shared::cta.bulk_group [%0, {%2, %3, %4}], [%1];" :: "l"(tm), "r"(src), "r"(c0), "r"(c1), "r"(c2) : "memory");
}
__device__ __forceinline__ void bulk_commit() { asm volatile("cp.async.bulk.commit_group;" ::: "memory"); }
__device__ __forceinline__ void bulk_wait_read() { asm volatile("cp.async.bulk.wait_group.read 0;" ::: "memory"); }
__device__ __forceinline__ void bulk_wait_all() { asm volatile("cp.async.bulk.wait_group 0;" ::: "memory"); }
__device__ __forceinline__ void l2_prefetch(const void* p, uint32_t bytes) { asm volatile("cp.async.bulk.prefetch.L2.global [%0], %1;" :: "l"(p), "r"(bytes) : "memory"); }
__device__ __forceinline__ void prefetch_tmap(const CUtensorMap* tm) { asm volatile("prefetch.tensormap [%0];" :: "l"(tm) : "memory"); }
__device__ __forceinline__ void fence_async_smem() { asm volatile("fence.proxy.async.shared::cta;" ::: "memory"); }
__device__ __forceinline__ void wg_fence() { asm volatile("wgmma.fence.sync.aligned;" ::: "memory"); }
__device__ __forceinline__ void wg_commit() { asm volatile("wgmma.commit_group.sync.aligned;" ::: "memory"); }
template<int N> __device__ __forceinline__ void wg_wait() { asm volatile("wgmma.wait_group.sync.aligned %0;" :: "n"(N) : "memory"); }
__device__ __forceinline__ void bar_sync(int id, int n) { asm volatile("bar.sync %0, %1;" :: "r"(id), "r"(n) : "memory"); }
__device__ __forceinline__ void bar_arrive(int id, int n) { asm volatile("bar.arrive %0, %1;" :: "r"(id), "r"(n) : "memory"); }
__device__ __forceinline__ float ex2(float x) { float y; asm("ex2.approx.ftz.f32 %0, %1;" : "=f"(y) : "f"(x)); return y; }
__device__ __forceinline__ float tanh_fast(float x) { float y; asm("tanh.approx.f32 %0, %1;" : "=f"(y) : "f"(x)); return y; }
__device__ __forceinline__ uint32_t pack_bf16(float lo, float hi) { uint32_t r; asm("cvt.rn.bf16x2.f32 %0, %1, %2;" : "=r"(r) : "f"(hi), "f"(lo)); return r; }
__device__ __forceinline__ uint32_t bmul2(uint32_t a, uint32_t b) { uint32_t d; asm("mul.rn.bf16x2 %0, %1, %2;" : "=r"(d) : "r"(a), "r"(b)); return d; }
__device__ __forceinline__ uint32_t bfma2(uint32_t a, uint32_t b, uint32_t c) { uint32_t d; asm("fma.rn.bf16x2 %0, %1, %2, %3;" : "=r"(d) : "r"(a), "r"(b), "r"(c)); return d; }
__device__ __forceinline__ float bf_lo(uint32_t u) { return __uint_as_float(u << 16); }
__device__ __forceinline__ float bf_hi(uint32_t u) { return __uint_as_float(u & 0xffff0000u); }
__device__ __forceinline__ void ldsm_x4(uint32_t addr, uint32_t& r0, uint32_t& r1, uint32_t& r2, uint32_t& r3) {
  asm volatile("ldmatrix.sync.aligned.m8n8.x4.shared.b16 {%0,%1,%2,%3}, [%4];" : "=r"(r0), "=r"(r1), "=r"(r2), "=r"(r3) : "r"(addr) : "memory");
}
__device__ __forceinline__ void stsm_x4(uint32_t addr, uint32_t r0, uint32_t r1, uint32_t r2, uint32_t r3) {
  asm volatile("stmatrix.sync.aligned.m8n8.x4.shared.b16 [%0], {%1,%2,%3,%4};" :: "r"(addr), "r"(r0), "r"(r1), "r"(r2), "r"(r3) : "memory");
}
__device__ __forceinline__ void sts128(uint32_t addr, uint4 v) { asm volatile("st.shared.v4.b32 [%0], {%1,%2,%3,%4};" :: "r"(addr), "r"(v.x), "r"(v.y), "r"(v.z), "r"(v.w) : "memory"); }
__device__ __forceinline__ uint4 lds128(uint32_t addr) { uint4 v; asm volatile("ld.shared.v4.b32 {%0,%1,%2,%3}, [%4];" : "=r"(v.x), "=r"(v.y), "=r"(v.z), "=r"(v.w) : "r"(addr) : "memory"); return v; }
__device__ __forceinline__ void sts64f(uint32_t addr, float a, float b) { asm volatile("st.shared.v2.f32 [%0], {%1,%2};" :: "r"(addr), "f"(a), "f"(b) : "memory"); }
__device__ __forceinline__ float2 lds64f(uint32_t addr) { float2 v; asm volatile("ld.shared.v2.f32 {%0,%1}, [%2];" : "=f"(v.x), "=f"(v.y) : "r"(addr) : "memory"); return v; }
__device__ __forceinline__ uint32_t dlo(uint32_t addr, uint32_t lbo) { return ((addr & 0x3FFFF) >> 4) | ((lbo >> 4) << 16); }

template<int SD> __device__ __forceinline__ void wg_ss_n128_tb1(float (&d)[64], uint32_t da, uint32_t db) {
  asm volatile("{\n.reg .b64 da, db;\nmov.b64 da, {%64, 0x40000040};\nmov.b64 db, {%65, 0x40000040};\n"
    "wgmma.mma_async.sync.aligned.m64n128k16.f32.bf16.bf16 {%0, %1, %2, %3, %4, %5, %6, %7, %8, %9, %10, %11, %12, %13, %14, %15, %16, %17, %18, %19, %20, %21, %22, %23, %24, %25, %26, %27, %28, %29, %30, %31, %32, %33, %34, %35, %36, %37, %38, %39, %40, %41, %42, %43, %44, %45, %46, %47, %48, %49, %50, %51, %52, %53, %54, %55, %56, %57, %58, %59, %60, %61, %62, %63}, da, db, %66, 1, 1, 0, 1;\n}\n"
    : "+f"(d[0]), "+f"(d[1]), "+f"(d[2]), "+f"(d[3]), "+f"(d[4]), "+f"(d[5]), "+f"(d[6]), "+f"(d[7]), "+f"(d[8]), "+f"(d[9]), "+f"(d[10]), "+f"(d[11]), "+f"(d[12]), "+f"(d[13]), "+f"(d[14]), "+f"(d[15]), "+f"(d[16]), "+f"(d[17]), "+f"(d[18]), "+f"(d[19]), "+f"(d[20]), "+f"(d[21]), "+f"(d[22]), "+f"(d[23]), "+f"(d[24]), "+f"(d[25]), "+f"(d[26]), "+f"(d[27]), "+f"(d[28]), "+f"(d[29]), "+f"(d[30]), "+f"(d[31]), "+f"(d[32]), "+f"(d[33]), "+f"(d[34]), "+f"(d[35]), "+f"(d[36]), "+f"(d[37]), "+f"(d[38]), "+f"(d[39]), "+f"(d[40]), "+f"(d[41]), "+f"(d[42]), "+f"(d[43]), "+f"(d[44]), "+f"(d[45]), "+f"(d[46]), "+f"(d[47]), "+f"(d[48]), "+f"(d[49]), "+f"(d[50]), "+f"(d[51]), "+f"(d[52]), "+f"(d[53]), "+f"(d[54]), "+f"(d[55]), "+f"(d[56]), "+f"(d[57]), "+f"(d[58]), "+f"(d[59]), "+f"(d[60]), "+f"(d[61]), "+f"(d[62]), "+f"(d[63])
    : "r"(da), "r"(db), "n"(SD));
}
template<int SD> __device__ __forceinline__ void wg_rs_n128_tb1(float (&d)[64], uint32_t a0, uint32_t a1, uint32_t a2, uint32_t a3, uint32_t db) {
  asm volatile("{\n.reg .b64 db;\nmov.b64 db, {%68, 0x40000040};\n"
    "wgmma.mma_async.sync.aligned.m64n128k16.f32.bf16.bf16 {%0, %1, %2, %3, %4, %5, %6, %7, %8, %9, %10, %11, %12, %13, %14, %15, %16, %17, %18, %19, %20, %21, %22, %23, %24, %25, %26, %27, %28, %29, %30, %31, %32, %33, %34, %35, %36, %37, %38, %39, %40, %41, %42, %43, %44, %45, %46, %47, %48, %49, %50, %51, %52, %53, %54, %55, %56, %57, %58, %59, %60, %61, %62, %63}, {%64, %65, %66, %67}, db, %69, 1, 1, 1;\n}\n"
    : "+f"(d[0]), "+f"(d[1]), "+f"(d[2]), "+f"(d[3]), "+f"(d[4]), "+f"(d[5]), "+f"(d[6]), "+f"(d[7]), "+f"(d[8]), "+f"(d[9]), "+f"(d[10]), "+f"(d[11]), "+f"(d[12]), "+f"(d[13]), "+f"(d[14]), "+f"(d[15]), "+f"(d[16]), "+f"(d[17]), "+f"(d[18]), "+f"(d[19]), "+f"(d[20]), "+f"(d[21]), "+f"(d[22]), "+f"(d[23]), "+f"(d[24]), "+f"(d[25]), "+f"(d[26]), "+f"(d[27]), "+f"(d[28]), "+f"(d[29]), "+f"(d[30]), "+f"(d[31]), "+f"(d[32]), "+f"(d[33]), "+f"(d[34]), "+f"(d[35]), "+f"(d[36]), "+f"(d[37]), "+f"(d[38]), "+f"(d[39]), "+f"(d[40]), "+f"(d[41]), "+f"(d[42]), "+f"(d[43]), "+f"(d[44]), "+f"(d[45]), "+f"(d[46]), "+f"(d[47]), "+f"(d[48]), "+f"(d[49]), "+f"(d[50]), "+f"(d[51]), "+f"(d[52]), "+f"(d[53]), "+f"(d[54]), "+f"(d[55]), "+f"(d[56]), "+f"(d[57]), "+f"(d[58]), "+f"(d[59]), "+f"(d[60]), "+f"(d[61]), "+f"(d[62]), "+f"(d[63])
    : "r"(a0), "r"(a1), "r"(a2), "r"(a3), "r"(db), "n"(SD));
}
template<int SD> __device__ __forceinline__ void wg_ss_n64_tb1(float (&d)[32], uint32_t da, uint32_t db) {
  asm volatile("{\n.reg .b64 da, db;\nmov.b64 da, {%32, 0x40000040};\nmov.b64 db, {%33, 0x40000040};\n"
    "wgmma.mma_async.sync.aligned.m64n64k16.f32.bf16.bf16 {%0, %1, %2, %3, %4, %5, %6, %7, %8, %9, %10, %11, %12, %13, %14, %15, %16, %17, %18, %19, %20, %21, %22, %23, %24, %25, %26, %27, %28, %29, %30, %31}, da, db, %34, 1, 1, 0, 1;\n}\n"
    : "+f"(d[0]), "+f"(d[1]), "+f"(d[2]), "+f"(d[3]), "+f"(d[4]), "+f"(d[5]), "+f"(d[6]), "+f"(d[7]), "+f"(d[8]), "+f"(d[9]), "+f"(d[10]), "+f"(d[11]), "+f"(d[12]), "+f"(d[13]), "+f"(d[14]), "+f"(d[15]), "+f"(d[16]), "+f"(d[17]), "+f"(d[18]), "+f"(d[19]), "+f"(d[20]), "+f"(d[21]), "+f"(d[22]), "+f"(d[23]), "+f"(d[24]), "+f"(d[25]), "+f"(d[26]), "+f"(d[27]), "+f"(d[28]), "+f"(d[29]), "+f"(d[30]), "+f"(d[31])
    : "r"(da), "r"(db), "n"(SD));
}
template<int SD> __device__ __forceinline__ void wg_ss_n80_tb0(float (&d)[40], uint32_t da, uint32_t db) {
  asm volatile("{\n.reg .b64 da, db;\nmov.b64 da, {%40, 0x40000040};\nmov.b64 db, {%41, 0x40000040};\n"
    "wgmma.mma_async.sync.aligned.m64n80k16.f32.bf16.bf16 {%0, %1, %2, %3, %4, %5, %6, %7, %8, %9, %10, %11, %12, %13, %14, %15, %16, %17, %18, %19, %20, %21, %22, %23, %24, %25, %26, %27, %28, %29, %30, %31, %32, %33, %34, %35, %36, %37, %38, %39}, da, db, %42, 1, 1, 0, 0;\n}\n"
    : "+f"(d[0]), "+f"(d[1]), "+f"(d[2]), "+f"(d[3]), "+f"(d[4]), "+f"(d[5]), "+f"(d[6]), "+f"(d[7]), "+f"(d[8]), "+f"(d[9]), "+f"(d[10]), "+f"(d[11]), "+f"(d[12]), "+f"(d[13]), "+f"(d[14]), "+f"(d[15]), "+f"(d[16]), "+f"(d[17]), "+f"(d[18]), "+f"(d[19]), "+f"(d[20]), "+f"(d[21]), "+f"(d[22]), "+f"(d[23]), "+f"(d[24]), "+f"(d[25]), "+f"(d[26]), "+f"(d[27]), "+f"(d[28]), "+f"(d[29]), "+f"(d[30]), "+f"(d[31]), "+f"(d[32]), "+f"(d[33]), "+f"(d[34]), "+f"(d[35]), "+f"(d[36]), "+f"(d[37]), "+f"(d[38]), "+f"(d[39])
    : "r"(da), "r"(db), "n"(SD));
}
template<int SD> __device__ __forceinline__ void wg_rs_n64_tb1(float (&d)[32], uint32_t a0, uint32_t a1, uint32_t a2, uint32_t a3, uint32_t db) {
  asm volatile("{\n.reg .b64 db;\nmov.b64 db, {%36, 0x40000040};\n"
    "wgmma.mma_async.sync.aligned.m64n64k16.f32.bf16.bf16 {%0, %1, %2, %3, %4, %5, %6, %7, %8, %9, %10, %11, %12, %13, %14, %15, %16, %17, %18, %19, %20, %21, %22, %23, %24, %25, %26, %27, %28, %29, %30, %31}, {%32, %33, %34, %35}, db, %37, 1, 1, 1;\n}\n"
    : "+f"(d[0]), "+f"(d[1]), "+f"(d[2]), "+f"(d[3]), "+f"(d[4]), "+f"(d[5]), "+f"(d[6]), "+f"(d[7]), "+f"(d[8]), "+f"(d[9]), "+f"(d[10]), "+f"(d[11]), "+f"(d[12]), "+f"(d[13]), "+f"(d[14]), "+f"(d[15]), "+f"(d[16]), "+f"(d[17]), "+f"(d[18]), "+f"(d[19]), "+f"(d[20]), "+f"(d[21]), "+f"(d[22]), "+f"(d[23]), "+f"(d[24]), "+f"(d[25]), "+f"(d[26]), "+f"(d[27]), "+f"(d[28]), "+f"(d[29]), "+f"(d[30]), "+f"(d[31])
    : "r"(a0), "r"(a1), "r"(a2), "r"(a3), "r"(db), "n"(SD));
}

constexpr int RING = 5;
constexpr uint32_t STAGE = 32768;
constexpr uint32_t OFF_X = 32768, OFF_W = 65536, OFF_MISC = OFF_W + RING * STAGE;
constexpr int SMEM_BYTES = OFF_MISC + 256 + 1024 + 1024;

struct Ctx {
  uint32_t sA, sX, sW, full, empty, stats;
  uint32_t frag;
  uint32_t rsw;
  uint32_t hi;
  int wg, tid, lane;
  int pk;
  uint32_t dry;
};
__device__ __forceinline__ uint32_t stage_wait(const Ctx& c, int n) {
  const int q = n / RING, s = n - q * RING;
  if (c.tid == 0) PROF_STG(n + c.pk, 1);
  mbar_wait(c.full + 8 * s, (q | c.dry) & 1);
  if (c.tid == 0) PROF_STG(n + c.pk, 2);
  return dlo(c.sW + s * STAGE, 0);
}
__device__ __forceinline__ void stage_release(const Ctx& c, int n) {
  const int s = n % RING;
  if (c.tid == 0) { mbar_arrive(c.empty + 8 * s); PROF_STG(n + c.pk, 3); }
}
__device__ __forceinline__ void turn_begin(const Ctx& c) { bar_sync(5 + c.wg, 256); }
__device__ __forceinline__ void turn_end(const Ctx& c) { bar_arrive(5 + (c.wg ^ 1), 256); }
template<int FIRST> __device__ __forceinline__ void piece_ss(float (&acc)[64], uint32_t dA, uint32_t dB) {
  dB += (16384 >> 4) << 16;
  wg_ss_n128_tb1<FIRST ? 0 : 1>(acc, dA, dB);
#pragma unroll
  for (int kk = 1; kk < 8; kk++) wg_ss_n128_tb1<1>(acc, dA + (kk >> 2) * 512 + (kk & 3) * 2, dB + kk * 128);
}
__device__ __forceinline__ void ff_g1(float (&h)[32], uint32_t dA, uint32_t dB) {
  wg_ss_n64_tb1<0>(h, dA, dB);
#pragma unroll
  for (int kk = 1; kk < 16; kk++) wg_ss_n64_tb1<1>(h, dA + (kk >> 2) * 512 + (kk & 3) * 2, dB + kk * 128);
}
__device__ __forceinline__ void ff_g2(float (&acc)[64], const uint32_t (&P)[16], uint32_t dB, int half) {
  dB += ((8192 >> 4) << 16) + half * 1024;
#pragma unroll
  for (int kk = 0; kk < 4; kk++) wg_rs_n128_tb1<1>(acc, P[4 * kk], P[4 * kk + 1], P[4 * kk + 2], P[4 * kk + 3], dB + kk * 128);
}
template<int FIRST> __device__ __forceinline__ void gemm256(const Ctx& c, float (&acc)[64], int n) {
  const uint32_t dA = dlo(c.sA, 16);
  uint32_t b = stage_wait(c, n);
  turn_begin(c);
  wg_fence(); piece_ss<FIRST>(acc, dA, b); wg_commit();
  b = stage_wait(c, n + 1);
  wg_fence(); piece_ss<0>(acc, dA + 1024, b); wg_commit();
  turn_end(c);
  wg_wait<1>(); stage_release(c, n);
  wg_wait<0>(); stage_release(c, n + 1);
}
__device__ __forceinline__ uint32_t frag_addr(const Ctx& c, uint32_t tile, int j) {
  return tile + (2 * c.wg + (j >> 2)) * 8192 + c.frag + ((((j & 3) * 2 + c.hi) ^ c.rsw) << 4);
}
__device__ __forceinline__ void load_half(const Ctx& c, uint32_t tile, float (&v)[64]) {
#pragma unroll
  for (int j = 0; j < 8; j++) {
    uint32_t r0, r1, r2, r3;
    ldsm_x4(frag_addr(c, tile, j), r0, r1, r2, r3);
    v[8 * j] = bf_lo(r0); v[8 * j + 1] = bf_hi(r0); v[8 * j + 2] = bf_lo(r1); v[8 * j + 3] = bf_hi(r1);
    v[8 * j + 4] = bf_lo(r2); v[8 * j + 5] = bf_hi(r2); v[8 * j + 6] = bf_lo(r3); v[8 * j + 7] = bf_hi(r3);
  }
}
__device__ __forceinline__ void store_half(const Ctx& c, uint32_t tile, const float (&v)[64], float a0, float b0, float a1, float b1) {
#pragma unroll
  for (int j = 0; j < 8; j++)
    stsm_x4(frag_addr(c, tile, j),
            pack_bf16(fmaf(v[8 * j], a0, b0), fmaf(v[8 * j + 1], a0, b0)), pack_bf16(fmaf(v[8 * j + 2], a1, b1), fmaf(v[8 * j + 3], a1, b1)),
            pack_bf16(fmaf(v[8 * j + 4], a0, b0), fmaf(v[8 * j + 5], a0, b0)), pack_bf16(fmaf(v[8 * j + 6], a1, b1), fmaf(v[8 * j + 7], a1, b1)));
}
__device__ __forceinline__ void store_half_raw(const Ctx& c, uint32_t tile, const float (&v)[64]) {
#pragma unroll
  for (int j = 0; j < 8; j++)
    stsm_x4(frag_addr(c, tile, j), pack_bf16(v[8 * j], v[8 * j + 1]), pack_bf16(v[8 * j + 2], v[8 * j + 3]),
            pack_bf16(v[8 * j + 4], v[8 * j + 5]), pack_bf16(v[8 * j + 6], v[8 * j + 7]));
}
__device__ __forceinline__ void ln_stats(const Ctx& c, const float (&v)[64], float scale, float& a0, float& b0, float& a1, float& b1) {
  float s0 = 0.f, s1 = 0.f, q0 = 0.f, q1 = 0.f, s2 = 0.f, s3 = 0.f, q2 = 0.f, q3 = 0.f;
#pragma unroll
  for (int i = 0; i < 16; i++) {
    s0 += v[4 * i]; q0 = fmaf(v[4 * i], v[4 * i], q0);
    s2 += v[4 * i + 1]; q2 = fmaf(v[4 * i + 1], v[4 * i + 1], q2);
    s1 += v[4 * i + 2]; q1 = fmaf(v[4 * i + 2], v[4 * i + 2], q1);
    s3 += v[4 * i + 3]; q3 = fmaf(v[4 * i + 3], v[4 * i + 3], q3);
  }
  s0 += s2; q0 += q2; s1 += s3; q1 += q3;
  s0 += __shfl_xor_sync(0xffffffff, s0, 1); q0 += __shfl_xor_sync(0xffffffff, q0, 1);
  s1 += __shfl_xor_sync(0xffffffff, s1, 1); q1 += __shfl_xor_sync(0xffffffff, q1, 1);
  s0 += __shfl_xor_sync(0xffffffff, s0, 2); q0 += __shfl_xor_sync(0xffffffff, q0, 2);
  s1 += __shfl_xor_sync(0xffffffff, s1, 2); q1 += __shfl_xor_sync(0xffffffff, q1, 2);
  const uint32_t row = (c.tid >> 5) * 16 + (c.lane >> 2);
  if ((c.lane & 3) == 0) {
    sts64f(c.stats + c.wg * 512 + row * 8, s0, q0);
    sts64f(c.stats + c.wg * 512 + (row + 8) * 8, s1, q1);
  }
  bar_sync(1, 256);
  const float2 o0 = lds64f(c.stats + (c.wg ^ 1) * 512 + row * 8), o1 = lds64f(c.stats + (c.wg ^ 1) * 512 + (row + 8) * 8);
  const float m0 = (s0 + o0.x) * (1.f / 256.f), m1 = (s1 + o1.x) * (1.f / 256.f);
  const float var0 = fmaxf(fmaf(-m0, m0, (q0 + o0.y) * (1.f / 256.f)), 0.f), var1 = fmaxf(fmaf(-m1, m1, (q1 + o1.y) * (1.f / 256.f)), 0.f);
  a0 = rsqrtf(var0 + 1e-5f) * scale; a1 = rsqrtf(var1 + 1e-5f) * scale;
  b0 = -m0 * a0; b1 = -m1 * a1;
}
__device__ __forceinline__ float silu_half(float h) { return fmaf(h, tanh_fast(h), h); }
__device__ __forceinline__ float silu_quarter(float h) { const float q = 0.5f * h; return fmaf(q, tanh_fast(h), q); }
__device__ __forceinline__ void silu_pack(const float (&acc)[32], uint32_t (&P)[16]) {
#pragma unroll
  for (int i = 0; i < 16; i++) P[i] = pack_bf16(silu_quarter(acc[2 * i]), silu_quarter(acc[2 * i + 1]));
}
__device__ __forceinline__ void ff_block(const Ctx& c, int n0, float (&own)[64]) {
  float oth[64], h[32];
  uint32_t P[16];
#pragma unroll
  for (int i = 0; i < 64; i++) oth[i] = 0.f;
  const uint32_t dA = dlo(c.sA, 16);
  {
    const uint32_t b = stage_wait(c, n0 + c.wg);
    turn_begin(c);
    wg_fence(); ff_g1(h, dA, b); wg_commit();
    turn_end(c);
    wg_wait<0>(); stage_release(c, n0 + c.wg);
    silu_pack(h, P);
  }
#pragma unroll 1
  for (int it = c.dry ? 7 : 1; it < 8; it++) {
    const int n = n0 + 4 * it - 2 + 2 * c.wg;
    uint32_t b = stage_wait(c, n);
    turn_begin(c);
    wg_fence(); ff_g2(own, P, b, c.wg); ff_g2(oth, P, b, c.wg ^ 1); wg_commit();
    b = stage_wait(c, n + 1);
    wg_fence(); ff_g1(h, dA, b); wg_commit();
    turn_end(c);
    wg_wait<1>(); stage_release(c, n);
    wg_wait<0>(); stage_release(c, n + 1);
    silu_pack(h, P);
  }
  if (c.wg == 0) bar_arrive(2, 256);
  {
    const int n = n0 + 30 + c.wg;
    const uint32_t b = stage_wait(c, n);
    turn_begin(c);
    wg_fence(); ff_g2(oth, P, b, c.wg ^ 1); wg_commit();
    ff_g2(own, P, b, c.wg); wg_commit();
    turn_end(c);
    wg_wait<1>();
    if (c.wg == 1) bar_sync(2, 256);
    const uint32_t e = (c.wg == 0 ? c.sX : c.sA) + c.tid * 16;
#pragma unroll
    for (int i = 0; i < 16; i++)
      sts128(e + i * 2048, make_uint4(__float_as_uint(oth[4 * i]), __float_as_uint(oth[4 * i + 1]), __float_as_uint(oth[4 * i + 2]), __float_as_uint(oth[4 * i + 3])));
    wg_wait<0>(); stage_release(c, n);
  }
  bar_sync(1, 256);
  const uint32_t e = (c.wg == 0 ? c.sA : c.sX) + c.tid * 16;
#pragma unroll
  for (int i = 0; i < 16; i++) {
    const uint4 u = lds128(e + i * 2048);
    own[4 * i] += __uint_as_float(u.x); own[4 * i + 1] += __uint_as_float(u.y);
    own[4 * i + 2] += __uint_as_float(u.z); own[4 * i + 3] += __uint_as_float(u.w);
  }
}
struct Maps { CUtensorMap X, W1a, W1b, Wqkv, QKVst, Q, KV, Wo, Pw1, Pw2, W2a, W2b, Out; };
constexpr int NA = 44;
constexpr int NC = 45;
__constant__ uint16_t c_stage[92] = {0x1, 0x11, 0x2, 0x21, 0x102, 0x31, 0x202, 0x41, 0x302, 0x51, 0x402, 0x61, 0x502, 0x71, 0x602, 0x81, 0x702, 0x91, 0x802, 0xa1, 0x902, 0xb1, 0xa02, 0xc1, 0xb02, 0xd1, 0xc02, 0xe1, 0xd02, 0xf1, 0xe02, 0xf02, 0x3, 0x203, 0x23, 0x223, 0x43, 0x243, 0x63, 0x263, 0x83, 0x283, 0xa3, 0x2a3, 0x7, 0x207, 0x27, 0x227, 0x8, 0x208, 0x2008, 0x2208, 0x1008, 0x1208, 0x3008, 0x3208, 0x9, 0x29, 0x209, 0x229, 0xa, 0x1a, 0xb, 0x2a, 0x10b, 0x3a, 0x20b, 0x4a, 0x30b, 0x5a, 0x40b, 0x6a, 0x50b, 0x7a, 0x60b, 0x8a, 0x70b, 0x9a, 0x80b, 0xaa, 0x90b, 0xba, 0xa0b, 0xca, 0xb0b, 0xda, 0xc0b, 0xea, 0xd0b, 0xfa, 0xe0b, 0xf0b};
__device__ __forceinline__ void load_stage(uint32_t dst, uint32_t bar, const Maps& tm, int n) {
  const uint32_t e = c_stage[n - (n > NA)];
  mbar_expect_tx(bar, STAGE);
  tma_load_3d(dst, &tm.X + (e & 15), bar, (e >> 12) * 64, ((e >> 8) & 15) * 64, (e >> 4) & 15);
}
__device__ __forceinline__ void produce(uint32_t sW, uint32_t full, const Maps& tm, int n0, int n1) {
  uint32_t s = n0 % RING, ph = ((n0 / RING) & 1) ^ 1;
#pragma unroll 1
  for (int n = n0; n < n1; n++) {
    mbar_wait(full + 8 * RING + 8 * s, ph);
    PROF_STG(n, 0);
    load_stage(sW + s * STAGE, full + 8 * s, tm, n);
    if (++s == RING) { s = 0; ph ^= 1; }
  }
}
__device__ __forceinline__ Ctx make_ctx(uint32_t base, uint32_t dry, int pk = 0) {
  Ctx c; c.pk = pk; c.dry = dry;
  c.sA = base; c.sX = base + OFF_X; c.sW = base + OFF_W;
  c.full = base + OFF_MISC; c.empty = c.full + 8 * RING; c.stats = base + OFF_MISC + 256;
  c.wg = __shfl_sync(0xffffffff, (int)(threadIdx.x >> 7), 0);
  c.tid = threadIdx.x & 127; c.lane = threadIdx.x & 31;
  const uint32_t r = (c.tid >> 5) * 16 + (c.lane & 7) + ((c.lane >> 3) & 1) * 8;
  c.frag = r * 128; c.rsw = r & 7; c.hi = c.lane >> 4;
  return c;
}

constexpr int NSTG = 4;
constexpr int KVB = 160 * 128;
constexpr int NKV = T_ / 160;
static_assert(NSTG * 2 * KVB == RING * STAGE, "the K/V ring reuses the weight ring");

struct AttCtx { uint32_t sKV, full, empty, dry, wfull; const Maps* tm; int h, b, wg; };
__device__ __forceinline__ int kv_slot(int i) { return (i + 3) & 3; }
__device__ __forceinline__ void att_load(const AttCtx& a, int i, int v) {
  const int s = i & 3;
  mbar_expect_tx(a.full + 8 * (s + v * NSTG), KVB);
  tma_load_3d(a.sKV + kv_slot(i) * 2 * KVB + v * KVB, &a.tm->KV, a.full + 8 * (s + v * NSTG), 256 + v * 256 + a.h * 64, i * 160, a.b);
}
__device__ __forceinline__ void att_load_stage(const AttCtx& a, int i) { att_load(a, i, 0); att_load(a, i, 1); }
__device__ __forceinline__ void att_init_bars(const AttCtx& a) {
  for (int i = 0; i < NSTG; i++) { mbar_init(a.full + 8 * i, 1); mbar_init(a.full + 8 * (NSTG + i), 1); mbar_init(a.empty + 8 * i, 4); }
}
__device__ __forceinline__ void att_qk(float (&S)[40], uint32_t dQ, uint32_t kd) {
  wg_ss_n80_tb0<0>(S, dQ, kd);
#pragma unroll
  for (int kk = 1; kk < 4; kk++) wg_ss_n80_tb0<1>(S, dQ + kk * 2, kd + kk * 2);
}
__device__ __forceinline__ void att_pv(float (&O)[32], const uint32_t (&P)[20], uint32_t vd) {
#pragma unroll
  for (int kk = 0; kk < 5; kk++) wg_rs_n64_tb1<1>(O, P[kk * 4], P[kk * 4 + 1], P[kk * 4 + 2], P[kk * 4 + 3], vd + kk * 128);
}
template<bool SAFE>
__device__ __forceinline__ void att_softmax(const float (&S)[40], uint32_t (&P)[20], float (&O)[32], float& m0, float& m1, float& l0, float& l1) {
  if (SAFE) {
    float x0 = fmaxf(S[0], S[1]), x1 = fmaxf(S[2], S[3]);
#pragma unroll
    for (int i = 1; i < 10; i++) { x0 = fmaxf(x0, fmaxf(S[4 * i], S[4 * i + 1])); x1 = fmaxf(x1, fmaxf(S[4 * i + 2], S[4 * i + 3])); }
    x0 = fmaxf(x0, __shfl_xor_sync(0xffffffff, x0, 1)); x1 = fmaxf(x1, __shfl_xor_sync(0xffffffff, x1, 1));
    x0 = fmaxf(x0, __shfl_xor_sync(0xffffffff, x0, 2)); x1 = fmaxf(x1, __shfl_xor_sync(0xffffffff, x1, 2));
    const float n0 = fmaxf(m0, x0), n1 = fmaxf(m1, x1);
    const float f0 = ex2(m0 - n0), f1 = ex2(m1 - n1);
    m0 = n0; m1 = n1; l0 *= f0; l1 *= f1;
#pragma unroll
    for (int i = 0; i < 8; i++) { O[4 * i] *= f0; O[4 * i + 1] *= f0; O[4 * i + 2] *= f1; O[4 * i + 3] *= f1; }
  }
#pragma unroll
  for (int i = 0; i < 10; i++) {
    float p0, p1, p2, p3;
    if (SAFE) { p0 = ex2(S[4 * i] - m0); p1 = ex2(S[4 * i + 1] - m0); p2 = ex2(S[4 * i + 2] - m1); p3 = ex2(S[4 * i + 3] - m1); }
    else { p0 = ex2(S[4 * i]); p1 = ex2(S[4 * i + 1]); p2 = ex2(S[4 * i + 2]); p3 = ex2(S[4 * i + 3]); }
    l0 += p0 + p1; l1 += p2 + p3;
    P[2 * i] = pack_bf16(p0, p1); P[2 * i + 1] = pack_bf16(p2, p3);
  }
}
template<bool SAFE>
__device__ __forceinline__ void att_refill(const AttCtx& a, int it) {
  if ((threadIdx.x & 127) == 0) {
    mbar_arrive(a.empty + 8 * (it & 3));
    if (a.wg == (it & 3) && it >= 1 && !a.dry) {
      const bool kv = it - 1 + NSTG < NKV;
      if (kv || (!SAFE && a.wfull)) {
        mbar_wait(a.empty + 8 * ((it - 1) & 3), ((it - 1) >> 2) & 1);
        if (kv) att_load_stage(a, it - 1 + NSTG);
        else load_stage(a.sKV + (it - 22) * STAGE, a.wfull + 8 * (it - 22), *a.tm, NC + it - 22);
      }
    }
  }
  __syncwarp();
}
constexpr uint32_t KV_STG = 2 * KVB / 16, KV_VOFF = KVB / 16, KV_HALF = 80 * 128 / 16;
template<bool SAFE>
__device__ __forceinline__ void att_pass(const AttCtx& a, uint32_t dQ, float (&O)[32], float& l0, float& l1) {
  float S[40];
  uint32_t P[20];
  float m0 = -INFINITY, m1 = -INFINITY;
  l0 = 0.f; l1 = 0.f;
#pragma unroll
  for (int i = 0; i < 32; i++) O[i] = 0.f;
  const uint32_t dKV = dlo(a.sKV, 16);
  if (SAFE) {
#pragma unroll 1
    for (int j = 0; j < 2 * NKV; j++) {
      const int it = j >> 1, s = it & 3;
      const uint32_t kb = dKV + kv_slot(it) * KV_STG + (j & 1) * KV_HALF;
      mbar_wait(a.full + 8 * s, (it >> 2) & 1);
      wg_fence(); att_qk(S, dQ, kb); wg_commit(); wg_wait<0>();
      att_softmax<true>(S, P, O, m0, m1, l0, l1);
      mbar_wait(a.full + 8 * (NSTG + s), (it >> 2) & 1);
      wg_fence(); att_pv(O, P, kb + KV_VOFF); wg_commit(); wg_wait<0>();
      if (j & 1) att_refill<true>(a, it);
    }
  } else {
    mbar_wait(a.full, a.dry);
    wg_fence(); att_qk(S, dQ, dKV + 3 * KV_STG); wg_commit(); wg_wait<0>();
    att_softmax<false>(S, P, O, m0, m1, l0, l1);
    mbar_wait(a.full + 8 * NSTG, a.dry);
    wg_fence(); att_pv(O, P, dKV + 3 * KV_STG + KV_VOFF); att_qk(S, dQ, dKV + 3 * KV_STG + KV_HALF); wg_commit(); wg_wait<0>();
#pragma unroll 1
    for (int it = a.dry ? NKV - 2 : 0; it < NKV - 1; it++) {
      const int sn = (it + 1) & 3;
      const uint32_t kb = dKV + kv_slot(it) * KV_STG, kn = dKV + kv_slot(it + 1) * KV_STG, par = (((it + 1) >> 2) | a.dry) & 1;
      att_softmax<false>(S, P, O, m0, m1, l0, l1);
      mbar_wait(a.full + 8 * sn, par);
      wg_fence(); att_pv(O, P, kb + KV_VOFF + KV_HALF); att_qk(S, dQ, kn); wg_commit(); wg_wait<0>();
      att_refill<false>(a, it);
      att_softmax<false>(S, P, O, m0, m1, l0, l1);
      mbar_wait(a.full + 8 * (NSTG + sn), par);
      wg_fence(); att_pv(O, P, kn + KV_VOFF); att_qk(S, dQ, kn + KV_HALF); wg_commit(); wg_wait<0>();
    }
    att_softmax<false>(S, P, O, m0, m1, l0, l1);
    wg_fence(); att_pv(O, P, dKV + 3 * KV_STG + KV_VOFF + KV_HALF); wg_commit(); wg_wait<0>();
  }
  l0 += __shfl_xor_sync(0xffffffff, l0, 1); l1 += __shfl_xor_sync(0xffffffff, l1, 1);
  l0 += __shfl_xor_sync(0xffffffff, l0, 2); l1 += __shfl_xor_sync(0xffffffff, l1, 2);
}

struct Wptrs { const void* p[8]; uint32_t bytes[8]; };

constexpr uint32_t B_FULL = 0, B_EMPTY = 8 * RING, B_X = 16 * RING, B_ADONE = B_X + 8, B_Q = B_X + 16, B_EP = B_X + 24, B_ATT = B_X + 32;

__global__ void __launch_bounds__(512, 1) conformer_kernel(const __grid_constant__ Maps tm, const __grid_constant__ Wptrs wp, const uint4* __restrict__ dw) {
  extern __shared__ uint8_t smem_raw[];
  const uint32_t base = (smem_u32(smem_raw) + 1023) & ~1023u, misc = base + OFF_MISC;
  const uint32_t dry = blockIdx.x >= 128;
  const int tile = dry ? 0 : blockIdx.x;
  const bool has_tile = dry ? blockIdx.x == 128 : tile < NTILE;
  const int wg = __shfl_sync(0xffffffff, (int)(threadIdx.x >> 7), 0);
  AttCtx a;
  a.sKV = base + OFF_W; a.full = misc + B_ATT; a.empty = a.full + 16 * NSTG; a.tm = &tm;
  a.h = (blockIdx.x >> 4) & 3; a.b = (blockIdx.x >> 6) & 1; a.wg = wg; a.dry = dry; a.wfull = has_tile ? misc + B_FULL : 0;
  const int qt = blockIdx.x & 15;

  if (threadIdx.x == 256) {
    mbar_init(misc + B_X, 1);
    for (int i = 0; i < RING; i++) { mbar_init(misc + B_FULL + 8 * i, 1); mbar_init(misc + B_EMPTY + 8 * i, 1); }
    asm volatile("fence.mbarrier_init.release.cluster;" ::: "memory");
    if (has_tile && !dry) {
      mbar_expect_tx(misc + B_X, 32768);
      tma_load_3d(base + OFF_X, &tm.X, misc + B_X, 0, tile * 64, 0);
#pragma unroll 1
      for (int i = 0; i < RING; i++) load_stage(base + OFF_W + i * STAGE, misc + B_FULL + 8 * i, tm, i);
    }
  } else if (threadIdx.x == 288) {
    mbar_init(misc + B_ADONE, 2);
    mbar_init(misc + B_Q, 1);
    mbar_init(misc + B_EP, 1);
    att_init_bars(a);
    asm volatile("fence.mbarrier_init.release.cluster;" ::: "memory");
  } else if (threadIdx.x >= 320 && threadIdx.x < 333) {
    prefetch_tmap(&tm.X + (threadIdx.x - 320));
  }
  __syncthreads();
  auto get_epoch = [&]() {
    uint32_t e;
    mbar_wait(misc + B_EP, 0);
    asm volatile("ld.shared.u32 %0, [%1];" : "=r"(e) : "r"(misc + 248) : "memory");
    return e;
  };

  if (wg >= 2) {
    asm volatile("setmaxnreg.dec.sync.aligned.u32 24;");
    const uint32_t full = misc + B_FULL;
    if (threadIdx.x == 320) {
      const uint32_t e = atomicAdd(&g_start, 1) / NCTA;
      asm volatile("st.shared.u32 [%0], %1;" :: "r"(misc + 248), "r"(e + 1) : "memory");
      mbar_arrive(misc + B_EP);
    }
    if (dry) {
    } else if (threadIdx.x == 256) {
      if (has_tile) {
        produce(base + OFF_W, full, tm, RING, NA);
        mbar_wait(full + 8 * RING + 8 * 4, 1);
        mbar_arrive(full + 8 * 4); mbar_arrive(full + 8 * RING + 8 * 4);
        mbar_wait(misc + B_ADONE, 0);
      }
      cnt_wait(g_cnt1 + a.b * 64, 126 * get_epoch());
      mbar_expect_tx(misc + B_Q, 32768);
      tma_load_3d(base, &tm.Q, misc + B_Q, a.h * 64, qt * 256, a.b);
      att_load(a, 0, 0);
      mbar_wait(misc + B_Q, 0);
#pragma unroll 1
      for (int i = 1; i < NSTG; i++) att_load(a, i, 0);
    } else if ((threadIdx.x >> 5) == 12) {
      if (has_tile) bar_sync(9, 288);
      if (threadIdx.x == 384) {
        cnt_wait(g_cnt1 + a.b * 64 + 32, 126 * get_epoch());
        att_load(a, 0, 1);
        mbar_wait(a.full + 8 * NSTG, 0);
#pragma unroll 1
        for (int i = 1; i < NSTG; i++) att_load(a, i, 1);
      }
    } else if (has_tile && threadIdx.x >= 288 && threadIdx.x < 296) {
      const int w = threadIdx.x - 288;
      mbar_wait(misc + B_X, 0);
      const uint32_t bytes = wp.bytes[w], per = ((bytes / NTILE) + 127) & ~127u, off = per * tile;
      if (off < bytes) l2_prefetch((const uint8_t*)wp.p[w] + off, min(per, bytes - off));
    } else if (has_tile && threadIdx.x >= 416) {
      mbar_wait(full, 0);
      const int t = threadIdx.x - 416;
#pragma unroll 2
      for (int i = t; i < 2048; i += 96) g_att[tile * 2048 + i] = make_uint4(~0u, ~0u, ~0u, ~0u);
      g_halo[tile * 128 + t] = make_uint4(~0u, ~0u, ~0u, ~0u);
      if (t < 32) g_halo[tile * 128 + 96 + t] = make_uint4(~0u, ~0u, ~0u, ~0u);
    }
    __syncwarp();
    bar_sync(5 + wg, 384);
    asm volatile("setmaxnreg.inc.sync.aligned.u32 128;");
  } else {
    asm volatile("setmaxnreg.inc.sync.aligned.u32 232;");
    if (has_tile) {
      const Ctx c = make_ctx(base, dry);
      if (c.wg == 1) turn_end(c);
      float own[64];
      float a0, b0, a1, b1;
      PROF_MARK(0, 0);
      mbar_wait(misc + B_X, dry);
      PROF_MARK(0, 1);
      load_half(c, c.sX, own);
      ln_stats(c, own, 0.5f, a0, b0, a1, b1);
      store_half(c, c.sA, own, a0, b0, a1, b1);
      fence_async_smem();
      bar_sync(1, 256);
      PROF_MARK(0, 2);
      ff_block(c, 0, own);
      PROF_MARK(0, 3);
      ln_stats(c, own, 1.f, a0, b0, a1, b1);
      store_half(c, c.sA, own, a0, b0, a1, b1);
      fence_async_smem();
      bar_sync(1, 256);
      PROF_MARK(0, 4);
#pragma unroll 1
      for (int cc = dry ? 2 : 0; cc < 3; cc++) {
        float acc[64];
        const int j = 2 * cc + c.wg;
        gemm256<1>(c, acc, 32 + 2 * j);
        const float sc = (cc == 0) ? 0.125f * 1.4426950408889634f : 1.f;
        if (cc == 2 && !dry) bar_arrive(9, 288);
        if (c.tid == 0 && !dry) {
          if (cc == 2) {
            mbar_arrive(misc + B_ADONE);
            bulk_wait_all();
            if (tile <= 62) cnt_signal(g_cnt1);
            if (tile >= 62) cnt_signal(g_cnt1 + 64);
          } else bulk_wait_read();
        }
        bar_sync(3 + c.wg, 128);
        store_half(c, c.sX, acc, sc, 0.f, sc, 0.f);
        fence_async_smem();
        bar_sync(3 + c.wg, 128);
        if (c.tid == 0 && !dry) { tma_store_3d(&tm.QKVst, c.sX + c.wg * 16384, 0, tile * 64, 2 * j); bulk_commit(); }
      }
      PROF_MARK(0, 5);
      if (c.tid == 0) bulk_wait_read();
      bar_sync(3 + c.wg, 128);
      store_half_raw(c, c.sX, own);
    }
    else bar_sync(3 + wg, 128);
    asm volatile("setmaxnreg.dec.sync.aligned.u32 128;");
    bar_arrive(7, 384); bar_arrive(8, 384);
    if (has_tile && !dry && (threadIdx.x & 127) == 0) {
      bulk_wait_all();
      if (tile <= 62) cnt_signal(g_cnt1 + 32);
      if (tile >= 62) cnt_signal(g_cnt1 + 96);
    }
    __syncwarp();
    PROF_MARK(0, 6);
  }

  if (blockIdx.x == 128) return;
  if (blockIdx.x != 130) {
    const int lane = threadIdx.x & 31, wq = (threadIdx.x >> 5) & 3;
    const uint32_t dQ = dlo(base + wg * 8192, 16);
    float O[32], l0, l1;
    PROF_MARK(1, 1);
    mbar_wait(misc + B_Q, dry);
    PROF_MARK(1, 2);
    att_pass<false>(a, dQ, O, l0, l1);
    PROF_MARK(1, 3);
    float z = 0.f;
#pragma unroll
    for (int i = 0; i < 32; i++) z = fmaf(O[i], 0.f, z);
    const bool ok = (l0 >= 0x1p-80f) && (l0 <= 0x1p100f) && (l1 >= 0x1p-80f) && (l1 <= 0x1p100f) && (z == 0.f);
    const bool warp_bad = !__all_sync(0xffffffff, ok) && !dry;
    auto store_out = [&]() {
      const float i0 = 1.f / l0, i1 = 1.f / l1;
      const int row = qt * 256 + wg * 64 + wq * 16;
      if (row < T_ && !dry) {
        const int slab = (a.b * T_ + row) / 16;
        uint4* op = g_att + (slab * 16 + a.h * 4) * 32 + lane;
#pragma unroll
        for (int j = 0; j < 4; j++)
          asm volatile("st.relaxed.gpu.global.v4.u32 [%0], {%1,%2,%3,%4};" :: "l"(op + j * 32),
                       "r"(pack_bf16(O[8 * j] * i0, O[8 * j + 1] * i0)), "r"(pack_bf16(O[8 * j + 2] * i1, O[8 * j + 3] * i1)),
                       "r"(pack_bf16(O[8 * j + 4] * i0, O[8 * j + 5] * i0)), "r"(pack_bf16(O[8 * j + 6] * i1, O[8 * j + 7] * i1)) : "memory");
        __syncwarp();
        if (lane == 0) cnt_signal(g_cnt2 + slab * 32);
      }
      PROF_MARK(1, 4);
    };
    if (!warp_bad) store_out();
    if (__syncthreads_or(warp_bad)) {
      if (threadIdx.x == 0) {
        if (has_tile) { mbar_wait(misc + B_FULL, 1); mbar_wait(misc + B_FULL + 8, 1); }
        for (int i = 0; i < 3 * NSTG; i++) mbar_inval(a.full + 8 * i);
        att_init_bars(a);
        asm volatile("fence.mbarrier_init.release.cluster;" ::: "memory");
        fence_async_smem();
#pragma unroll 1
        for (int i = 0; i < NSTG; i++) att_load_stage(a, i);
      }
      __syncthreads();
      att_pass<true>(a, dQ, O, l0, l1);
      if (warp_bad) store_out();
      __syncthreads();
      if (has_tile) {
        if (threadIdx.x == 32) {
          load_stage(base + OFF_W, misc + B_X, tm, NC);
          load_stage(base + OFF_W + STAGE, misc + B_Q, tm, NC + 1);
        }
        mbar_wait(misc + B_X, 1); mbar_wait(misc + B_Q, 1);
      }
    }
    PROF_MARK(1, 5);
  } else {
    __syncthreads();
  }
  if (dry ? blockIdx.x != 130 : !has_tile) return;

  if (wg >= 2) {
    asm volatile("setmaxnreg.dec.sync.aligned.u32 24;");
    if (threadIdx.x == 256 && !dry) produce(base + OFF_W, misc + B_FULL, tm, NC + 2, NC + 48);
  } else {
    asm volatile("setmaxnreg.inc.sync.aligned.u32 232;");
    const Ctx c = make_ctx(base, dry);
    if (dry && c.wg == 1) turn_end(c);
    float own[64];
    float a0, b0, a1, b1;
    PROF_MARK(2, 0);
    {
      uint4 af[16];
      const int slab = tile * 4 + (c.tid >> 5);
      const uint4* ap = g_att + slab * 512 + c.lane;
      if (c.wg == 1) load_half(c, c.sX, own);
      for (uint32_t n = 0; n < (1u << 18); n++) {
        bool any = false;
#pragma unroll
        for (int i = 0; i < 16; i++)
          asm volatile("ld.relaxed.gpu.global.v4.u32 {%0,%1,%2,%3}, [%4];" : "=r"(af[i].x), "=r"(af[i].y), "=r"(af[i].z), "=r"(af[i].w) : "l"(ap + i * 32) : "memory");
        if (n == 0 && c.wg == 0) load_half(c, c.sX, own);
#pragma unroll
        for (int i = 0; i < 16; i++) any |= max(max(af[i].x, af[i].y), max(af[i].z, af[i].w)) == ~0u;
        if (!__any_sync(0xffffffff, any) || dry) break;
        if (c.lane == 0) cnt_wait(g_cnt2 + slab * 32, 4 * get_epoch());
        __syncwarp();
      }
      PROF_MARK(2, 2);
      const int n = NC + 2 * c.wg;
      uint32_t b = stage_wait(c, n) + ((16384 >> 4) << 16);
      turn_begin(c);
      wg_fence();
#pragma unroll
      for (int kk = 0; kk < 8; kk++) wg_rs_n128_tb1<1>(own, af[kk].x, af[kk].y, af[kk].z, af[kk].w, b + kk * 128);
      wg_commit();
      b = stage_wait(c, n + 1) + ((16384 >> 4) << 16);
      wg_fence();
#pragma unroll
      for (int kk = 0; kk < 8; kk++) wg_rs_n128_tb1<1>(own, af[8 + kk].x, af[8 + kk].y, af[8 + kk].z, af[8 + kk].w, b + kk * 128);
      wg_commit();
      turn_end(c);
      wg_wait<1>(); stage_release(c, n);
      wg_wait<0>(); stage_release(c, n + 1);
    }
    PROF_MARK(2, 3);
    ln_stats(c, own, 0.5f, a0, b0, a1, b1);
    store_half(c, c.sA, own, a0, b0, a1, b1);
    fence_async_smem();
    bar_sync(1, 256);
    PROF_MARK(2, 4);
    uint4 dwr[5];
#pragma unroll
    for (int i = 0; i < 5; i++) dwr[i] = __ldg(dw + i * 32 + c.wg * 16 + (c.lane & 15));
    const bool top = c.tid < 8, pub = (top || c.tid >= 120) && !dry;
    uint32_t* halo_out = (uint32_t*)g_halo + (tile * 4 + (top ? (c.tid >> 2) : ((c.tid >> 2) - 28))) * 128 + c.wg * 64 + (c.lane & 3);
#pragma unroll 1
    for (int q = dry; q < 2; q++) {
      float ab[64];
      gemm256<1>(c, ab, NC + 4 + 4 * q + 2 * c.wg);
#pragma unroll
      for (int j = 0; j < 4; j++) {
        float g[8];
#pragma unroll
        for (int i = 0; i < 8; i++) g[i] = fmaf(ab[8 * j + i], tanh_fast(ab[32 + 8 * j + i]), ab[8 * j + i]);
        const uint32_t p0 = pack_bf16(g[0], g[1]), p1 = pack_bf16(g[2], g[3]), p2 = pack_bf16(g[4], g[5]), p3 = pack_bf16(g[6], g[7]);
        if (pub) {
          uint32_t* hp = halo_out + q * 32 + j * 8;
          asm volatile("st.relaxed.gpu.global.u32 [%0], %1;" :: "l"(hp), "r"(top ? p0 : p1) : "memory");
          asm volatile("st.relaxed.gpu.global.u32 [%0], %1;" :: "l"(hp + 4), "r"(top ? p2 : p3) : "memory");
        }
        stsm_x4(c.sX + (2 * c.wg + q) * 8192 + c.frag + (((j * 2 + c.hi) ^ c.rsw) << 4), p0, p1, p2, p3);
      }
    }
    auto pw2_half = [&](int kh) {
      const uint32_t b = stage_wait(c, NC + 12 + 2 * kh + c.wg);
      turn_begin(c);
      wg_fence(); piece_ss<0>(own, dlo(c.sX, 16) + kh * 1024, b); wg_commit();
      turn_end(c);
    };
    if (c.wg == 1) pw2_half(0);
    bar_sync(3 + c.wg, 128);
    PROF_MARK(2, 5);
    {
      const int wi = c.tid >> 4;
      const uint32_t col = (2 * c.wg + ((c.lane >> 3) & 1)) * 8192, ch = c.lane & 7;
      uint4 r[12];
      const int R0 = tile * 64 + wi * 8;
      const bool first = (R0 % T_) == 0, last = ((R0 + 8) % T_) == 0;
      const bool far = ((wi == 0 && !first) || (wi == 7 && !last)) && !dry;
      const uint4* sp = g_halo + (wi == 0 ? (tile - 1) * 4 + 2 : (tile + 1) * 4) * 32 + c.wg * 16 + (c.lane & 15);
      uint4 h0 = make_uint4(0, 0, 0, 0), h1 = h0;
      auto ld_halo = [&]() {
        asm volatile("ld.relaxed.gpu.global.v4.u32 {%0,%1,%2,%3}, [%4];" : "=r"(h0.x), "=r"(h0.y), "=r"(h0.z), "=r"(h0.w) : "l"(sp) : "memory");
        asm volatile("ld.relaxed.gpu.global.v4.u32 {%0,%1,%2,%3}, [%4];" : "=r"(h1.x), "=r"(h1.y), "=r"(h1.z), "=r"(h1.w) : "l"(sp + 32) : "memory");
      };
      if (far) ld_halo();
#pragma unroll
      for (int i = 0; i < 12; i++) {
        const int row = (wi * 8 - 2 + i) & 63;
        r[i] = lds128(c.sX + col + row * 128 + ((ch ^ (row & 7)) << 4));
      }
      bar_sync(3 + c.wg, 128);
      uint32_t w[5][4];
#pragma unroll
      for (int k = 0; k < 5; k++) {
        w[k][0] = bmul2(dwr[k].x, 0x3F003F00u); w[k][1] = bmul2(dwr[k].y, 0x3F003F00u);
        w[k][2] = bmul2(dwr[k].z, 0x3F003F00u); w[k][3] = bmul2(dwr[k].w, 0x3F003F00u);
      }
      auto conv_row = [&](int i) {
        uint32_t o[4];
#pragma unroll
        for (int q = 0; q < 4; q++) {
          uint32_t acc = bmul2(q == 0 ? r[i].x : q == 1 ? r[i].y : q == 2 ? r[i].z : r[i].w, w[0][q]);
#pragma unroll
          for (int k = 1; k < 5; k++) acc = bfma2(q == 0 ? r[i + k].x : q == 1 ? r[i + k].y : q == 2 ? r[i + k].z : r[i + k].w, w[k][q], acc);
          o[q] = pack_bf16(silu_half(bf_lo(acc)), silu_half(bf_hi(acc)));
        }
        sts128(c.sX + col + (wi * 8 + i) * 128 + ((ch ^ i) << 4), make_uint4(o[0], o[1], o[2], o[3]));
      };
      conv_row(2); conv_row(3); conv_row(4); conv_row(5);
      if (far) {
        for (uint32_t n = 0; n < (1u << 18); n++) {
          const uint32_t mx = max(max(max(h0.x, h0.y), max(h0.z, h0.w)), max(max(h1.x, h1.y), max(h1.z, h1.w)));
          if (mx != ~0u) break;
          ld_halo();
        }
      }
      __syncwarp();
      if (first || (far && wi == 0)) { r[0] = h0; r[1] = h1; }
      if (last || (far && wi == 7)) { r[10] = h0; r[11] = h1; }
      conv_row(0); conv_row(1); conv_row(6); conv_row(7);
    }
    fence_async_smem();
    if (c.wg == 0) { bar_sync(3, 128); pw2_half(0); }
    bar_sync(1, 256);
    PROF_MARK(2, 6);
    pw2_half(1);
    wg_wait<1>(); stage_release(c, NC + 12 + c.wg);
    wg_wait<0>(); stage_release(c, NC + 14 + c.wg);
    PROF_MARK(2, 7);
    ln_stats(c, own, 0.5f, a0, b0, a1, b1);
    store_half(c, c.sA, own, a0, b0, a1, b1);
    fence_async_smem();
    bar_sync(1, 256);
    PROF_MARK(2, 8);
    ff_block(c, NC + 16, own);
    PROF_MARK(2, 9);
    ln_stats(c, own, 1.f, a0, b0, a1, b1);
    store_half(c, c.sX, own, a0, b0, a1, b1);
    fence_async_smem();
    bar_sync(3 + c.wg, 128);
    if (c.tid == 0 && !dry) { tma_store_3d(&tm.Out, c.sX + c.wg * 16384, 0, tile * 64, 2 * c.wg); bulk_commit(); PROF_MARK(2, 10); bulk_wait_all(); }
    PROF_MARK(2, 11);
  }
}

typedef CUresult (*EncodeFn)(CUtensorMap*, CUtensorMapDataType, cuuint32_t, void*, const cuuint64_t*, const cuuint64_t*, const cuuint32_t*,
                             const cuuint32_t*, CUtensorMapInterleave, CUtensorMapSwizzle, CUtensorMapL2promotion, CUtensorMapFloatOOBfill);

CUtensorMap make_map(EncodeFn enc, const void* p, uint64_t d0, uint64_t d1, uint64_t d2, uint64_t s1, uint64_t s2, uint32_t b1, uint32_t b2) {
  CUtensorMap tm;
  cuuint64_t dims[3] = {d0, d1, d2};
  cuuint64_t strides[2] = {s1, s2};
  cuuint32_t box[3] = {64, b1, b2};
  cuuint32_t es[3] = {1, 1, 1};
  enc(&tm, CU_TENSOR_MAP_DATA_TYPE_BFLOAT16, 3, const_cast<void*>(p), dims, strides, box, es, CU_TENSOR_MAP_INTERLEAVE_NONE,
      CU_TENSOR_MAP_SWIZZLE_128B, CU_TENSOR_MAP_L2_PROMOTION_L2_256B, CU_TENSOR_MAP_FLOAT_OOB_FILL_NONE);
  return tm;
}
CUtensorMap blk_map(EncodeFn enc, const void* p, uint64_t rows, uint64_t cols, uint32_t boxrows, uint32_t boxblks) {
  return make_map(enc, p, 64, rows, cols / 64, cols * 2, 128, boxrows, boxblks);
}
CUtensorMap seq_map(EncodeFn enc, const void* p, uint64_t cols, uint32_t boxrows) {
  return make_map(enc, p, cols, T_, 2, cols * 2, cols * 2 * T_, boxrows, 1);
}

}

extern "C" void kernel_launch(void* const* d_in, const int* in_sizes, int n_in, void* d_out, int out_size) {
  (void)in_sizes; (void)n_in; (void)out_size;
  const void *x = d_in[0], *w1a = d_in[1], *w1b = d_in[2], *wqkv = d_in[3], *wo = d_in[4], *pw1 = d_in[5], *dw = d_in[6], *pw2 = d_in[7],
             *w2a = d_in[8], *w2b = d_in[9];
  void* fn = nullptr;
  cudaDriverEntryPointQueryResult qr;
  cudaGetDriverEntryPoint("cuTensorMapEncodeTiled", &fn, cudaEnableDefault, &qr);
  EncodeFn enc = (EncodeFn)fn;
  void* qkv;
  cudaGetSymbolAddress(&qkv, g_qkv);
  cudaFuncSetAttribute(conformer_kernel, cudaFuncAttributeMaxDynamicSharedMemorySize, SMEM_BYTES);

  Wptrs wp;
  const void* ws[8] = {w1a, w1b, wqkv, wo, pw1, pw2, w2a, w2b};
  const uint32_t wb[8] = {524288, 524288, 393216, 131072, 262144, 131072, 524288, 524288};
  for (int i = 0; i < 8; i++) { wp.p[i] = ws[i]; wp.bytes[i] = wb[i]; }
  Maps tm;
  tm.X = blk_map(enc, x, ROWS, 256, 64, 4);
  tm.W1a = blk_map(enc, w1a, 256, 1024, 256, 1);
  tm.W1b = blk_map(enc, w1b, 1024, 256, 64, 4);
  tm.Wqkv = blk_map(enc, wqkv, 256, 768, 128, 2);
  tm.QKVst = blk_map(enc, qkv, ROWS, 768, 64, 2);
  tm.Q = seq_map(enc, qkv, 768, 256);
  tm.KV = seq_map(enc, qkv, 768, 160);
  tm.Wo = blk_map(enc, wo, 256, 256, 128, 2);
  tm.Pw1 = make_map(enc, pw1, 256, 256, 2, 1024, 512, 128, 2);
  tm.Pw2 = blk_map(enc, pw2, 256, 256, 128, 2);
  tm.W2a = blk_map(enc, w2a, 256, 1024, 256, 1);
  tm.W2b = blk_map(enc, w2b, 1024, 256, 64, 4);
  tm.Out = blk_map(enc, d_out, ROWS, 256, 64, 2);
  conformer_kernel<<<NCTA, 512, SMEM_BYTES, cudaStreamPerThread>>>(tm, wp, (const uint4*)dw);
}
```

```cpp
#include <cuda_runtime.h>
#include <cuda_bf16.h>
#include <cuda.h>
#include <stdint.h>

namespace {

constexpr int T_ = 4000;
constexpr int ROWS = 8000;
constexpr int NTILE = 125;
#define NCTA_ 131
constexpr int NCTA = NCTA_;

__device__ __nv_bfloat16 g_qkv[ROWS * 768];
__device__ uint4 g_att[(ROWS / 16) * 16 * 32];
__device__ uint4 g_halo[NTILE * 4 * 32];
__device__ uint32_t g_start;
__device__ uint32_t g_cnt1[4 * 32];
__device__ uint32_t g_cnt2[ROWS / 16 * 32];

#define PROF_MARK(k, i) do {} while (0)
#define PROF_STG(n, i) do {} while (0)

__device__ __forceinline__ uint32_t smem_u32(const void* p) { return (uint32_t)__cvta_generic_to_shared(p); }
__device__ __forceinline__ void mbar_init(uint32_t bar, uint32_t cnt) { asm volatile("mbarrier.init.shared::cta.b64 [%0], %1;" :: "r"(bar), "r"(cnt) : "memory"); }
__device__ __forceinline__ void mbar_inval(uint32_t bar) { asm volatile("mbarrier.inval.shared::cta.b64 [%0];" :: "r"(bar) : "memory"); }
__device__ __forceinline__ void mbar_expect_tx(uint32_t bar, uint32_t bytes) { asm volatile("mbarrier.arrive.expect_tx.shared::cta.b64 _, [%0], %1;" :: "r"(bar), "r"(bytes) : "memory"); }
__device__ __forceinline__ void mbar_arrive(uint32_t bar) { asm volatile("mbarrier.arrive.shared::cta.b64 _, [%0];" :: "r"(bar) : "memory"); }
__device__ __forceinline__ void mbar_wait(uint32_t bar, uint32_t parity) {
  asm volatile("{\n.reg .pred p;\n.reg .u32 n;\n"
               "mbarrier.try_wait.parity.shared::cta.b64 p, [%0], %1;\n@p bra DONE_%=;\nmov.u32 n, 0;\n"
               "LOOP_%=:\nmbarrier.try_wait.parity.shared::cta.b64 p, [%0], %1;\n@p bra DONE_%=;\n"
               "add.u32 n, n, 1;\nsetp.lt.u32 p, n, 262144;\n@p bra LOOP_%=;\ntrap;\nDONE_%=:\n}\n" :: "r"(bar), "r"(parity) : "memory");
}
__device__ __forceinline__ void cnt_wait(const uint32_t* p, uint32_t target) {
  asm volatile("{\n.reg .pred p;\n.reg .u32 n, v;\nmov.u32 n, 0;\n"
               "LOOP_%=:\nld.relaxed.gpu.global.u32 v, [%0];\nsub.u32 v, v, %1;\nsetp.ge.s32 p, v, 0;\n@p bra DONE_%=;\n"
               "nanosleep.u32 40;\nadd.u32 n, n, 1;\nsetp.lt.u32 p, n, 262144;\n@p bra LOOP_%=;\ntrap;\nDONE_%=:\n}\n" :: "l"(p), "r"(target) : "memory");
}
__device__ __forceinline__ void cnt_signal(uint32_t* p) {
  asm volatile("red.relaxed.gpu.global.add.u32 [%0], 1;" :: "l"(p) : "memory");
}
__device__ __forceinline__ void tma_load_3d(uint32_t dst, const CUtensorMap* tm, uint32_t bar, int c0, int c1, int c2) {
  asm volatile("cp.async.bulk.tensor.3d.shared::cluster.global.mbarrier::complete_tx::bytes [%0], [%1, {%3, %4, %5}], [%2];"
    :: "r"(dst), "l"(tm), "r"(bar), "r"(c0), "r"(c1), "r"(c2) : "memory");
}
__device__ __forceinline__ void tma_store_3d(const CUtensorMap* tm, uint32_t src, int c0, int c1, int c2) {
  asm volatile("cp.async.bulk.tensor.3d.global.shared::cta.bulk_group [%0, {%2, %3, %4}], [%1];" :: "l"(tm), "r"(src), "r"(c0), "r"(c1), "r"(c2) : "memory");
}
__device__ __forceinline__ void bulk_commit() { asm volatile("cp.async.bulk.commit_group;" ::: "memory"); }
__device__ __forceinline__ void bulk_wait_read() { asm volatile("cp.async.bulk.wait_group.read 0;" ::: "memory"); }
__device__ __forceinline__ void bulk_wait_all() { asm volatile("cp.async.bulk.wait_group 0;" ::: "memory"); }
__device__ __forceinline__ void l2_prefetch(const void* p, uint32_t bytes) { asm volatile("cp.async.bulk.prefetch.L2.global [%0], %1;" :: "l"(p), "r"(bytes) : "memory"); }
__device__ __forceinline__ void prefetch_tmap(const CUtensorMap* tm) { asm volatile("prefetch.tensormap [%0];" :: "l"(tm) : "memory"); }
__device__ __forceinline__ void fence_async_smem() { asm volatile("fence.proxy.async.shared::cta;" ::: "memory"); }
__device__ __forceinline__ void wg_fence() { asm volatile("wgmma.fence.sync.aligned;" ::: "memory"); }
__device__ __forceinline__ void wg_commit() { asm volatile("wgmma.commit_group.sync.aligned;" ::: "memory"); }
template<int N> __device__ __forceinline__ void wg_wait() { asm volatile("wgmma.wait_group.sync.aligned %0;" :: "n"(N) : "memory"); }
__device__ __forceinline__ void bar_sync(int id, int n) { asm volatile("bar.sync %0, %1;" :: "r"(id), "r"(n) : "memory"); }
__device__ __forceinline__ void bar_arrive(int id, int n) { asm volatile("bar.arrive %0, %1;" :: "r"(id), "r"(n) : "memory"); }
__device__ __forceinline__ float ex2(float x) { float y; asm("ex2.approx.ftz.f32 %0, %1;" : "=f"(y) : "f"(x)); return y; }
__device__ __forceinline__ float tanh_fast(float x) { float y; asm("tanh.approx.f32 %0, %1;" : "=f"(y) : "f"(x)); return y; }
__device__ __forceinline__ uint32_t pack_bf16(float lo, float hi) { uint32_t r; asm("cvt.rn.bf16x2.f32 %0, %1, %2;" : "=r"(r) : "f"(hi), "f"(lo)); return r; }
__device__ __forceinline__ uint32_t bmul2(uint32_t a, uint32_t b) { uint32_t d; asm("mul.rn.bf16x2 %0, %1, %2;" : "=r"(d) : "r"(a), "r"(b)); return d; }
__device__ __forceinline__ uint32_t bfma2(uint32_t a, uint32_t b, uint32_t c) { uint32_t d; asm("fma.rn.bf16x2 %0, %1, %2, %3;" : "=r"(d) : "r"(a), "r"(b), "r"(c)); return d; }
__device__ __forceinline__ float bf_lo(uint32_t u) { return __uint_as_float(u << 16); }
__device__ __forceinline__ float bf_hi(uint32_t u) { return __uint_as_float(u & 0xffff0000u); }
__device__ __forceinline__ void ldsm_x4(uint32_t addr, uint32_t& r0, uint32_t& r1, uint32_t& r2, uint32_t& r3) {
  asm volatile("ldmatrix.sync.aligned.m8n8.x4.shared.b16 {%0,%1,%2,%3}, [%4];" : "=r"(r0), "=r"(r1), "=r"(r2), "=r"(r3) : "r"(addr) : "memory");
}
__device__ __forceinline__ void stsm_x4(uint32_t addr, uint32_t r0, uint32_t r1, uint32_t r2, uint32_t r3) {
  asm volatile("stmatrix.sync.aligned.m8n8.x4.shared.b16 [%0], {%1,%2,%3,%4};" :: "r"(addr), "r"(r0), "r"(r1), "r"(r2), "r"(r3) : "memory");
}
__device__ __forceinline__ void sts128(uint32_t addr, uint4 v) { asm volatile("st.shared.v4.b32 [%0], {%1,%2,%3,%4};" :: "r"(addr), "r"(v.x), "r"(v.y), "r"(v.z), "r"(v.w) : "memory"); }
__device__ __forceinline__ uint4 lds128(uint32_t addr) { uint4 v; asm volatile("ld.shared.v4.b32 {%0,%1,%2,%3}, [%4];" : "=r"(v.x), "=r"(v.y), "=r"(v.z), "=r"(v.w) : "r"(addr) : "memory"); return v; }
__device__ __forceinline__ void sts64f(uint32_t addr, float a, float b) { asm volatile("st.shared.v2.f32 [%0], {%1,%2};" :: "r"(addr), "f"(a), "f"(b) : "memory"); }
__device__ __forceinline__ float2 lds64f(uint32_t addr) { float2 v; asm volatile("ld.shared.v2.f32 {%0,%1}, [%2];" : "=f"(v.x), "=f"(v.y) : "r"(addr) : "memory"); return v; }
__device__ __forceinline__ uint32_t dlo(uint32_t addr, uint32_t lbo) { return ((addr & 0x3FFFF) >> 4) | ((lbo >> 4) << 16); }

template<int SD> __device__ __forceinline__ void wg_ss_n128_tb1(float (&d)[64], uint32_t da, uint32_t db) {
  asm volatile("{\n.reg .b64 da, db;\nmov.b64 da, {%64, 0x40000040};\nmov.b64 db, {%65, 0x40000040};\n"
    "wgmma.mma_async.sync.aligned.m64n128k16.f32.bf16.bf16 {%0, %1, %2, %3, %4, %5, %6, %7, %8, %9, %10, %11, %12, %13, %14, %15, %16, %17, %18, %19, %20, %21, %22, %23, %24, %25, %26, %27, %28, %29, %30, %31, %32, %33, %34, %35, %36, %37, %38, %39, %40, %41, %42, %43, %44, %45, %46, %47, %48, %49, %50, %51, %52, %53, %54, %55, %56, %57, %58, %59, %60, %61, %62, %63}, da, db, %66, 1, 1, 0, 1;\n}\n"
    : "+f"(d[0]), "+f"(d[1]), "+f"(d[2]), "+f"(d[3]), "+f"(d[4]), "+f"(d[5]), "+f"(d[6]), "+f"(d[7]), "+f"(d[8]), "+f"(d[9]), "+f"(d[10]), "+f"(d[11]), "+f"(d[12]), "+f"(d[13]), "+f"(d[14]), "+f"(d[15]), "+f"(d[16]), "+f"(d[17]), "+f"(d[18]), "+f"(d[19]), "+f"(d[20]), "+f"(d[21]), "+f"(d[22]), "+f"(d[23]), "+f"(d[24]), "+f"(d[25]), "+f"(d[26]), "+f"(d[27]), "+f"(d[28]), "+f"(d[29]), "+f"(d[30]), "+f"(d[31]), "+f"(d[32]), "+f"(d[33]), "+f"(d[34]), "+f"(d[35]), "+f"(d[36]), "+f"(d[37]), "+f"(d[38]), "+f"(d[39]), "+f"(d[40]), "+f"(d[41]), "+f"(d[42]), "+f"(d[43]), "+f"(d[44]), "+f"(d[45]), "+f"(d[46]), "+f"(d[47]), "+f"(d[48]), "+f"(d[49]), "+f"(d[50]), "+f"(d[51]), "+f"(d[52]), "+f"(d[53]), "+f"(d[54]), "+f"(d[55]), "+f"(d[56]), "+f"(d[57]), "+f"(d[58]), "+f"(d[59]), "+f"(d[60]), "+f"(d[61]), "+f"(d[62]), "+f"(d[63])
    : "r"(da), "r"(db), "n"(SD));
}
template<int SD> __device__ __forceinline__ void wg_rs_n128_tb1(float (&d)[64], uint32_t a0, uint32_t a1, uint32_t a2, uint32_t a3, uint32_t db) {
  asm volatile("{\n.reg .b64 db;\nmov.b64 db, {%68, 0x40000040};\n"
    "wgmma.mma_async.sync.aligned.m64n128k16.f32.bf16.bf16 {%0, %1, %2, %3, %4, %5, %6, %7, %8, %9, %10, %11, %12, %13, %14, %15, %16, %17, %18, %19, %20, %21, %22, %23, %24, %25, %26, %27, %28, %29, %30, %31, %32, %33, %34, %35, %36, %37, %38, %39, %40, %41, %42, %43, %44, %45, %46, %47, %48, %49, %50, %51, %52, %53, %54, %55, %56, %57, %58, %59, %60, %61, %62, %63}, {%64, %65, %66, %67}, db, %69, 1, 1, 1;\n}\n"
    : "+f"(d[0]), "+f"(d[1]), "+f"(d[2]), "+f"(d[3]), "+f"(d[4]), "+f"(d[5]), "+f"(d[6]), "+f"(d[7]), "+f"(d[8]), "+f"(d[9]), "+f"(d[10]), "+f"(d[11]), "+f"(d[12]), "+f"(d[13]), "+f"(d[14]), "+f"(d[15]), "+f"(d[16]), "+f"(d[17]), "+f"(d[18]), "+f"(d[19]), "+f"(d[20]), "+f"(d[21]), "+f"(d[22]), "+f"(d[23]), "+f"(d[24]), "+f"(d[25]), "+f"(d[26]), "+f"(d[27]), "+f"(d[28]), "+f"(d[29]), "+f"(d[30]), "+f"(d[31]), "+f"(d[32]), "+f"(d[33]), "+f"(d[34]), "+f"(d[35]), "+f"(d[36]), "+f"(d[37]), "+f"(d[38]), "+f"(d[39]), "+f"(d[40]), "+f"(d[41]), "+f"(d[42]), "+f"(d[43]), "+f"(d[44]), "+f"(d[45]), "+f"(d[46]), "+f"(d[47]), "+f"(d[48]), "+f"(d[49]), "+f"(d[50]), "+f"(d[51]), "+f"(d[52]), "+f"(d[53]), "+f"(d[54]), "+f"(d[55]), "+f"(d[56]), "+f"(d[57]), "+f"(d[58]), "+f"(d[59]), "+f"(d[60]), "+f"(d[61]), "+f"(d[62]), "+f"(d[63])
    : "r"(a0), "r"(a1), "r"(a2), "r"(a3), "r"(db), "n"(SD));
}
template<int SD> __device__ __forceinline__ void wg_ss_n64_tb1(float (&d)[32], uint32_t da, uint32_t db) {
  asm volatile("{\n.reg .b64 da, db;\nmov.b64 da, {%32, 0x40000040};\nmov.b64 db, {%33, 0x40000040};\n"
    "wgmma.mma_async.sync.aligned.m64n64k16.f32.bf16.bf16 {%0, %1, %2, %3, %4, %5, %6, %7, %8, %9, %10, %11, %12, %13, %14, %15, %16, %17, %18, %19, %20, %21, %22, %23, %24, %25, %26, %27, %28, %29, %30, %31}, da, db, %34, 1, 1, 0, 1;\n}\n"
    : "+f"(d[0]), "+f"(d[1]), "+f"(d[2]), "+f"(d[3]), "+f"(d[4]), "+f"(d[5]), "+f"(d[6]), "+f"(d[7]), "+f"(d[8]), "+f"(d[9]), "+f"(d[10]), "+f"(d[11]), "+f"(d[12]), "+f"(d[13]), "+f"(d[14]), "+f"(d[15]), "+f"(d[16]), "+f"(d[17]), "+f"(d[18]), "+f"(d[19]), "+f"(d[20]), "+f"(d[21]), "+f"(d[22]), "+f"(d[23]), "+f"(d[24]), "+f"(d[25]), "+f"(d[26]), "+f"(d[27]), "+f"(d[28]), "+f"(d[29]), "+f"(d[30]), "+f"(d[31])
    : "r"(da), "r"(db), "n"(SD));
}
template<int SD> __device__ __forceinline__ void wg_ss_n80_tb0(float (&d)[40], uint32_t da, uint32_t db) {
  asm volatile("{\n.reg .b64 da, db;\nmov.b64 da, {%40, 0x40000040};\nmov.b64 db, {%41, 0x40000040};\n"
    "wgmma.mma_async.sync.aligned.m64n80k16.f32.bf16.bf16 {%0, %1, %2, %3, %4, %5, %6, %7, %8, %9, %10, %11, %12, %13, %14, %15, %16, %17, %18, %19, %20, %21, %22, %23, %24, %25, %26, %27, %28, %29, %30, %31, %32, %33, %34, %35, %36, %37, %38, %39}, da, db, %42, 1, 1, 0, 0;\n}\n"
    : "+f"(d[0]), "+f"(d[1]), "+f"(d[2]), "+f"(d[3]), "+f"(d[4]), "+f"(d[5]), "+f"(d[6]), "+f"(d[7]), "+f"(d[8]), "+f"(d[9]), "+f"(d[10]), "+f"(d[11]), "+f"(d[12]), "+f"(d[13]), "+f"(d[14]), "+f"(d[15]), "+f"(d[16]), "+f"(d[17]), "+f"(d[18]), "+f"(d[19]), "+f"(d[20]), "+f"(d[21]), "+f"(d[22]), "+f"(d[23]), "+f"(d[24]), "+f"(d[25]), "+f"(d[26]), "+f"(d[27]), "+f"(d[28]), "+f"(d[29]), "+f"(d[30]), "+f"(d[31]), "+f"(d[32]), "+f"(d[33]), "+f"(d[34]), "+f"(d[35]), "+f"(d[36]), "+f"(d[37]), "+f"(d[38]), "+f"(d[39])
    : "r"(da), "r"(db), "n"(SD));
}
template<int SD> __device__ __forceinline__ void wg_rs_n64_tb1(float (&d)[32], uint32_t a0, uint32_t a1, uint32_t a2, uint32_t a3, uint32_t db) {
  asm volatile("{\n.reg .b64 db;\nmov.b64 db, {%36, 0x40000040};\n"
    "wgmma.mma_async.sync.aligned.m64n64k16.f32.bf16.bf16 {%0, %1, %2, %3, %4, %5, %6, %7, %8, %9, %10, %11, %12, %13, %14, %15, %16, %17, %18, %19, %20, %21, %22, %23, %24, %25, %26, %27, %28, %29, %30, %31}, {%32, %33, %34, %35}, db, %37, 1, 1, 1;\n}\n"
    : "+f"(d[0]), "+f"(d[1]), "+f"(d[2]), "+f"(d[3]), "+f"(d[4]), "+f"(d[5]), "+f"(d[6]), "+f"(d[7]), "+f"(d[8]), "+f"(d[9]), "+f"(d[10]), "+f"(d[11]), "+f"(d[12]), "+f"(d[13]), "+f"(d[14]), "+f"(d[15]), "+f"(d[16]), "+f"(d[17]), "+f"(d[18]), "+f"(d[19]), "+f"(d[20]), "+f"(d[21]), "+f"(d[22]), "+f"(d[23]), "+f"(d[24]), "+f"(d[25]), "+f"(d[26]), "+f"(d[27]), "+f"(d[28]), "+f"(d[29]), "+f"(d[30]), "+f"(d[31])
    : "r"(a0), "r"(a1), "r"(a2), "r"(a3), "r"(db), "n"(SD));
}

constexpr int RING = 5;
constexpr uint32_t STAGE = 32768;
constexpr uint32_t OFF_X = 32768, OFF_W = 65536, OFF_MISC = OFF_W + RING * STAGE;
constexpr int SMEM_BYTES = OFF_MISC + 256 + 1024 + 1024;

struct Ctx {
  uint32_t sA, sX, sW, full, empty, stats;
  uint32_t frag;
  uint32_t rsw;
  uint32_t hi;
  int wg, tid, lane;
  int pk;
  uint32_t dry;
};
__device__ __forceinline__ uint32_t stage_wait(const Ctx& c, int n) {
  const int q = n / RING, s = n - q * RING;
  if (c.tid == 0) PROF_STG(n + c.pk, 1);
  mbar_wait(c.full + 8 * s, (q | c.dry) & 1);
  if (c.tid == 0) PROF_STG(n + c.pk, 2);
  return dlo(c.sW + s * STAGE, 0);
}
__device__ __forceinline__ void stage_release(const Ctx& c, int n) {
  const int s = n % RING;
  if (c.tid == 0) { mbar_arrive(c.empty + 8 * s); PROF_STG(n + c.pk, 3); }
}
__device__ __forceinline__ void turn_begin(const Ctx& c) { bar_sync(5 + c.wg, 256); }
__device__ __forceinline__ void turn_end(const Ctx& c) { bar_arrive(5 + (c.wg ^ 1), 256); }
template<int FIRST> __device__ __forceinline__ void piece_ss(float (&acc)[64], uint32_t dA, uint32_t dB) {
  dB += (16384 >> 4) << 16;
  wg_ss_n128_tb1<FIRST ? 0 : 1>(acc, dA, dB);
#pragma unroll
  for (int kk = 1; kk < 8; kk++) wg_ss_n128_tb1<1>(acc, dA + (kk >> 2) * 512 + (kk & 3) * 2, dB + kk * 128);
}
__device__ __forceinline__ void ff_g1(float (&h)[32], uint32_t dA, uint32_t dB) {
  wg_ss_n64_tb1<0>(h, dA, dB);
#pragma unroll
  for (int kk = 1; kk < 16; kk++) wg_ss_n64_tb1<1>(h, dA + (kk >> 2) * 512 + (kk & 3) * 2, dB + kk * 128);
}
__device__ __forceinline__ void ff_g2(float (&acc)[64], const uint32_t (&P)[16], uint32_t dB, int half) {
  dB += ((8192 >> 4) << 16) + half * 1024;
#pragma unroll
  for (int kk = 0; kk < 4; kk++) wg_rs_n128_tb1<1>(acc, P[4 * kk], P[4 * kk + 1], P[4 * kk + 2], P[4 * kk + 3], dB + kk * 128);
}
struct NoHook { __device__ __forceinline__ void operator()() const {} };
template<int FIRST, class Hook = NoHook> __device__ __forceinline__ void gemm256(const Ctx& c, float (&acc)[64], int n, Hook hook = Hook()) {
  const uint32_t dA = dlo(c.sA, 16);
  uint32_t b = stage_wait(c, n);
  turn_begin(c);
  wg_fence(); piece_ss<FIRST>(acc, dA, b); wg_commit();
  b = stage_wait(c, n + 1);
  wg_fence(); piece_ss<0>(acc, dA + 1024, b); wg_commit();
  turn_end(c);
  hook();
  wg_wait<1>(); stage_release(c, n);
  wg_wait<0>(); stage_release(c, n + 1);
}
__device__ __forceinline__ uint32_t frag_addr(const Ctx& c, uint32_t tile, int j) {
  return tile + (2 * c.wg + (j >> 2)) * 8192 + c.frag + ((((j & 3) * 2 + c.hi) ^ c.rsw) << 4);
}
__device__ __forceinline__ void load_half(const Ctx& c, uint32_t tile, float (&v)[64]) {
#pragma unroll
  for (int j = 0; j < 8; j++) {
    uint32_t r0, r1, r2, r3;
    ldsm_x4(frag_addr(c, tile, j), r0, r1, r2, r3);
    v[8 * j] = bf_lo(r0); v[8 * j + 1] = bf_hi(r0); v[8 * j + 2] = bf_lo(r1); v[8 * j + 3] = bf_hi(r1);
    v[8 * j + 4] = bf_lo(r2); v[8 * j + 5] = bf_hi(r2); v[8 * j + 6] = bf_lo(r3); v[8 * j + 7] = bf_hi(r3);
  }
}
__device__ __forceinline__ void store_half(const Ctx& c, uint32_t tile, const float (&v)[64], float a0, float b0, float a1, float b1) {
#pragma unroll
  for (int j = 0; j < 8; j++)
    stsm_x4(frag_addr(c, tile, j),
            pack_bf16(fmaf(v[8 * j], a0, b0), fmaf(v[8 * j + 1], a0, b0)), pack_bf16(fmaf(v[8 * j + 2], a1, b1), fmaf(v[8 * j + 3], a1, b1)),
            pack_bf16(fmaf(v[8 * j + 4], a0, b0), fmaf(v[8 * j + 5], a0, b0)), pack_bf16(fmaf(v[8 * j + 6], a1, b1), fmaf(v[8 * j + 7], a1, b1)));
}
__device__ __forceinline__ void store_half_raw(const Ctx& c, uint32_t tile, const float (&v)[64]) {
#pragma unroll
  for (int j = 0; j < 8; j++)
    stsm_x4(frag_addr(c, tile, j), pack_bf16(v[8 * j], v[8 * j + 1]), pack_bf16(v[8 * j + 2], v[8 * j + 3]),
            pack_bf16(v[8 * j + 4], v[8 * j + 5]), pack_bf16(v[8 * j + 6], v[8 * j + 7]));
}
__device__ __forceinline__ void ln_stats(const Ctx& c, const float (&v)[64], float scale, float& a0, float& b0, float& a1, float& b1) {
  float s0 = 0.f, s1 = 0.f, q0 = 0.f, q1 = 0.f, s2 = 0.f, s3 = 0.f, q2 = 0.f, q3 = 0.f;
#pragma unroll
  for (int i = 0; i < 16; i++) {
    s0 += v[4 * i]; q0 = fmaf(v[4 * i], v[4 * i], q0);
    s2 += v[4 * i + 1]; q2 = fmaf(v[4 * i + 1], v[4 * i + 1], q2);
    s1 += v[4 * i + 2]; q1 = fmaf(v[4 * i + 2], v[4 * i + 2], q1);
    s3 += v[4 * i + 3]; q3 = fmaf(v[4 * i + 3], v[4 * i + 3], q3);
  }
  s0 += s2; q0 += q2; s1 += s3; q1 += q3;
  s0 += __shfl_xor_sync(0xffffffff, s0, 1); q0 += __shfl_xor_sync(0xffffffff, q0, 1);
  s1 += __shfl_xor_sync(0xffffffff, s1, 1); q1 += __shfl_xor_sync(0xffffffff, q1, 1);
  s0 += __shfl_xor_sync(0xffffffff, s0, 2); q0 += __shfl_xor_sync(0xffffffff, q0, 2);
  s1 += __shfl_xor_sync(0xffffffff, s1, 2); q1 += __shfl_xor_sync(0xffffffff, q1, 2);
  const uint32_t row = (c.tid >> 5) * 16 + (c.lane >> 2);
  if ((c.lane & 3) == 0) {
    sts64f(c.stats + c.wg * 512 + row * 8, s0, q0);
    sts64f(c.stats + c.wg * 512 + (row + 8) * 8, s1, q1);
  }
  bar_sync(1, 256);
  const float2 o0 = lds64f(c.stats + (c.wg ^ 1) * 512 + row * 8), o1 = lds64f(c.stats + (c.wg ^ 1) * 512 + (row + 8) * 8);
  const float m0 = (s0 + o0.x) * (1.f / 256.f), m1 = (s1 + o1.x) * (1.f / 256.f);
  const float var0 = fmaxf(fmaf(-m0, m0, (q0 + o0.y) * (1.f / 256.f)), 0.f), var1 = fmaxf(fmaf(-m1, m1, (q1 + o1.y) * (1.f / 256.f)), 0.f);
  a0 = rsqrtf(var0 + 1e-5f) * scale; a1 = rsqrtf(var1 + 1e-5f) * scale;
  b0 = -m0 * a0; b1 = -m1 * a1;
}
__device__ __forceinline__ float silu_half(float h) { return fmaf(h, tanh_fast(h), h); }
__device__ __forceinline__ float silu_quarter(float h) { const float q = 0.5f * h; return fmaf(q, tanh_fast(h), q); }
__device__ __forceinline__ void silu_pack(const float (&acc)[32], uint32_t (&P)[16]) {
#pragma unroll
  for (int i = 0; i < 16; i++) P[i] = pack_bf16(silu_quarter(acc[2 * i]), silu_quarter(acc[2 * i + 1]));
}
__device__ __forceinline__ void ff_block(const Ctx& c, int n0, float (&own)[64]) {
  float oth[64], h[32];
  uint32_t P[16];
#pragma unroll
  for (int i = 0; i < 64; i++) oth[i] = 0.f;
  const uint32_t dA = dlo(c.sA, 16);
  {
    const uint32_t b = stage_wait(c, n0 + c.wg);
    turn_begin(c);
    wg_fence(); ff_g1(h, dA, b); wg_commit();
    turn_end(c);
    wg_wait<0>(); stage_release(c, n0 + c.wg);
    silu_pack(h, P);
  }
#pragma unroll 1
  for (int it = c.dry ? 7 : 1; it < 8; it++) {
    const int n = n0 + 4 * it - 2 + 2 * c.wg;
    uint32_t b = stage_wait(c, n);
    turn_begin(c);
    wg_fence(); ff_g2(own, P, b, c.wg); ff_g2(oth, P, b, c.wg ^ 1); wg_commit();
    b = stage_wait(c, n + 1);
    wg_fence(); ff_g1(h, dA, b); wg_commit();
    turn_end(c);
    wg_wait<1>(); stage_release(c, n);
    wg_wait<0>(); stage_release(c, n + 1);
    silu_pack(h, P);
  }
  if (c.wg == 0) bar_arrive(2, 256);
  {
    const int n = n0 + 30 + c.wg;
    const uint32_t b = stage_wait(c, n);
    turn_begin(c);
    wg_fence(); ff_g2(oth, P, b, c.wg ^ 1); wg_commit();
    ff_g2(own, P, b, c.wg); wg_commit();
    turn_end(c);
    wg_wait<1>();
    if (c.wg == 1) bar_sync(2, 256);
    const uint32_t e = (c.wg == 0 ? c.sX : c.sA) + c.tid * 16;
#pragma unroll
    for (int i = 0; i < 16; i++)
      sts128(e + i * 2048, make_uint4(__float_as_uint(oth[4 * i]), __float_as_uint(oth[4 * i + 1]), __float_as_uint(oth[4 * i + 2]), __float_as_uint(oth[4 * i + 3])));
    wg_wait<0>(); stage_release(c, n);
  }
  bar_sync(1, 256);
  const uint32_t e = (c.wg == 0 ? c.sA : c.sX) + c.tid * 16;
#pragma unroll
  for (int i = 0; i < 16; i++) {
    const uint4 u = lds128(e + i * 2048);
    own[4 * i] += __uint_as_float(u.x); own[4 * i + 1] += __uint_as_float(u.y);
    own[4 * i + 2] += __uint_as_float(u.z); own[4 * i + 3] += __uint_as_float(u.w);
  }
}
struct Maps { CUtensorMap X, W1a, W1b, Wqkv, QKVst, Q, KV, Wo, Pw1, Pw2, W2a, W2b, Out; };
constexpr int NA = 44;
constexpr int NC = 45;
__constant__ uint16_t c_stage[92] = {0x1, 0x11, 0x2, 0x21, 0x102, 0x31, 0x202, 0x41, 0x302, 0x51, 0x402, 0x61, 0x502, 0x71, 0x602, 0x81, 0x702, 0x91, 0x802, 0xa1, 0x902, 0xb1, 0xa02, 0xc1, 0xb02, 0xd1, 0xc02, 0xe1, 0xd02, 0xf1, 0xe02, 0xf02, 0x3, 0x203, 0x23, 0x223, 0x43, 0x243, 0x63, 0x263, 0x83, 0x283, 0xa3, 0x2a3, 0x7, 0x207, 0x27, 0x227, 0x8, 0x208, 0x2008, 0x2208, 0x1008, 0x1208, 0x3008, 0x3208, 0x9, 0x29, 0x209, 0x229, 0xa, 0x1a, 0xb, 0x2a, 0x10b, 0x3a, 0x20b, 0x4a, 0x30b, 0x5a, 0x40b, 0x6a, 0x50b, 0x7a, 0x60b, 0x8a, 0x70b, 0x9a, 0x80b, 0xaa, 0x90b, 0xba, 0xa0b, 0xca, 0xb0b, 0xda, 0xc0b, 0xea, 0xd0b, 0xfa, 0xe0b, 0xf0b};
__device__ __forceinline__ void load_stage(uint32_t dst, uint32_t bar, const Maps& tm, int n) {
  const uint32_t e = c_stage[n - (n > NA)];
  mbar_expect_tx(bar, STAGE);
  tma_load_3d(dst, &tm.X + (e & 15), bar, (e >> 12) * 64, ((e >> 8) & 15) * 64, (e >> 4) & 15);
}
__device__ __forceinline__ void produce(uint32_t sW, uint32_t full, const Maps& tm, int n0, int n1) {
  uint32_t s = n0 % RING, ph = ((n0 / RING) & 1) ^ 1;
#pragma unroll 1
  for (int n = n0; n < n1; n++) {
    mbar_wait(full + 8 * RING + 8 * s, ph);
    PROF_STG(n, 0);
    load_stage(sW + s * STAGE, full + 8 * s, tm, n);
    if (++s == RING) { s = 0; ph ^= 1; }
  }
}
__device__ __forceinline__ Ctx make_ctx(uint32_t base, uint32_t dry, int pk = 0) {
  Ctx c; c.pk = pk; c.dry = dry;
  c.sA = base; c.sX = base + OFF_X; c.sW = base + OFF_W;
  c.full = base + OFF_MISC; c.empty = c.full + 8 * RING; c.stats = base + OFF_MISC + 256;
  c.wg = __shfl_sync(0xffffffff, (int)(threadIdx.x >> 7), 0);
  c.tid = threadIdx.x & 127; c.lane = threadIdx.x & 31;
  const uint32_t r = (c.tid >> 5) * 16 + (c.lane & 7) + ((c.lane >> 3) & 1) * 8;
  c.frag = r * 128; c.rsw = r & 7; c.hi = c.lane >> 4;
  return c;
}

constexpr int NSTG = 4;
constexpr int KVB = 160 * 128;
constexpr int NKV = T_ / 160;
static_assert(NSTG * 2 * KVB == RING * STAGE, "the K/V ring reuses the weight ring");

struct AttCtx { uint32_t sKV, full, empty, dry, wfull; const Maps* tm; int h, b, wg; };
__device__ __forceinline__ int kv_slot(int i) { return (i + 3) & 3; }
__device__ __forceinline__ void att_load(const AttCtx& a, int i, int v) {
  const int s = i & 3;
  mbar_expect_tx(a.full + 8 * (s + v * NSTG), KVB);
  tma_load_3d(a.sKV + kv_slot(i) * 2 * KVB + v * KVB, &a.tm->KV, a.full + 8 * (s + v * NSTG), 256 + v * 256 + a.h * 64, i * 160, a.b);
}
__device__ __forceinline__ void att_load_stage(const AttCtx& a, int i) { att_load(a, i, 0); att_load(a, i, 1); }
__device__ __forceinline__ void att_init_bars(const AttCtx& a) {
  for (int i = 0; i < NSTG; i++) { mbar_init(a.full + 8 * i, 1); mbar_init(a.full + 8 * (NSTG + i), 1); mbar_init(a.empty + 8 * i, 4); }
}
__device__ __forceinline__ void att_qk(float (&S)[40], uint32_t dQ, uint32_t kd) {
  wg_ss_n80_tb0<0>(S, dQ, kd);
#pragma unroll
  for (int kk = 1; kk < 4; kk++) wg_ss_n80_tb0<1>(S, dQ + kk * 2, kd + kk * 2);
}
__device__ __forceinline__ void att_pv(float (&O)[32], const uint32_t (&P)[20], uint32_t vd) {
#pragma unroll
  for (int kk = 0; kk < 5; kk++) wg_rs_n64_tb1<1>(O, P[kk * 4], P[kk * 4 + 1], P[kk * 4 + 2], P[kk * 4 + 3], vd + kk * 128);
}
template<bool SAFE>
__device__ __forceinline__ void att_softmax(const float (&S)[40], uint32_t (&P)[20], float (&O)[32], float& m0, float& m1, float& l0, float& l1) {
  if (SAFE) {
    float x0 = fmaxf(S[0], S[1]), x1 = fmaxf(S[2], S[3]);
#pragma unroll
    for (int i = 1; i < 10; i++) { x0 = fmaxf(x0, fmaxf(S[4 * i], S[4 * i + 1])); x1 = fmaxf(x1, fmaxf(S[4 * i + 2], S[4 * i + 3])); }
    x0 = fmaxf(x0, __shfl_xor_sync(0xffffffff, x0, 1)); x1 = fmaxf(x1, __shfl_xor_sync(0xffffffff, x1, 1));
    x0 = fmaxf(x0, __shfl_xor_sync(0xffffffff, x0, 2)); x1 = fmaxf(x1, __shfl_xor_sync(0xffffffff, x1, 2));
    const float n0 = fmaxf(m0, x0), n1 = fmaxf(m1, x1);
    const float f0 = ex2(m0 - n0), f1 = ex2(m1 - n1);
    m0 = n0; m1 = n1; l0 *= f0; l1 *= f1;
#pragma unroll
    for (int i = 0; i < 8; i++) { O[4 * i] *= f0; O[4 * i + 1] *= f0; O[4 * i + 2] *= f1; O[4 * i + 3] *= f1; }
  }
#pragma unroll
  for (int i = 0; i < 10; i++) {
    float p0, p1, p2, p3;
    if (SAFE) { p0 = ex2(S[4 * i] - m0); p1 = ex2(S[4 * i + 1] - m0); p2 = ex2(S[4 * i + 2] - m1); p3 = ex2(S[4 * i + 3] - m1); }
    else { p0 = ex2(S[4 * i]); p1 = ex2(S[4 * i + 1]); p2 = ex2(S[4 * i + 2]); p3 = ex2(S[4 * i + 3]); }
    l0 += p0 + p1; l1 += p2 + p3;
    P[2 * i] = pack_bf16(p0, p1); P[2 * i + 1] = pack_bf16(p2, p3);
  }
}
template<bool SAFE>
__device__ __forceinline__ void att_refill(const AttCtx& a, int it) {
  if ((threadIdx.x & 127) == 0) {
    mbar_arrive(a.empty + 8 * (it & 3));
    if (a.wg == (it & 3) && it >= 1 && !a.dry) {
      const bool kv = it - 1 + NSTG < NKV;
      if (kv || (!SAFE && a.wfull)) {
        mbar_wait(a.empty + 8 * ((it - 1) & 3), ((it - 1) >> 2) & 1);
        if (kv) att_load_stage(a, it - 1 + NSTG);
        else load_stage(a.sKV + (it - 22) * STAGE, a.wfull + 8 * (it - 22), *a.tm, NC + it - 22);
      }
    }
  }
  __syncwarp();
}
constexpr uint32_t KV_STG = 2 * KVB / 16, KV_VOFF = KVB / 16, KV_HALF = 80 * 128 / 16;
template<bool SAFE>
__device__ __forceinline__ void att_pass(const AttCtx& a, uint32_t dQ, float (&O)[32], float& l0, float& l1) {
  float S[40];
  uint32_t P[20];
  float m0 = -INFINITY, m1 = -INFINITY;
  l0 = 0.f; l1 = 0.f;
#pragma unroll
  for (int i = 0; i < 32; i++) O[i] = 0.f;
  const uint32_t dKV = dlo(a.sKV, 16);
  if (SAFE) {
#pragma unroll 1
    for (int j = 0; j < 2 * NKV; j++) {
      const int it = j >> 1, s = it & 3;
      const uint32_t kb = dKV + kv_slot(it) * KV_STG + (j & 1) * KV_HALF;
      mbar_wait(a.full + 8 * s, (it >> 2) & 1);
      wg_fence(); att_qk(S, dQ, kb); wg_commit(); wg_wait<0>();
      att_softmax<true>(S, P, O, m0, m1, l0, l1);
      mbar_wait(a.full + 8 * (NSTG + s), (it >> 2) & 1);
      wg_fence(); att_pv(O, P, kb + KV_VOFF); wg_commit(); wg_wait<0>();
      if (j & 1) att_refill<true>(a, it);
    }
  } else {
    mbar_wait(a.full, a.dry);
    wg_fence(); att_qk(S, dQ, dKV + 3 * KV_STG); wg_commit(); wg_wait<0>();
    att_softmax<false>(S, P, O, m0, m1, l0, l1);
    mbar_wait(a.full + 8 * NSTG, a.dry);
    wg_fence(); att_pv(O, P, dKV + 3 * KV_STG + KV_VOFF); att_qk(S, dQ, dKV + 3 * KV_STG + KV_HALF); wg_commit(); wg_wait<0>();
#pragma unroll 1
    for (int it = a.dry ? NKV - 2 : 0; it < NKV - 1; it++) {
      const int sn = (it + 1) & 3;
      const uint32_t kb = dKV + kv_slot(it) * KV_STG, kn = dKV + kv_slot(it + 1) * KV_STG, par = (((it + 1) >> 2) | a.dry) & 1;
      att_softmax<false>(S, P, O, m0, m1, l0, l1);
      mbar_wait(a.full + 8 * sn, par);
      wg_fence(); att_pv(O, P, kb + KV_VOFF + KV_HALF); att_qk(S, dQ, kn); wg_commit(); wg_wait<0>();
      att_refill<false>(a, it);
      att_softmax<false>(S, P, O, m0, m1, l0, l1);
      mbar_wait(a.full + 8 * (NSTG + sn), par);
      wg_fence(); att_pv(O, P, kn + KV_VOFF); att_qk(S, dQ, kn + KV_HALF); wg_commit(); wg_wait<0>();
    }
    att_softmax<false>(S, P, O, m0, m1, l0, l1);
    wg_fence(); att_pv(O, P, dKV + 3 * KV_STG + KV_VOFF + KV_HALF); wg_commit(); wg_wait<0>();
  }
  l0 += __shfl_xor_sync(0xffffffff, l0, 1); l1 += __shfl_xor_sync(0xffffffff, l1, 1);
  l0 += __shfl_xor_sync(0xffffffff, l0, 2); l1 += __shfl_xor_sync(0xffffffff, l1, 2);
}

struct Wptrs { const void* p[8]; uint32_t bytes[8]; };

constexpr uint32_t B_FULL = 0, B_EMPTY = 8 * RING, B_X = 16 * RING, B_ADONE = B_X + 8, B_Q = B_X + 16, B_EP = B_X + 24, B_ATT = B_X + 32;

__global__ void __launch_bounds__(512, 1) conformer_kernel(const __grid_constant__ Maps tm, const __grid_constant__ Wptrs wp, const uint4* __restrict__ dw) {
  extern __shared__ uint8_t smem_raw[];
  const uint32_t base = (smem_u32(smem_raw) + 1023) & ~1023u, misc = base + OFF_MISC;
  const uint32_t dry = blockIdx.x >= 128;
  const int tile = dry ? 0 : blockIdx.x;
  const bool has_tile = dry ? blockIdx.x == 128 : tile < NTILE;
  const int wg = __shfl_sync(0xffffffff, (int)(threadIdx.x >> 7), 0);
  AttCtx a;
  a.sKV = base + OFF_W; a.full = misc + B_ATT; a.empty = a.full + 16 * NSTG; a.tm = &tm;
  a.h = (blockIdx.x >> 4) & 3; a.b = (blockIdx.x >> 6) & 1; a.wg = wg; a.dry = dry; a.wfull = has_tile ? misc + B_FULL : 0;
  const int qt = blockIdx.x & 15;

  if (threadIdx.x == 256) {
    mbar_init(misc + B_X, 1);
    for (int i = 0; i < RING; i++) { mbar_init(misc + B_FULL + 8 * i, 1); mbar_init(misc + B_EMPTY + 8 * i, 1); }
    asm volatile("fence.mbarrier_init.release.cluster;" ::: "memory");
    if (has_tile && !dry) {
      mbar_expect_tx(misc + B_X, 32768);
      tma_load_3d(base + OFF_X, &tm.X, misc + B_X, 0, tile * 64, 0);
#pragma unroll 1
      for (int i = 0; i < RING; i++) load_stage(base + OFF_W + i * STAGE, misc + B_FULL + 8 * i, tm, i);
    }
  } else if (threadIdx.x == 288) {
    mbar_init(misc + B_ADONE, 2);
    mbar_init(misc + B_Q, 1);
    mbar_init(misc + B_EP, 1);
    att_init_bars(a);
    asm volatile("fence.mbarrier_init.release.cluster;" ::: "memory");
  } else if (threadIdx.x >= 320 && threadIdx.x < 333) {
    prefetch_tmap(&tm.X + (threadIdx.x - 320));
  }
  __syncthreads();
  auto get_epoch = [&]() {
    uint32_t e;
    mbar_wait(misc + B_EP, 0);
    asm volatile("ld.shared.u32 %0, [%1];" : "=r"(e) : "r"(misc + 248) : "memory");
    return e;
  };

  if (wg >= 2) {
    asm volatile("setmaxnreg.dec.sync.aligned.u32 24;");
    const uint32_t full = misc + B_FULL;
    if (threadIdx.x == 320) {
      const uint32_t e = atomicAdd(&g_start, 1) / NCTA;
      asm volatile("st.shared.u32 [%0], %1;" :: "r"(misc + 248), "r"(e + 1) : "memory");
      mbar_arrive(misc + B_EP);
    }
    if (dry) {
    } else if (threadIdx.x == 256) {
      if (has_tile) {
        produce(base + OFF_W, full, tm, RING, NA);
        mbar_wait(full + 8 * RING + 8 * 4, 1);
        mbar_arrive(full + 8 * 4); mbar_arrive(full + 8 * RING + 8 * 4);
        mbar_wait(misc + B_ADONE, 0);
      }
      cnt_wait(g_cnt1 + a.b * 64, 126 * get_epoch());
      mbar_expect_tx(misc + B_Q, 32768);
      tma_load_3d(base, &tm.Q, misc + B_Q, a.h * 64, qt * 256, a.b);
      att_load(a, 0, 0);
      mbar_wait(misc + B_Q, 0);
#pragma unroll 1
      for (int i = 1; i < NSTG; i++) att_load(a, i, 0);
    } else if ((threadIdx.x >> 5) == 12) {
      if (has_tile) bar_sync(9, 288);
      if (threadIdx.x == 384) {
        cnt_wait(g_cnt1 + a.b * 64 + 32, 126 * get_epoch());
        att_load(a, 0, 1);
        mbar_wait(a.full + 8 * NSTG, 0);
#pragma unroll 1
        for (int i = 1; i < NSTG; i++) att_load(a, i, 1);
      }
    } else if (has_tile && threadIdx.x >= 288 && threadIdx.x < 296) {
      const int w = threadIdx.x - 288;
      mbar_wait(misc + B_X, 0);
      const uint32_t bytes = wp.bytes[w], per = ((bytes / NTILE) + 127) & ~127u, off = per * tile;
      if (off < bytes) l2_prefetch((const uint8_t*)wp.p[w] + off, min(per, bytes - off));
    } else if (has_tile && threadIdx.x >= 416) {
      mbar_wait(full, 0);
      const int t = threadIdx.x - 416;
#pragma unroll 2
      for (int i = t; i < 2048; i += 96) g_att[tile * 2048 + i] = make_uint4(~0u, ~0u, ~0u, ~0u);
      g_halo[tile * 128 + t] = make_uint4(~0u, ~0u, ~0u, ~0u);
      if (t < 32) g_halo[tile * 128 + 96 + t] = make_uint4(~0u, ~0u, ~0u, ~0u);
    }
    __syncwarp();
    bar_sync(5 + wg, 384);
    asm volatile("setmaxnreg.inc.sync.aligned.u32 128;");
  } else {
    asm volatile("setmaxnreg.inc.sync.aligned.u32 232;");
    if (has_tile) {
      const Ctx c = make_ctx(base, dry);
      if (c.wg == 1) turn_end(c);
      float own[64];
      float a0, b0, a1, b1;
      PROF_MARK(0, 0);
      mbar_wait(misc + B_X, dry);
      PROF_MARK(0, 1);
      load_half(c, c.sX, own);
      ln_stats(c, own, 0.5f, a0, b0, a1, b1);
      store_half(c, c.sA, own, a0, b0, a1, b1);
      fence_async_smem();
      bar_sync(1, 256);
      PROF_MARK(0, 2);
      ff_block(c, 0, own);
      PROF_MARK(0, 3);
      ln_stats(c, own, 1.f, a0, b0, a1, b1);
      store_half(c, c.sA, own, a0, b0, a1, b1);
      fence_async_smem();
      bar_sync(1, 256);
      PROF_MARK(0, 4);
#pragma unroll 1
      for (int cc = dry ? 2 : 0; cc < 3; cc++) {
        float acc[64];
        const int j = 2 * cc + c.wg;
        gemm256<1>(c, acc, 32 + 2 * j, [&]() {
          if (c.tid == 0 && !dry) {
            if (cc == 2) {
              bulk_wait_all();
              if (tile <= 62) cnt_signal(g_cnt1);
              if (tile >= 62) cnt_signal(g_cnt1 + 64);
            } else bulk_wait_read();
          }
          bar_sync(3 + c.wg, 128);
        });
        if (cc == 2 && !dry) { bar_arrive(9, 288); if (c.tid == 0) mbar_arrive(misc + B_ADONE); }
        if (cc == 0) {
#pragma unroll
          for (int i = 0; i < 64; i++) acc[i] *= 0.125f * 1.4426950408889634f;
        }
        store_half_raw(c, c.sX, acc);
        fence_async_smem();
        bar_sync(3 + c.wg, 128);
        if (c.tid == 0 && !dry) { tma_store_3d(&tm.QKVst, c.sX + c.wg * 16384, 0, tile * 64, 2 * j); bulk_commit(); }
      }
      PROF_MARK(0, 5);
      if (c.tid == 0) bulk_wait_read();
      bar_sync(3 + c.wg, 128);
      store_half_raw(c, c.sX, own);
    }
    else bar_sync(3 + wg, 128);
    asm volatile("setmaxnreg.dec.sync.aligned.u32 128;");
    bar_arrive(7, 384); bar_arrive(8, 384);
    if (has_tile && !dry && (threadIdx.x & 127) == 0) {
      bulk_wait_all();
      if (tile <= 62) cnt_signal(g_cnt1 + 32);
      if (tile >= 62) cnt_signal(g_cnt1 + 96);
    }
    __syncwarp();
    PROF_MARK(0, 6);
  }

  if (blockIdx.x == 128) return;
  if (blockIdx.x != 130) {
    const int lane = threadIdx.x & 31, wq = (threadIdx.x >> 5) & 3;
    const uint32_t dQ = dlo(base + wg * 8192, 16);
    float O[32], l0, l1;
    PROF_MARK(1, 1);
    mbar_wait(misc + B_Q, dry);
    PROF_MARK(1, 2);
    att_pass<false>(a, dQ, O, l0, l1);
    PROF_MARK(1, 3);
    float z = 0.f;
#pragma unroll
    for (int i = 0; i < 32; i++) z = fmaf(O[i], 0.f, z);
    const bool ok = (l0 >= 0x1p-80f) && (l0 <= 0x1p100f) && (l1 >= 0x1p-80f) && (l1 <= 0x1p100f) && (z == 0.f);
    const bool warp_bad = !__all_sync(0xffffffff, ok) && !dry;
    auto store_out = [&]() {
      const float i0 = 1.f / l0, i1 = 1.f / l1;
      const int row = qt * 256 + wg * 64 + wq * 16;
      if (row < T_ && !dry) {
        const int slab = (a.b * T_ + row) / 16;
        uint4* op = g_att + (slab * 16 + a.h * 4) * 32 + lane;
#pragma unroll
        for (int j = 0; j < 4; j++)
          asm volatile("st.relaxed.gpu.global.v4.u32 [%0], {%1,%2,%3,%4};" :: "l"(op + j * 32),
                       "r"(pack_bf16(O[8 * j] * i0, O[8 * j + 1] * i0)), "r"(pack_bf16(O[8 * j + 2] * i1, O[8 * j + 3] * i1)),
                       "r"(pack_bf16(O[8 * j + 4] * i0, O[8 * j + 5] * i0)), "r"(pack_bf16(O[8 * j + 6] * i1, O[8 * j + 7] * i1)) : "memory");
        __syncwarp();
        if (lane == 0) cnt_signal(g_cnt2 + slab * 32);
      }
      PROF_MARK(1, 4);
    };
    if (!warp_bad) store_out();
    if (__syncthreads_or(warp_bad)) {
      if (threadIdx.x == 0) {
        if (has_tile) { mbar_wait(misc + B_FULL, 1); mbar_wait(misc + B_FULL + 8, 1); }
        for (int i = 0; i < 3 * NSTG; i++) mbar_inval(a.full + 8 * i);
        att_init_bars(a);
        asm volatile("fence.mbarrier_init.release.cluster;" ::: "memory");
        fence_async_smem();
#pragma unroll 1
        for (int i = 0; i < NSTG; i++) att_load_stage(a, i);
      }
      __syncthreads();
      att_pass<true>(a, dQ, O, l0, l1);
      if (warp_bad) store_out();
      __syncthreads();
      if (has_tile) {
        if (threadIdx.x == 32) {
          load_stage(base + OFF_W, misc + B_X, tm, NC);
          load_stage(base + OFF_W + STAGE, misc + B_Q, tm, NC + 1);
        }
        mbar_wait(misc + B_X, 1); mbar_wait(misc + B_Q, 1);
      }
    }
    PROF_MARK(1, 5);
  } else {
    __syncthreads();
  }
  if (dry ? blockIdx.x != 130 : !has_tile) return;

  if (wg >= 2) {
    asm volatile("setmaxnreg.dec.sync.aligned.u32 24;");
    if (threadIdx.x == 256 && !dry) produce(base + OFF_W, misc + B_FULL, tm, NC + 2, NC + 48);
  } else {
    asm volatile("setmaxnreg.inc.sync.aligned.u32 232;");
    const Ctx c = make_ctx(base, dry);
    if (dry && c.wg == 1) turn_end(c);
    float own[64];
    float a0, b0, a1, b1;
    PROF_MARK(2, 0);
    {
      uint4 af[16];
      const int slab = tile * 4 + (c.tid >> 5);
      const uint4* ap = g_att + slab * 512 + c.lane;
      if (c.wg == 1) load_half(c, c.sX, own);
      for (uint32_t n = 0; n < (1u << 18); n++) {
        bool any = false;
#pragma unroll
        for (int i = 0; i < 16; i++)
          asm volatile("ld.relaxed.gpu.global.v4.u32 {%0,%1,%2,%3}, [%4];" : "=r"(af[i].x), "=r"(af[i].y), "=r"(af[i].z), "=r"(af[i].w) : "l"(ap + i * 32) : "memory");
        if (n == 0 && c.wg == 0) load_half(c, c.sX, own);
#pragma unroll
        for (int i = 0; i < 16; i++) any |= max(max(af[i].x, af[i].y), max(af[i].z, af[i].w)) == ~0u;
        if (!__any_sync(0xffffffff, any) || dry) break;
        if (c.lane == 0) cnt_wait(g_cnt2 + slab * 32, 4 * get_epoch());
        __syncwarp();
      }
      PROF_MARK(2, 2);
      const int n = NC + 2 * c.wg;
      uint32_t b = stage_wait(c, n) + ((16384 >> 4) << 16);
      turn_begin(c);
      wg_fence();
#pragma unroll
      for (int kk = 0; kk < 8; kk++) wg_rs_n128_tb1<1>(own, af[kk].x, af[kk].y, af[kk].z, af[kk].w, b + kk * 128);
      wg_commit();
      b = stage_wait(c, n + 1) + ((16384 >> 4) << 16);
      wg_fence();
#pragma unroll
      for (int kk = 0; kk < 8; kk++) wg_rs_n128_tb1<1>(own, af[8 + kk].x, af[8 + kk].y, af[8 + kk].z, af[8 + kk].w, b + kk * 128);
      wg_commit();
      turn_end(c);
      wg_wait<1>(); stage_release(c, n);
      wg_wait<0>(); stage_release(c, n + 1);
    }
    PROF_MARK(2, 3);
    ln_stats(c, own, 0.5f, a0, b0, a1, b1);
    store_half(c, c.sA, own, a0, b0, a1, b1);
    fence_async_smem();
    bar_sync(1, 256);
    PROF_MARK(2, 4);
    uint4 dwr[5];
#pragma unroll
    for (int i = 0; i < 5; i++) dwr[i] = __ldg(dw + i * 32 + c.wg * 16 + (c.lane & 15));
    const bool top = c.tid < 8, pub = (top || c.tid >= 120) && !dry;
    uint32_t* halo_out = (uint32_t*)g_halo + (tile * 4 + (top ? (c.tid >> 2) : ((c.tid >> 2) - 28))) * 128 + c.wg * 64 + (c.lane & 3);
#pragma unroll 1
    for (int q = dry; q < 2; q++) {
      float ab[64];
      gemm256<1>(c, ab, NC + 4 + 4 * q + 2 * c.wg);
#pragma unroll
      for (int j = 0; j < 4; j++) {
        float g[8];
#pragma unroll
        for (int i = 0; i < 8; i++) g[i] = fmaf(ab[8 * j + i], tanh_fast(ab[32 + 8 * j + i]), ab[8 * j + i]);
        const uint32_t p0 = pack_bf16(g[0], g[1]), p1 = pack_bf16(g[2], g[3]), p2 = pack_bf16(g[4], g[5]), p3 = pack_bf16(g[6], g[7]);
        if (pub) {
          uint32_t* hp = halo_out + q * 32 + j * 8;
          asm volatile("st.relaxed.gpu.global.u32 [%0], %1;" :: "l"(hp), "r"(top ? p0 : p1) : "memory");
          asm volatile("st.relaxed.gpu.global.u32 [%0], %1;" :: "l"(hp + 4), "r"(top ? p2 : p3) : "memory");
        }
        stsm_x4(c.sX + (2 * c.wg + q) * 8192 + c.frag + (((j * 2 + c.hi) ^ c.rsw) << 4), p0, p1, p2, p3);
      }
    }
    bar_sync(3 + c.wg, 128);
    PROF_MARK(2, 5);
    {
      const int wi = c.tid >> 4;
      const uint32_t col = (2 * c.wg + ((c.lane >> 3) & 1)) * 8192, ch = c.lane & 7;
      uint4 r[12];
      const int R0 = tile * 64 + wi * 8;
      const bool first = (R0 % T_) == 0, last = ((R0 + 8) % T_) == 0;
      const bool far = ((wi == 0 && !first) || (wi == 7 && !last)) && !dry;
      const uint4* sp = g_halo + (wi == 0 ? (tile - 1) * 4 + 2 : (tile + 1) * 4) * 32 + c.wg * 16 + (c.lane & 15);
      uint4 h0 = make_uint4(0, 0, 0, 0), h1 = h0;
      auto ld_halo = [&]() {
        asm volatile("ld.relaxed.gpu.global.v4.u32 {%0,%1,%2,%3}, [%4];" : "=r"(h0.x), "=r"(h0.y), "=r"(h0.z), "=r"(h0.w) : "l"(sp) : "memory");
        asm volatile("ld.relaxed.gpu.global.v4.u32 {%0,%1,%2,%3}, [%4];" : "=r"(h1.x), "=r"(h1.y), "=r"(h1.z), "=r"(h1.w) : "l"(sp + 32) : "memory");
      };
      if (far) ld_halo();
#pragma unroll
      for (int i = 0; i < 12; i++) {
        const int row = (wi * 8 - 2 + i) & 63;
        r[i] = lds128(c.sX + col + row * 128 + ((ch ^ (row & 7)) << 4));
      }
      uint32_t w[5][4];
#pragma unroll
      for (int k = 0; k < 5; k++) {
        w[k][0] = bmul2(dwr[k].x, 0x3F003F00u); w[k][1] = bmul2(dwr[k].y, 0x3F003F00u);
        w[k][2] = bmul2(dwr[k].z, 0x3F003F00u); w[k][3] = bmul2(dwr[k].w, 0x3F003F00u);
      }
      auto conv4 = [&](int i0, int i1, int i2, int i3, bool sync) {
        const int rows[4] = {i0, i1, i2, i3};
        uint32_t acc[4][4];
#pragma unroll
        for (int k = 0; k < 5; k++)
#pragma unroll
          for (int j = 0; j < 4; j++) {
            const uint4 x = r[rows[j] + k];
            acc[j][0] = k ? bfma2(x.x, w[k][0], acc[j][0]) : bmul2(x.x, w[0][0]);
            acc[j][1] = k ? bfma2(x.y, w[k][1], acc[j][1]) : bmul2(x.y, w[0][1]);
            acc[j][2] = k ? bfma2(x.z, w[k][2], acc[j][2]) : bmul2(x.z, w[0][2]);
            acc[j][3] = k ? bfma2(x.w, w[k][3], acc[j][3]) : bmul2(x.w, w[0][3]);
          }
#pragma unroll
        for (int j = 0; j < 4; j++)
#pragma unroll
          for (int q = 0; q < 4; q++) acc[j][q] = pack_bf16(silu_half(bf_lo(acc[j][q])), silu_half(bf_hi(acc[j][q])));
        if (sync) bar_sync(3 + c.wg, 128);
#pragma unroll
        for (int j = 0; j < 4; j++)
          sts128(c.sX + col + (wi * 8 + rows[j]) * 128 + ((ch ^ rows[j]) << 4), make_uint4(acc[j][0], acc[j][1], acc[j][2], acc[j][3]));
      };
      conv4(2, 3, 4, 5, true);
      if (far) {
        for (uint32_t n = 0; n < (1u << 18); n++) {
          const uint32_t mx = max(max(max(h0.x, h0.y), max(h0.z, h0.w)), max(max(h1.x, h1.y), max(h1.z, h1.w)));
          if (mx != ~0u) break;
          ld_halo();
        }
      }
      __syncwarp();
      if (first || (far && wi == 0)) { r[0] = h0; r[1] = h1; }
      if (last || (far && wi == 7)) { r[10] = h0; r[11] = h1; }
      conv4(0, 1, 6, 7, false);
    }
    fence_async_smem();
    bar_sync(c.wg == 0 ? 3 : 1, c.wg == 0 ? 128 : 256);
    PROF_MARK(2, 6);
    {
      uint32_t b = stage_wait(c, NC + 12 + c.wg);
      turn_begin(c);
      wg_fence(); piece_ss<0>(own, dlo(c.sX, 16), b); wg_commit();
      if (c.wg == 0) { turn_end(c); bar_sync(1, 256); turn_begin(c); }
      b = stage_wait(c, NC + 14 + c.wg);
      wg_fence(); piece_ss<0>(own, dlo(c.sX, 16) + 1024, b); wg_commit();
      turn_end(c);
    }
    wg_wait<1>(); stage_release(c, NC + 12 + c.wg);
    wg_wait<0>(); stage_release(c, NC + 14 + c.wg);
    PROF_MARK(2, 7);
    ln_stats(c, own, 0.5f, a0, b0, a1, b1);
    if (c.wg == 1) { turn_begin(c); turn_end(c); }
    store_half(c, c.sA, own, a0, b0, a1, b1);
    fence_async_smem();
    bar_sync(1, 256);
    PROF_MARK(2, 8);
    ff_block(c, NC + 16, own);
    PROF_MARK(2, 9);
    ln_stats(c, own, 1.f, a0, b0, a1, b1);
    store_half(c, c.sX, own, a0, b0, a1, b1);
    fence_async_smem();
    bar_sync(3 + c.wg, 128);
    if (c.tid == 0 && !dry) { tma_store_3d(&tm.Out, c.sX + c.wg * 16384, 0, tile * 64, 2 * c.wg); bulk_commit(); PROF_MARK(2, 10); bulk_wait_read(); }
    PROF_MARK(2, 11);
  }
}

typedef CUresult (*EncodeFn)(CUtensorMap*, CUtensorMapDataType, cuuint32_t, void*, const cuuint64_t*, const cuuint64_t*, const cuuint32_t*,
                             const cuuint32_t*, CUtensorMapInterleave, CUtensorMapSwizzle, CUtensorMapL2promotion, CUtensorMapFloatOOBfill);

CUtensorMap make_map(EncodeFn enc, const void* p, uint64_t d0, uint64_t d1, uint64_t d2, uint64_t s1, uint64_t s2, uint32_t b1, uint32_t b2) {
  CUtensorMap tm;
  cuuint64_t dims[3] = {d0, d1, d2};
  cuuint64_t strides[2] = {s1, s2};
  cuuint32_t box[3] = {64, b1, b2};
  cuuint32_t es[3] = {1, 1, 1};
  enc(&tm, CU_TENSOR_MAP_DATA_TYPE_BFLOAT16, 3, const_cast<void*>(p), dims, strides, box, es, CU_TENSOR_MAP_INTERLEAVE_NONE,
      CU_TENSOR_MAP_SWIZZLE_128B, CU_TENSOR_MAP_L2_PROMOTION_L2_256B, CU_TENSOR_MAP_FLOAT_OOB_FILL_NONE);
  return tm;
}
CUtensorMap blk_map(EncodeFn enc, const void* p, uint64_t rows, uint64_t cols, uint32_t boxrows, uint32_t boxblks) {
  return make_map(enc, p, 64, rows, cols / 64, cols * 2, 128, boxrows, boxblks);
}
CUtensorMap seq_map(EncodeFn enc, const void* p, uint64_t cols, uint32_t boxrows) {
  return make_map(enc, p, cols, T_, 2, cols * 2, cols * 2 * T_, boxrows, 1);
}

}

extern "C" void kernel_launch(void* const* d_in, const int* in_sizes, int n_in, void* d_out, int out_size) {
  (void)in_sizes; (void)n_in; (void)out_size;
  const void *x = d_in[0], *w1a = d_in[1], *w1b = d_in[2], *wqkv = d_in[3], *wo = d_in[4], *pw1 = d_in[5], *dw = d_in[6], *pw2 = d_in[7],
             *w2a = d_in[8], *w2b = d_in[9];
  void* fn = nullptr;
  cudaDriverEntryPointQueryResult qr;
  cudaGetDriverEntryPoint("cuTensorMapEncodeTiled", &fn, cudaEnableDefault, &qr);
  EncodeFn enc = (EncodeFn)fn;
  void* qkv;
  cudaGetSymbolAddress(&qkv, g_qkv);
  cudaFuncSetAttribute(conformer_kernel, cudaFuncAttributeMaxDynamicSharedMemorySize, SMEM_BYTES);

  Wptrs wp;
  const void* ws[8] = {w1a, w1b, wqkv, wo, pw1, pw2, w2a, w2b};
  const uint32_t wb[8] = {524288, 524288, 393216, 131072, 262144, 131072, 524288, 524288};
  for (int i = 0; i < 8; i++) { wp.p[i] = ws[i]; wp.bytes[i] = wb[i]; }
  Maps tm;
  tm.X = blk_map(enc, x, ROWS, 256, 64, 4);
  tm.W1a = blk_map(enc, w1a, 256, 1024, 256, 1);
  tm.W1b = blk_map(enc, w1b, 1024, 256, 64, 4);
  tm.Wqkv = blk_map(enc, wqkv, 256, 768, 128, 2);
  tm.QKVst = blk_map(enc, qkv, ROWS, 768, 64, 2);
  tm.Q = seq_map(enc, qkv, 768, 256);
  tm.KV = seq_map(enc, qkv, 768, 160);
  tm.Wo = blk_map(enc, wo, 256, 256, 128, 2);
  tm.Pw1 = make_map(enc, pw1, 256, 256, 2, 1024, 512, 128, 2);
  tm.Pw2 = blk_map(enc, pw2, 256, 256, 128, 2);
  tm.W2a = blk_map(enc, w2a, 256, 1024, 256, 1);
  tm.W2b = blk_map(enc, w2b, 1024, 256, 64, 4);
  tm.Out = blk_map(enc, d_out, ROWS, 256, 64, 2);
  conformer_kernel<<<NCTA, 512, SMEM_BYTES, cudaStreamPerThread>>>(tm, wp, (const uint4*)dw);
}
```

```cpp
#include <cuda_runtime.h>
#include <cuda_bf16.h>
#include <cuda.h>
#include <stdint.h>

namespace {

constexpr int T_ = 4000;
constexpr int ROWS = 8000;
constexpr int NTILE = 125;
#define NCTA_ 131
constexpr int NCTA = NCTA_;

__device__ __nv_bfloat16 g_qkv[ROWS * 768];
__device__ uint4 g_att[(ROWS / 16) * 16 * 32];
__device__ uint4 g_halo[NTILE * 4 * 32];
__device__ uint32_t g_start;
__device__ uint32_t g_cnt1[4 * 32];
#define PROD_NS 200
#define POLL_NS 100

#define PROF_MARK(k, i) do {} while (0)
#define PROF_STG(n, i) do {} while (0)

__device__ __forceinline__ uint32_t smem_u32(const void* p) { return (uint32_t)__cvta_generic_to_shared(p); }
__device__ __forceinline__ void mbar_init(uint32_t bar, uint32_t cnt) { asm volatile("mbarrier.init.shared::cta.b64 [%0], %1;" :: "r"(bar), "r"(cnt) : "memory"); }
__device__ __forceinline__ void mbar_inval(uint32_t bar) { asm volatile("mbarrier.inval.shared::cta.b64 [%0];" :: "r"(bar) : "memory"); }
__device__ __forceinline__ void mbar_expect_tx(uint32_t bar, uint32_t bytes) { asm volatile("mbarrier.arrive.expect_tx.shared::cta.b64 _, [%0], %1;" :: "r"(bar), "r"(bytes) : "memory"); }
__device__ __forceinline__ void mbar_arrive(uint32_t bar) { asm volatile("mbarrier.arrive.shared::cta.b64 _, [%0];" :: "r"(bar) : "memory"); }
__device__ __forceinline__ void mbar_wait(uint32_t bar, uint32_t parity) {
  asm volatile("{\n.reg .pred p;\n.reg .u32 n;\n"
               "mbarrier.try_wait.parity.shared::cta.b64 p, [%0], %1;\n@p bra DONE_%=;\nmov.u32 n, 0;\n"
               "LOOP_%=:\nmbarrier.try_wait.parity.shared::cta.b64 p, [%0], %1;\n@p bra DONE_%=;\n"
               "add.u32 n, n, 1;\nsetp.lt.u32 p, n, 262144;\n@p bra LOOP_%=;\ntrap;\nDONE_%=:\n}\n" :: "r"(bar), "r"(parity) : "memory");
}
__device__ __forceinline__ void cnt_wait(const uint32_t* p, uint32_t target) {
  asm volatile("{\n.reg .pred p;\n.reg .u32 n, v;\nmov.u32 n, 0;\n"
               "LOOP_%=:\nld.relaxed.gpu.global.u32 v, [%0];\nsub.u32 v, v, %1;\nsetp.ge.s32 p, v, 0;\n@p bra DONE_%=;\n"
               "nanosleep.u32 40;\nadd.u32 n, n, 1;\nsetp.lt.u32 p, n, 262144;\n@p bra LOOP_%=;\ntrap;\nDONE_%=:\n}\n" :: "l"(p), "r"(target) : "memory");
}
__device__ __forceinline__ void cnt_signal(uint32_t* p) {
  asm volatile("red.relaxed.gpu.global.add.u32 [%0], 1;" :: "l"(p) : "memory");
}
__device__ __forceinline__ void tma_load_3d(uint32_t dst, const CUtensorMap* tm, uint32_t bar, int c0, int c1, int c2) {
  asm volatile("cp.async.bulk.tensor.3d.shared::cluster.global.mbarrier::complete_tx::bytes [%0], [%1, {%3, %4, %5}], [%2];"
    :: "r"(dst), "l"(tm), "r"(bar), "r"(c0), "r"(c1), "r"(c2) : "memory");
}
__device__ __forceinline__ void tma_store_3d(const CUtensorMap* tm, uint32_t src, int c0, int c1, int c2) {
  asm volatile("cp.async.bulk.tensor.3d.global.shared::cta.bulk_group [%0, {%2, %3, %4}], [%1];" :: "l"(tm), "r"(src), "r"(c0), "r"(c1), "r"(c2) : "memory");
}
__device__ __forceinline__ void bulk_commit() { asm volatile("cp.async.bulk.commit_group;" ::: "memory"); }
__device__ __forceinline__ void bulk_wait_read() { asm volatile("cp.async.bulk.wait_group.read 0;" ::: "memory"); }
__device__ __forceinline__ void bulk_wait_all() { asm volatile("cp.async.bulk.wait_group 0;" ::: "memory"); }
__device__ __forceinline__ void l2_prefetch(const void* p, uint32_t bytes) { asm volatile("cp.async.bulk.prefetch.L2.global [%0], %1;" :: "l"(p), "r"(bytes) : "memory"); }
__device__ __forceinline__ void prefetch_tmap(const CUtensorMap* tm) { asm volatile("prefetch.tensormap [%0];" :: "l"(tm) : "memory"); }
__device__ __forceinline__ void fence_async_smem() { asm volatile("fence.proxy.async.shared::cta;" ::: "memory"); }
__device__ __forceinline__ void wg_fence() { asm volatile("wgmma.fence.sync.aligned;" ::: "memory"); }
__device__ __forceinline__ void wg_commit() { asm volatile("wgmma.commit_group.sync.aligned;" ::: "memory"); }
template<int N> __device__ __forceinline__ void wg_wait() { asm volatile("wgmma.wait_group.sync.aligned %0;" :: "n"(N) : "memory"); }
__device__ __forceinline__ void bar_sync(int id, int n) { asm volatile("bar.sync %0, %1;" :: "r"(id), "r"(n) : "memory"); }
__device__ __forceinline__ void bar_arrive(int id, int n) { asm volatile("bar.arrive %0, %1;" :: "r"(id), "r"(n) : "memory"); }
__device__ __forceinline__ float ex2(float x) { float y; asm("ex2.approx.ftz.f32 %0, %1;" : "=f"(y) : "f"(x)); return y; }
__device__ __forceinline__ float tanh_fast(float x) { float y; asm("tanh.approx.f32 %0, %1;" : "=f"(y) : "f"(x)); return y; }
__device__ __forceinline__ uint32_t pack_bf16(float lo, float hi) { uint32_t r; asm("cvt.rn.bf16x2.f32 %0, %1, %2;" : "=r"(r) : "f"(hi), "f"(lo)); return r; }
__device__ __forceinline__ uint32_t bmul2(uint32_t a, uint32_t b) { uint32_t d; asm("mul.rn.bf16x2 %0, %1, %2;" : "=r"(d) : "r"(a), "r"(b)); return d; }
__device__ __forceinline__ uint32_t bfma2(uint32_t a, uint32_t b, uint32_t c) { uint32_t d; asm("fma.rn.bf16x2 %0, %1, %2, %3;" : "=r"(d) : "r"(a), "r"(b), "r"(c)); return d; }
__device__ __forceinline__ float bf_lo(uint32_t u) { return __uint_as_float(u << 16); }
__device__ __forceinline__ float bf_hi(uint32_t u) { return __uint_as_float(u & 0xffff0000u); }
__device__ __forceinline__ void ldsm_x4(uint32_t addr, uint32_t& r0, uint32_t& r1, uint32_t& r2, uint32_t& r3) {
  asm volatile("ldmatrix.sync.aligned.m8n8.x4.shared.b16 {%0,%1,%2,%3}, [%4];" : "=r"(r0), "=r"(r1), "=r"(r2), "=r"(r3) : "r"(addr) : "memory");
}
__device__ __forceinline__ void stsm_x4(uint32_t addr, uint32_t r0, uint32_t r1, uint32_t r2, uint32_t r3) {
  asm volatile("stmatrix.sync.aligned.m8n8.x4.shared.b16 [%0], {%1,%2,%3,%4};" :: "r"(addr), "r"(r0), "r"(r1), "r"(r2), "r"(r3) : "memory");
}
__device__ __forceinline__ void sts128(uint32_t addr, uint4 v) { asm volatile("st.shared.v4.b32 [%0], {%1,%2,%3,%4};" :: "r"(addr), "r"(v.x), "r"(v.y), "r"(v.z), "r"(v.w) : "memory"); }
__device__ __forceinline__ uint4 lds128(uint32_t addr) { uint4 v; asm volatile("ld.shared.v4.b32 {%0,%1,%2,%3}, [%4];" : "=r"(v.x), "=r"(v.y), "=r"(v.z), "=r"(v.w) : "r"(addr) : "memory"); return v; }
__device__ __forceinline__ void sts64f(uint32_t addr, float a, float b) { asm volatile("st.shared.v2.f32 [%0], {%1,%2};" :: "r"(addr), "f"(a), "f"(b) : "memory"); }
__device__ __forceinline__ float2 lds64f(uint32_t addr) { float2 v; asm volatile("ld.shared.v2.f32 {%0,%1}, [%2];" : "=f"(v.x), "=f"(v.y) : "r"(addr) : "memory"); return v; }
__device__ __forceinline__ uint32_t dlo(uint32_t addr, uint32_t lbo) { return ((addr & 0x3FFFF) >> 4) | ((lbo >> 4) << 16); }

template<int SD> __device__ __forceinline__ void wg_ss_n128_tb1(float (&d)[64], uint32_t da, uint32_t db) {
  asm volatile("{\n.reg .b64 da, db;\nmov.b64 da, {%64, 0x40000040};\nmov.b64 db, {%65, 0x40000040};\n"
    "wgmma.mma_async.sync.aligned.m64n128k16.f32.bf16.bf16 {%0, %1, %2, %3, %4, %5, %6, %7, %8, %9, %10, %11, %12, %13, %14, %15, %16, %17, %18, %19, %20, %21, %22, %23, %24, %25, %26, %27, %28, %29, %30, %31, %32, %33, %34, %35, %36, %37, %38, %39, %40, %41, %42, %43, %44, %45, %46, %47, %48, %49, %50, %51, %52, %53, %54, %55, %56, %57, %58, %59, %60, %61, %62, %63}, da, db, %66, 1, 1, 0, 1;\n}\n"
    : "+f"(d[0]), "+f"(d[1]), "+f"(d[2]), "+f"(d[3]), "+f"(d[4]), "+f"(d[5]), "+f"(d[6]), "+f"(d[7]), "+f"(d[8]), "+f"(d[9]), "+f"(d[10]), "+f"(d[11]), "+f"(d[12]), "+f"(d[13]), "+f"(d[14]), "+f"(d[15]), "+f"(d[16]), "+f"(d[17]), "+f"(d[18]), "+f"(d[19]), "+f"(d[20]), "+f"(d[21]), "+f"(d[22]), "+f"(d[23]), "+f"(d[24]), "+f"(d[25]), "+f"(d[26]), "+f"(d[27]), "+f"(d[28]), "+f"(d[29]), "+f"(d[30]), "+f"(d[31]), "+f"(d[32]), "+f"(d[33]), "+f"(d[34]), "+f"(d[35]), "+f"(d[36]), "+f"(d[37]), "+f"(d[38]), "+f"(d[39]), "+f"(d[40]), "+f"(d[41]), "+f"(d[42]), "+f"(d[43]), "+f"(d[44]), "+f"(d[45]), "+f"(d[46]), "+f"(d[47]), "+f"(d[48]), "+f"(d[49]), "+f"(d[50]), "+f"(d[51]), "+f"(d[52]), "+f"(d[53]), "+f"(d[54]), "+f"(d[55]), "+f"(d[56]), "+f"(d[57]), "+f"(d[58]), "+f"(d[59]), "+f"(d[60]), "+f"(d[61]), "+f"(d[62]), "+f"(d[63])
    : "r"(da), "r"(db), "n"(SD));
}
template<int SD> __device__ __forceinline__ void wg_rs_n128_tb1(float (&d)[64], uint32_t a0, uint32_t a1, uint32_t a2, uint32_t a3, uint32_t db) {
  asm volatile("{\n.reg .b64 db;\nmov.b64 db, {%68, 0x40000040};\n"
    "wgmma.mma_async.sync.aligned.m64n128k16.f32.bf16.bf16 {%0, %1, %2, %3, %4, %5, %6, %7, %8, %9, %10, %11, %12, %13, %14, %15, %16, %17, %18, %19, %20, %21, %22, %23, %24, %25, %26, %27, %28, %29, %30, %31, %32, %33, %34, %35, %36, %37, %38, %39, %40, %41, %42, %43, %44, %45, %46, %47, %48, %49, %50, %51, %52, %53, %54, %55, %56, %57, %58, %59, %60, %61, %62, %63}, {%64, %65, %66, %67}, db, %69, 1, 1, 1;\n}\n"
    : "+f"(d[0]), "+f"(d[1]), "+f"(d[2]), "+f"(d[3]), "+f"(d[4]), "+f"(d[5]), "+f"(d[6]), "+f"(d[7]), "+f"(d[8]), "+f"(d[9]), "+f"(d[10]), "+f"(d[11]), "+f"(d[12]), "+f"(d[13]), "+f"(d[14]), "+f"(d[15]), "+f"(d[16]), "+f"(d[17]), "+f"(d[18]), "+f"(d[19]), "+f"(d[20]), "+f"(d[21]), "+f"(d[22]), "+f"(d[23]), "+f"(d[24]), "+f"(d[25]), "+f"(d[26]), "+f"(d[27]), "+f"(d[28]), "+f"(d[29]), "+f"(d[30]), "+f"(d[31]), "+f"(d[32]), "+f"(d[33]), "+f"(d[34]), "+f"(d[35]), "+f"(d[36]), "+f"(d[37]), "+f"(d[38]), "+f"(d[39]), "+f"(d[40]), "+f"(d[41]), "+f"(d[42]), "+f"(d[43]), "+f"(d[44]), "+f"(d[45]), "+f"(d[46]), "+f"(d[47]), "+f"(d[48]), "+f"(d[49]), "+f"(d[50]), "+f"(d[51]), "+f"(d[52]), "+f"(d[53]), "+f"(d[54]), "+f"(d[55]), "+f"(d[56]), "+f"(d[57]), "+f"(d[58]), "+f"(d[59]), "+f"(d[60]), "+f"(d[61]), "+f"(d[62]), "+f"(d[63])
    : "r"(a0), "r"(a1), "r"(a2), "r"(a3), "r"(db), "n"(SD));
}
template<int SD> __device__ __forceinline__ void wg_ss_n64_tb1(float (&d)[32], uint32_t da, uint32_t db) {
  asm volatile("{\n.reg .b64 da, db;\nmov.b64 da, {%32, 0x40000040};\nmov.b64 db, {%33, 0x40000040};\n"
    "wgmma.mma_async.sync.aligned.m64n64k16.f32.bf16.bf16 {%0, %1, %2, %3, %4, %5, %6, %7, %8, %9, %10, %11, %12, %13, %14, %15, %16, %17, %18, %19, %20, %21, %22, %23, %24, %25, %26, %27, %28, %29, %30, %31}, da, db, %34, 1, 1, 0, 1;\n}\n"
    : "+f"(d[0]), "+f"(d[1]), "+f"(d[2]), "+f"(d[3]), "+f"(d[4]), "+f"(d[5]), "+f"(d[6]), "+f"(d[7]), "+f"(d[8]), "+f"(d[9]), "+f"(d[10]), "+f"(d[11]), "+f"(d[12]), "+f"(d[13]), "+f"(d[14]), "+f"(d[15]), "+f"(d[16]), "+f"(d[17]), "+f"(d[18]), "+f"(d[19]), "+f"(d[20]), "+f"(d[21]), "+f"(d[22]), "+f"(d[23]), "+f"(d[24]), "+f"(d[25]), "+f"(d[26]), "+f"(d[27]), "+f"(d[28]), "+f"(d[29]), "+f"(d[30]), "+f"(d[31])
    : "r"(da), "r"(db), "n"(SD));
}
template<int SD> __device__ __forceinline__ void wg_ss_n80_tb0(float (&d)[40], uint32_t da, uint32_t db) {
  asm volatile("{\n.reg .b64 da, db;\nmov.b64 da, {%40, 0x40000040};\nmov.b64 db, {%41, 0x40000040};\n"
    "wgmma.mma_async.sync.aligned.m64n80k16.f32.bf16.bf16 {%0, %1, %2, %3, %4, %5, %6, %7, %8, %9, %10, %11, %12, %13, %14, %15, %16, %17, %18, %19, %20, %21, %22, %23, %24, %25, %26, %27, %28, %29, %30, %31, %32, %33, %34, %35, %36, %37, %38, %39}, da, db, %42, 1, 1, 0, 0;\n}\n"
    : "+f"(d[0]), "+f"(d[1]), "+f"(d[2]), "+f"(d[3]), "+f"(d[4]), "+f"(d[5]), "+f"(d[6]), "+f"(d[7]), "+f"(d[8]), "+f"(d[9]), "+f"(d[10]), "+f"(d[11]), "+f"(d[12]), "+f"(d[13]), "+f"(d[14]), "+f"(d[15]), "+f"(d[16]), "+f"(d[17]), "+f"(d[18]), "+f"(d[19]), "+f"(d[20]), "+f"(d[21]), "+f"(d[22]), "+f"(d[23]), "+f"(d[24]), "+f"(d[25]), "+f"(d[26]), "+f"(d[27]), "+f"(d[28]), "+f"(d[29]), "+f"(d[30]), "+f"(d[31]), "+f"(d[32]), "+f"(d[33]), "+f"(d[34]), "+f"(d[35]), "+f"(d[36]), "+f"(d[37]), "+f"(d[38]), "+f"(d[39])
    : "r"(da), "r"(db), "n"(SD));
}
template<int SD> __device__ __forceinline__ void wg_rs_n64_tb1(float (&d)[32], uint32_t a0, uint32_t a1, uint32_t a2, uint32_t a3, uint32_t db) {
  asm volatile("{\n.reg .b64 db;\nmov.b64 db, {%36, 0x40000040};\n"
    "wgmma.mma_async.sync.aligned.m64n64k16.f32.bf16.bf16 {%0, %1, %2, %3, %4, %5, %6, %7, %8, %9, %10, %11, %12, %13, %14, %15, %16, %17, %18, %19, %20, %21, %22, %23, %24, %25, %26, %27, %28, %29, %30, %31}, {%32, %33, %34, %35}, db, %37, 1, 1, 1;\n}\n"
    : "+f"(d[0]), "+f"(d[1]), "+f"(d[2]), "+f"(d[3]), "+f"(d[4]), "+f"(d[5]), "+f"(d[6]), "+f"(d[7]), "+f"(d[8]), "+f"(d[9]), "+f"(d[10]), "+f"(d[11]), "+f"(d[12]), "+f"(d[13]), "+f"(d[14]), "+f"(d[15]), "+f"(d[16]), "+f"(d[17]), "+f"(d[18]), "+f"(d[19]), "+f"(d[20]), "+f"(d[21]), "+f"(d[22]), "+f"(d[23]), "+f"(d[24]), "+f"(d[25]), "+f"(d[26]), "+f"(d[27]), "+f"(d[28]), "+f"(d[29]), "+f"(d[30]), "+f"(d[31])
    : "r"(a0), "r"(a1), "r"(a2), "r"(a3), "r"(db), "n"(SD));
}

constexpr int RING = 5;
constexpr uint32_t STAGE = 32768;
constexpr uint32_t OFF_X = 32768, OFF_W = 65536, OFF_MISC = OFF_W + RING * STAGE;
constexpr int SMEM_BYTES = OFF_MISC + 256 + 1024 + 1024;

struct Ctx {
  uint32_t sA, sX, sW, full, empty, stats;
  uint32_t frag;
  uint32_t rsw;
  uint32_t hi;
  int wg, tid, lane;
  int pk;
  uint32_t dry;
};
__device__ __forceinline__ uint32_t stage_wait(const Ctx& c, int n) {
  const int q = n / RING, s = n - q * RING;
  if (c.tid == 0) PROF_STG(n + c.pk, 1);
  mbar_wait(c.full + 8 * s, (q | c.dry) & 1);
  if (c.tid == 0) PROF_STG(n + c.pk, 2);
  return dlo(c.sW + s * STAGE, 0);
}
__device__ __forceinline__ void stage_release(const Ctx& c, int n) {
  const int s = n % RING;
  if (c.tid == 0) { mbar_arrive(c.empty + 8 * s); PROF_STG(n + c.pk, 3); }
}
__device__ __forceinline__ void turn_begin(const Ctx& c) { bar_sync(5 + c.wg, 256); }
__device__ __forceinline__ void turn_end(const Ctx& c) { bar_arrive(5 + (c.wg ^ 1), 256); }
template<int FIRST, int LAST> __device__ __forceinline__ void piece_ss(const Ctx& c, float (&acc)[64], uint32_t dA, uint32_t dB) {
  dB += (16384 >> 4) << 16;
  wg_ss_n128_tb1<FIRST ? 0 : 1>(acc, dA, dB);
#pragma unroll
  for (int kk = 1; kk < 8; kk++) {
    wg_ss_n128_tb1<1>(acc, dA + (kk >> 2) * 512 + (kk & 3) * 2, dB + kk * 128);
  }
  if (LAST) turn_end(c);
}
__device__ __forceinline__ void ff_g1(const Ctx& c, float (&h)[32], uint32_t dA, uint32_t dB) {
  wg_ss_n64_tb1<0>(h, dA, dB);
#pragma unroll
  for (int kk = 1; kk < 16; kk++) {
    wg_ss_n64_tb1<1>(h, dA + (kk >> 2) * 512 + (kk & 3) * 2, dB + kk * 128);
  }
}
__device__ __forceinline__ void ff_g2(float (&acc)[64], const uint32_t (&P)[16], uint32_t dB, int half) {
  dB += ((8192 >> 4) << 16) + half * 1024;
#pragma unroll
  for (int kk = 0; kk < 4; kk++) wg_rs_n128_tb1<1>(acc, P[4 * kk], P[4 * kk + 1], P[4 * kk + 2], P[4 * kk + 3], dB + kk * 128);
}
struct NoHook { __device__ __forceinline__ void operator()() const {} };
template<int FIRST, class Hook = NoHook> __device__ __forceinline__ void gemm256(const Ctx& c, float (&acc)[64], int n, Hook hook = Hook()) {
  const uint32_t dA = dlo(c.sA, 16);
  uint32_t b = stage_wait(c, n);
  turn_begin(c);
  wg_fence(); piece_ss<FIRST, 0>(c, acc, dA, b); wg_commit();
  b = stage_wait(c, n + 1);
  wg_fence(); piece_ss<0, 1>(c, acc, dA + 1024, b); wg_commit();
  hook();
  wg_wait<1>(); stage_release(c, n);
  wg_wait<0>(); stage_release(c, n + 1);
}
__device__ __forceinline__ uint32_t frag_addr(const Ctx& c, uint32_t tile, int j) {
  return tile + (2 * c.wg + (j >> 2)) * 8192 + c.frag + ((((j & 3) * 2 + c.hi) ^ c.rsw) << 4);
}
__device__ __forceinline__ void load_half(const Ctx& c, uint32_t tile, float (&v)[64]) {
#pragma unroll
  for (int j = 0; j < 8; j++) {
    uint32_t r0, r1, r2, r3;
    ldsm_x4(frag_addr(c, tile, j), r0, r1, r2, r3);
    v[8 * j] = bf_lo(r0); v[8 * j + 1] = bf_hi(r0); v[8 * j + 2] = bf_lo(r1); v[8 * j + 3] = bf_hi(r1);
    v[8 * j + 4] = bf_lo(r2); v[8 * j + 5] = bf_hi(r2); v[8 * j + 6] = bf_lo(r3); v[8 * j + 7] = bf_hi(r3);
  }
}
__device__ __forceinline__ void store_half(const Ctx& c, uint32_t tile, const float (&v)[64], float a0, float b0, float a1, float b1) {
#pragma unroll
  for (int j = 0; j < 8; j++)
    stsm_x4(frag_addr(c, tile, j),
            pack_bf16(fmaf(v[8 * j], a0, b0), fmaf(v[8 * j + 1], a0, b0)), pack_bf16(fmaf(v[8 * j + 2], a1, b1), fmaf(v[8 * j + 3], a1, b1)),
            pack_bf16(fmaf(v[8 * j + 4], a0, b0), fmaf(v[8 * j + 5], a0, b0)), pack_bf16(fmaf(v[8 * j + 6], a1, b1), fmaf(v[8 * j + 7], a1, b1)));
}
__device__ __forceinline__ void store_half_raw(const Ctx& c, uint32_t tile, const float (&v)[64]) {
#pragma unroll
  for (int j = 0; j < 8; j++)
    stsm_x4(frag_addr(c, tile, j), pack_bf16(v[8 * j], v[8 * j + 1]), pack_bf16(v[8 * j + 2], v[8 * j + 3]),
            pack_bf16(v[8 * j + 4], v[8 * j + 5]), pack_bf16(v[8 * j + 6], v[8 * j + 7]));
}
__device__ __forceinline__ void ln_stats(const Ctx& c, const float (&v)[64], float scale, float& a0, float& b0, float& a1, float& b1) {
  float s0 = 0.f, s1 = 0.f, q0 = 0.f, q1 = 0.f, s2 = 0.f, s3 = 0.f, q2 = 0.f, q3 = 0.f;
#pragma unroll
  for (int i = 0; i < 16; i++) {
    s0 += v[4 * i]; q0 = fmaf(v[4 * i], v[4 * i], q0);
    s2 += v[4 * i + 1]; q2 = fmaf(v[4 * i + 1], v[4 * i + 1], q2);
    s1 += v[4 * i + 2]; q1 = fmaf(v[4 * i + 2], v[4 * i + 2], q1);
    s3 += v[4 * i + 3]; q3 = fmaf(v[4 * i + 3], v[4 * i + 3], q3);
  }
  s0 += s2; q0 += q2; s1 += s3; q1 += q3;
  s0 += __shfl_xor_sync(0xffffffff, s0, 1); q0 += __shfl_xor_sync(0xffffffff, q0, 1);
  s1 += __shfl_xor_sync(0xffffffff, s1, 1); q1 += __shfl_xor_sync(0xffffffff, q1, 1);
  s0 += __shfl_xor_sync(0xffffffff, s0, 2); q0 += __shfl_xor_sync(0xffffffff, q0, 2);
  s1 += __shfl_xor_sync(0xffffffff, s1, 2); q1 += __shfl_xor_sync(0xffffffff, q1, 2);
  const uint32_t row = (c.tid >> 5) * 16 + (c.lane >> 2);
  if ((c.lane & 3) == 0) {
    sts64f(c.stats + c.wg * 512 + row * 8, s0, q0);
    sts64f(c.stats + c.wg * 512 + (row + 8) * 8, s1, q1);
  }
  bar_sync(1, 256);
  const float2 o0 = lds64f(c.stats + (c.wg ^ 1) * 512 + row * 8), o1 = lds64f(c.stats + (c.wg ^ 1) * 512 + (row + 8) * 8);
  const float m0 = (s0 + o0.x) * (1.f / 256.f), m1 = (s1 + o1.x) * (1.f / 256.f);
  const float var0 = fmaxf(fmaf(-m0, m0, (q0 + o0.y) * (1.f / 256.f)), 0.f), var1 = fmaxf(fmaf(-m1, m1, (q1 + o1.y) * (1.f / 256.f)), 0.f);
  a0 = rsqrtf(var0 + 1e-5f) * scale; a1 = rsqrtf(var1 + 1e-5f) * scale;
  b0 = -m0 * a0; b1 = -m1 * a1;
}
__device__ __forceinline__ float silu_half(float h) { return fmaf(h, tanh_fast(h), h); }
__device__ __forceinline__ float silu_quarter(float h) { const float q = 0.5f * h; return fmaf(q, tanh_fast(h), q); }
__device__ __forceinline__ void silu_inplace(float (&h)[32]) {
#pragma unroll
  for (int i = 0; i < 32; i++) h[i] = silu_quarter(h[i]);
}
__device__ __forceinline__ void pack_p(const float (&h)[32], uint32_t (&P)[16]) {
#pragma unroll
  for (int i = 0; i < 16; i++) asm volatile("cvt.rn.bf16x2.f32 %0, %1, %2;" : "=r"(P[i]) : "f"(h[2 * i + 1]), "f"(h[2 * i]));
}
__device__ __forceinline__ void ff_block(const Ctx& c, int n0, float (&own)[64]) {
  float oth[64], h[32];
  uint32_t P[16];
#pragma unroll
  for (int i = 0; i < 64; i++) oth[i] = 0.f;
  const uint32_t dA = dlo(c.sA, 16);
  {
    const uint32_t b = stage_wait(c, n0 + c.wg);
    turn_begin(c);
    wg_fence(); ff_g1(c, h, dA, b); wg_commit();
    turn_end(c);
    wg_wait<0>(); stage_release(c, n0 + c.wg);
    silu_inplace(h);
  }
#pragma unroll 1
  for (int it = c.dry ? 7 : 1; it < 8; it++) {
    const int n = n0 + 4 * it - 2 + 2 * c.wg;
    pack_p(h, P);
    uint32_t b = stage_wait(c, n);
    turn_begin(c);
    wg_fence(); ff_g1(c, h, dA, b); wg_commit();
    b = stage_wait(c, n + 1);
    wg_fence(); ff_g2(own, P, b, c.wg); ff_g2(oth, P, b, c.wg ^ 1); wg_commit();
    turn_end(c);
    wg_wait<1>(); stage_release(c, n);
    silu_inplace(h);
    wg_wait<0>(); stage_release(c, n + 1);
  }
  pack_p(h, P);
  if (c.wg == 0) bar_arrive(2, 256);
  {
    const int n = n0 + 30 + c.wg;
    const uint32_t b = stage_wait(c, n);
    turn_begin(c);
    wg_fence(); ff_g2(oth, P, b, c.wg ^ 1); wg_commit();
    ff_g2(own, P, b, c.wg); wg_commit();
    turn_end(c);
    wg_wait<1>();
    if (c.wg == 1) bar_sync(2, 256);
    const uint32_t e = (c.wg == 0 ? c.sX : c.sA) + c.tid * 16;
#pragma unroll
    for (int i = 0; i < 16; i++)
      sts128(e + i * 2048, make_uint4(__float_as_uint(oth[4 * i]), __float_as_uint(oth[4 * i + 1]), __float_as_uint(oth[4 * i + 2]), __float_as_uint(oth[4 * i + 3])));
    wg_wait<0>(); stage_release(c, n);
  }
  bar_sync(1, 256);
  const uint32_t e = (c.wg == 0 ? c.sA : c.sX) + c.tid * 16;
#pragma unroll
  for (int i = 0; i < 16; i++) {
    const uint4 u = lds128(e + i * 2048);
    own[4 * i] += __uint_as_float(u.x); own[4 * i + 1] += __uint_as_float(u.y);
    own[4 * i + 2] += __uint_as_float(u.z); own[4 * i + 3] += __uint_as_float(u.w);
  }
}
struct Maps { CUtensorMap X, W1a, W1b, Wqkv, QKVst, Q, KV, Wo, Pw1, Pw2, W2a, W2b, Out; };
constexpr int NA = 44;
constexpr int NC = 45;
__constant__ uint16_t c_stage[92] = {0x1, 0x11, 0x21, 0x2, 0x31, 0x102, 0x41, 0x202, 0x51, 0x302, 0x61, 0x402, 0x71, 0x502, 0x81, 0x602, 0x91, 0x702, 0xa1, 0x802, 0xb1, 0x902, 0xc1, 0xa02, 0xd1, 0xb02, 0xe1, 0xc02, 0xf1, 0xd02, 0xe02, 0xf02, 0x3, 0x203, 0x23, 0x223, 0x43, 0x243, 0x63, 0x263, 0x83, 0x283, 0xa3, 0x2a3, 0x7, 0x207, 0x27, 0x227, 0x8, 0x208, 0x2008, 0x2208, 0x1008, 0x1208, 0x3008, 0x3208, 0x9, 0x29, 0x209, 0x229, 0xa, 0x1a, 0x2a, 0xb, 0x3a, 0x10b, 0x4a, 0x20b, 0x5a, 0x30b, 0x6a, 0x40b, 0x7a, 0x50b, 0x8a, 0x60b, 0x9a, 0x70b, 0xaa, 0x80b, 0xba, 0x90b, 0xca, 0xa0b, 0xda, 0xb0b, 0xea, 0xc0b, 0xfa, 0xd0b, 0xe0b, 0xf0b};
__device__ __forceinline__ void load_stage(uint32_t dst, uint32_t bar, const Maps& tm, int n) {
  const uint32_t e = c_stage[n - (n > NA)];
  mbar_expect_tx(bar, STAGE);
  tma_load_3d(dst, &tm.X + (e & 15), bar, (e >> 12) * 64, ((e >> 8) & 15) * 64, (e >> 4) & 15);
}
__device__ __forceinline__ void produce(uint32_t sW, uint32_t full, const Maps& tm, int n0, int n1) {
  uint32_t s = n0 % RING, ph = ((n0 / RING) & 1) ^ 1;
#pragma unroll 1
  for (int n = n0; n < n1; n++) {
    mbar_wait(full + 8 * RING + 8 * s, ph);
    PROF_STG(n, 0);
    load_stage(sW + s * STAGE, full + 8 * s, tm, n);
    if (++s == RING) { s = 0; ph ^= 1; }
  }
}
__device__ __forceinline__ Ctx make_ctx(uint32_t base, uint32_t dry, int pk = 0) {
  Ctx c; c.pk = pk; c.dry = dry;
  c.sA = base; c.sX = base + OFF_X; c.sW = base + OFF_W;
  c.full = base + OFF_MISC; c.empty = c.full + 8 * RING; c.stats = base + OFF_MISC + 256;
  c.wg = __shfl_sync(0xffffffff, (int)(threadIdx.x >> 7), 0);
  c.tid = threadIdx.x & 127; c.lane = threadIdx.x & 31;
  const uint32_t r = (c.tid >> 5) * 16 + (c.lane & 7) + ((c.lane >> 3) & 1) * 8;
  c.frag = r * 128; c.rsw = r & 7; c.hi = c.lane >> 4;
  return c;
}

constexpr int NSTG = 4;
constexpr int KVB = 160 * 128;
constexpr int NKV = T_ / 160;
static_assert(NSTG * 2 * KVB == RING * STAGE, "the K/V ring reuses the weight ring");

struct AttCtx { uint32_t sKV, full, empty, dry, wfull; const Maps* tm; int h, b, wg; };
__device__ __forceinline__ int kv_slot(int i) { return (i + 3) & 3; }
__device__ __forceinline__ void att_load(const AttCtx& a, int i, int v) {
  const int s = i & 3;
  mbar_expect_tx(a.full + 8 * (s + v * NSTG), KVB);
  tma_load_3d(a.sKV + kv_slot(i) * 2 * KVB + v * KVB, &a.tm->KV, a.full + 8 * (s + v * NSTG), 256 + v * 256 + a.h * 64, i * 160, a.b);
}
__device__ __forceinline__ void att_load_stage(const AttCtx& a, int i) { att_load(a, i, 0); att_load(a, i, 1); }
__device__ __forceinline__ void att_init_bars(const AttCtx& a) {
  for (int i = 0; i < NSTG; i++) { mbar_init(a.full + 8 * i, 1); mbar_init(a.full + 8 * (NSTG + i), 1); mbar_init(a.empty + 8 * i, 4); }
}
__device__ __forceinline__ void att_qk(float (&S)[40], uint32_t dQ, uint32_t kd) {
  wg_ss_n80_tb0<0>(S, dQ, kd);
#pragma unroll
  for (int kk = 1; kk < 4; kk++) wg_ss_n80_tb0<1>(S, dQ + kk * 2, kd + kk * 2);
}
__device__ __forceinline__ void att_pv(float (&O)[32], const uint32_t (&P)[20], uint32_t vd) {
#pragma unroll
  for (int kk = 0; kk < 5; kk++) wg_rs_n64_tb1<1>(O, P[kk * 4], P[kk * 4 + 1], P[kk * 4 + 2], P[kk * 4 + 3], vd + kk * 128);
}
template<bool SAFE>
__device__ __forceinline__ void att_softmax(const float (&S)[40], uint32_t (&P)[20], float (&O)[32], float& m0, float& m1, float& l0, float& l1) {
  if (SAFE) {
    float x0 = fmaxf(S[0], S[1]), x1 = fmaxf(S[2], S[3]);
#pragma unroll
    for (int i = 1; i < 10; i++) { x0 = fmaxf(x0, fmaxf(S[4 * i], S[4 * i + 1])); x1 = fmaxf(x1, fmaxf(S[4 * i + 2], S[4 * i + 3])); }
    x0 = fmaxf(x0, __shfl_xor_sync(0xffffffff, x0, 1)); x1 = fmaxf(x1, __shfl_xor_sync(0xffffffff, x1, 1));
    x0 = fmaxf(x0, __shfl_xor_sync(0xffffffff, x0, 2)); x1 = fmaxf(x1, __shfl_xor_sync(0xffffffff, x1, 2));
    const float n0 = fmaxf(m0, x0), n1 = fmaxf(m1, x1);
    const float f0 = ex2(m0 - n0), f1 = ex2(m1 - n1);
    m0 = n0; m1 = n1; l0 *= f0; l1 *= f1;
#pragma unroll
    for (int i = 0; i < 8; i++) { O[4 * i] *= f0; O[4 * i + 1] *= f0; O[4 * i + 2] *= f1; O[4 * i + 3] *= f1; }
  }
#pragma unroll
  for (int i = 0; i < 10; i++) {
    float p0, p1, p2, p3;
    if (SAFE) { p0 = ex2(S[4 * i] - m0); p1 = ex2(S[4 * i + 1] - m0); p2 = ex2(S[4 * i + 2] - m1); p3 = ex2(S[4 * i + 3] - m1); }
    else { p0 = ex2(S[4 * i]); p1 = ex2(S[4 * i + 1]); p2 = ex2(S[4 * i + 2]); p3 = ex2(S[4 * i + 3]); }
    l0 += p0 + p1; l1 += p2 + p3;
    P[2 * i] = pack_bf16(p0, p1); P[2 * i + 1] = pack_bf16(p2, p3);
  }
}
template<bool SAFE>
__device__ __forceinline__ void att_refill(const AttCtx& a, int it) {
  if ((threadIdx.x & 127) == 0) {
    mbar_arrive(a.empty + 8 * (it & 3));
    if (a.wg == (it & 3) && it >= 1 && !a.dry) {
      const bool kv = it - 1 + NSTG < NKV;
      if (kv || (!SAFE && a.wfull)) {
        mbar_wait(a.empty + 8 * ((it - 1) & 3), ((it - 1) >> 2) & 1);
        if (kv) att_load_stage(a, it - 1 + NSTG);
        else load_stage(a.sKV + (it - 22) * STAGE, a.wfull + 8 * (it - 22), *a.tm, NC + it - 22);
      }
    }
  }
  __syncwarp();
}
constexpr uint32_t KV_STG = 2 * KVB / 16, KV_VOFF = KVB / 16, KV_HALF = 80 * 128 / 16;
template<bool SAFE>
__device__ __forceinline__ void att_pass(const AttCtx& a, uint32_t dQ, float (&O)[32], float& l0, float& l1) {
  float S[40];
  uint32_t P[20];
  float m0 = -INFINITY, m1 = -INFINITY;
  l0 = 0.f; l1 = 0.f;
#pragma unroll
  for (int i = 0; i < 32; i++) O[i] = 0.f;
  const uint32_t dKV = dlo(a.sKV, 16);
  if (SAFE) {
#pragma unroll 1
    for (int j = 0; j < 2 * NKV; j++) {
      const int it = j >> 1, s = it & 3;
      const uint32_t kb = dKV + kv_slot(it) * KV_STG + (j & 1) * KV_HALF;
      mbar_wait(a.full + 8 * s, (it >> 2) & 1);
      wg_fence(); att_qk(S, dQ, kb); wg_commit(); wg_wait<0>();
      att_softmax<true>(S, P, O, m0, m1, l0, l1);
      mbar_wait(a.full + 8 * (NSTG + s), (it >> 2) & 1);
      wg_fence(); att_pv(O, P, kb + KV_VOFF); wg_commit(); wg_wait<0>();
      if (j & 1) att_refill<true>(a, it);
    }
  } else {
    mbar_wait(a.full, a.dry);
    wg_fence(); att_qk(S, dQ, dKV + 3 * KV_STG); wg_commit(); wg_wait<0>();
    att_softmax<false>(S, P, O, m0, m1, l0, l1);
    mbar_wait(a.full + 8 * NSTG, a.dry);
    wg_fence(); att_pv(O, P, dKV + 3 * KV_STG + KV_VOFF); att_qk(S, dQ, dKV + 3 * KV_STG + KV_HALF); wg_commit(); wg_wait<0>();
#pragma unroll 1
    for (int it = a.dry ? NKV - 2 : 0; it < NKV - 1; it++) {
      const int sn = (it + 1) & 3;
      const uint32_t kb = dKV + kv_slot(it) * KV_STG, kn = dKV + kv_slot(it + 1) * KV_STG, par = (((it + 1) >> 2) | a.dry) & 1;
      att_softmax<false>(S, P, O, m0, m1, l0, l1);
      mbar_wait(a.full + 8 * sn, par);
      wg_fence(); att_pv(O, P, kb + KV_VOFF + KV_HALF); att_qk(S, dQ, kn); wg_commit(); wg_wait<0>();
      att_refill<false>(a, it);
      att_softmax<false>(S, P, O, m0, m1, l0, l1);
      mbar_wait(a.full + 8 * (NSTG + sn), par);
      wg_fence(); att_pv(O, P, kn + KV_VOFF); att_qk(S, dQ, kn + KV_HALF); wg_commit(); wg_wait<0>();
    }
    att_softmax<false>(S, P, O, m0, m1, l0, l1);
    wg_fence(); att_pv(O, P, dKV + 3 * KV_STG + KV_VOFF + KV_HALF); wg_commit(); wg_wait<0>();
  }
  l0 += __shfl_xor_sync(0xffffffff, l0, 1); l1 += __shfl_xor_sync(0xffffffff, l1, 1);
  l0 += __shfl_xor_sync(0xffffffff, l0, 2); l1 += __shfl_xor_sync(0xffffffff, l1, 2);
}

struct Wptrs { const void* p[8]; uint32_t bytes[8]; };

constexpr uint32_t B_FULL = 0, B_EMPTY = 8 * RING, B_X = 16 * RING, B_ADONE = B_X + 8, B_Q = B_X + 16, B_EP = B_X + 24, B_ATT = B_X + 32;

__global__ void __launch_bounds__(512, 1) conformer_kernel(const __grid_constant__ Maps tm, const __grid_constant__ Wptrs wp, const uint4* __restrict__ dw) {
  extern __shared__ uint8_t smem_raw[];
  const uint32_t base = (smem_u32(smem_raw) + 1023) & ~1023u, misc = base + OFF_MISC;
  const uint32_t dry = blockIdx.x >= 128;
  const int tile = dry ? 0 : blockIdx.x;
  const bool has_tile = dry ? blockIdx.x == 128 : tile < NTILE;
  const int wg = __shfl_sync(0xffffffff, (int)(threadIdx.x >> 7), 0);
  AttCtx a;
  a.sKV = base + OFF_W; a.full = misc + B_ATT; a.empty = a.full + 16 * NSTG; a.tm = &tm;
  a.h = (blockIdx.x >> 4) & 3; a.b = (blockIdx.x >> 6) & 1; a.wg = wg; a.dry = dry; a.wfull = has_tile ? misc + B_FULL : 0;
  const int qt = blockIdx.x & 15;

  if (threadIdx.x == 256) {
    mbar_init(misc + B_X, 1);
    for (int i = 0; i < RING; i++) { mbar_init(misc + B_FULL + 8 * i, 1); mbar_init(misc + B_EMPTY + 8 * i, 1); }
    asm volatile("fence.mbarrier_init.release.cluster;" ::: "memory");
    if (has_tile && !dry) {
      mbar_expect_tx(misc + B_X, 32768);
      tma_load_3d(base + OFF_X, &tm.X, misc + B_X, 0, tile * 64, 0);
#pragma unroll 1
      for (int i = 0; i < RING; i++) load_stage(base + OFF_W + i * STAGE, misc + B_FULL + 8 * i, tm, i);
    }
  } else if (threadIdx.x == 288) {
    mbar_init(misc + B_ADONE, 2);
    mbar_init(misc + B_Q, 1);
    mbar_init(misc + B_EP, 1);
    att_init_bars(a);
    asm volatile("fence.mbarrier_init.release.cluster;" ::: "memory");
  } else if (threadIdx.x >= 320 && threadIdx.x < 333) {
    prefetch_tmap(&tm.X + (threadIdx.x - 320));
  }
  __syncthreads();
  auto get_epoch = [&]() {
    uint32_t e;
    mbar_wait(misc + B_EP, 0);
    asm volatile("ld.shared.u32 %0, [%1];" : "=r"(e) : "r"(misc + 248) : "memory");
    return e;
  };

  if (wg >= 2) {
    asm volatile("setmaxnreg.dec.sync.aligned.u32 24;");
    const uint32_t full = misc + B_FULL;
    if (threadIdx.x == 320) {
      const uint32_t e = atomicAdd(&g_start, 1) / NCTA;
      asm volatile("st.shared.u32 [%0], %1;" :: "r"(misc + 248), "r"(e + 1) : "memory");
      mbar_arrive(misc + B_EP);
    }
    if (dry) {
    } else if (threadIdx.x == 256) {
      if (has_tile) {
        produce(base + OFF_W, full, tm, RING, NA);
        mbar_wait(full + 8 * RING + 8 * 4, 1);
        mbar_arrive(full + 8 * 4); mbar_arrive(full + 8 * RING + 8 * 4);
        mbar_wait(misc + B_ADONE, 0);
      }
      cnt_wait(g_cnt1 + a.b * 64, 126 * get_epoch());
      mbar_expect_tx(misc + B_Q, 32768);
      tma_load_3d(base, &tm.Q, misc + B_Q, a.h * 64, qt * 256, a.b);
      att_load(a, 0, 0);
      mbar_wait(misc + B_Q, 0);
#pragma unroll 1
      for (int i = 1; i < NSTG; i++) att_load(a, i, 0);
    } else if ((threadIdx.x >> 5) == 12) {
      if (has_tile) bar_sync(9, 288);
      if (threadIdx.x == 384) {
        cnt_wait(g_cnt1 + a.b * 64 + 32, 126 * get_epoch());
        att_load(a, 0, 1);
        mbar_wait(a.full + 8 * NSTG, 0);
#pragma unroll 1
        for (int i = 1; i < NSTG; i++) att_load(a, i, 1);
      }
    } else if (has_tile && threadIdx.x >= 288 && threadIdx.x < 296) {
      const int w = threadIdx.x - 288;
      mbar_wait(misc + B_X, 0);
      const uint32_t bytes = wp.bytes[w], per = ((bytes / NTILE) + 127) & ~127u, off = per * tile;
      if (off < bytes) l2_prefetch((const uint8_t*)wp.p[w] + off, min(per, bytes - off));
    } else if (has_tile && threadIdx.x >= 416) {
      mbar_wait(full, 0);
      const int t = threadIdx.x - 416;
#pragma unroll 2
      for (int i = t; i < 2048; i += 96) g_att[tile * 2048 + i] = make_uint4(~0u, ~0u, ~0u, ~0u);
      g_halo[tile * 128 + t] = make_uint4(~0u, ~0u, ~0u, ~0u);
      if (t < 32) g_halo[tile * 128 + 96 + t] = make_uint4(~0u, ~0u, ~0u, ~0u);
    }
    __syncwarp();
    bar_sync(5 + wg, 384);
    asm volatile("setmaxnreg.inc.sync.aligned.u32 128;");
  } else {
    asm volatile("setmaxnreg.inc.sync.aligned.u32 232;");
    if (has_tile) {
      const Ctx c = make_ctx(base, dry);
      if (c.wg == 1) turn_end(c);
      float own[64];
      float a0, b0, a1, b1;
      PROF_MARK(0, 0);
      mbar_wait(misc + B_X, dry);
      PROF_MARK(0, 1);
      load_half(c, c.sX, own);
      ln_stats(c, own, 0.5f, a0, b0, a1, b1);
      store_half(c, c.sA, own, a0, b0, a1, b1);
      fence_async_smem();
      bar_sync(1, 256);
      PROF_MARK(0, 2);
      ff_block(c, 0, own);
      PROF_MARK(0, 3);
      ln_stats(c, own, 1.f, a0, b0, a1, b1);
      store_half(c, c.sA, own, a0, b0, a1, b1);
      fence_async_smem();
      bar_sync(1, 256);
      PROF_MARK(0, 4);
#pragma unroll 1
      for (int cc = dry ? 2 : 0; cc < 3; cc++) {
        float acc[64];
        const int j = 2 * cc + c.wg;
        gemm256<1>(c, acc, 32 + 2 * j, [&]() {
          if (c.tid == 0 && !dry) {
            if (cc == 2) {
              bulk_wait_all();
              if (tile <= 62) cnt_signal(g_cnt1);
              if (tile >= 62) cnt_signal(g_cnt1 + 64);
            } else bulk_wait_read();
          }
          bar_sync(3 + c.wg, 128);
        });
        if (cc == 2 && !dry) { bar_arrive(9, 288); if (c.tid == 0) mbar_arrive(misc + B_ADONE); }
        if (cc == 0) {
#pragma unroll
          for (int i = 0; i < 64; i++) acc[i] *= 0.125f * 1.4426950408889634f;
        }
        store_half_raw(c, c.sX, acc);
        fence_async_smem();
        bar_sync(3 + c.wg, 128);
        if (c.tid == 0 && !dry) { tma_store_3d(&tm.QKVst, c.sX + c.wg * 16384, 0, tile * 64, 2 * j); bulk_commit(); }
      }
      PROF_MARK(0, 5);
      if (c.tid == 0) bulk_wait_read();
      bar_sync(3 + c.wg, 128);
      store_half_raw(c, c.sX, own);
    }
    else bar_sync(3 + wg, 128);
    asm volatile("setmaxnreg.dec.sync.aligned.u32 128;");
    bar_arrive(7, 384); bar_arrive(8, 384);
    if (has_tile && !dry && (threadIdx.x & 127) == 0) {
      bulk_wait_all();
      if (tile <= 62) cnt_signal(g_cnt1 + 32);
      if (tile >= 62) cnt_signal(g_cnt1 + 96);
    }
    __syncwarp();
    PROF_MARK(0, 6);
  }

  if (blockIdx.x == 128) return;
  if (blockIdx.x != 130) {
    const int lane = threadIdx.x & 31, wq = (threadIdx.x >> 5) & 3;
    const uint32_t dQ = dlo(base + wg * 8192, 16);
    float O[32], l0, l1;
    PROF_MARK(1, 1);
    mbar_wait(misc + B_Q, dry);
    PROF_MARK(1, 2);
    att_pass<false>(a, dQ, O, l0, l1);
    PROF_MARK(1, 3);
    float z = 0.f;
#pragma unroll
    for (int i = 0; i < 32; i++) z = fmaf(O[i], 0.f, z);
    const bool ok = (l0 >= 0x1p-80f) && (l0 <= 0x1p100f) && (l1 >= 0x1p-80f) && (l1 <= 0x1p100f) && (z == 0.f);
    const bool warp_bad = !__all_sync(0xffffffff, ok) && !dry;
    auto store_out = [&]() {
      const float i0 = 1.f / l0, i1 = 1.f / l1;
      const int row = qt * 256 + wg * 64 + wq * 16;
      if (row < T_ && !dry) {
        const int slab = (a.b * T_ + row) / 16;
        uint4* op = g_att + (slab * 16 + a.h * 4) * 32 + lane;
#pragma unroll
        for (int j = 0; j < 4; j++)
          asm volatile("st.relaxed.gpu.global.v4.u32 [%0], {%1,%2,%3,%4};" :: "l"(op + j * 32),
                       "r"(pack_bf16(O[8 * j] * i0, O[8 * j + 1] * i0)), "r"(pack_bf16(O[8 * j + 2] * i1, O[8 * j + 3] * i1)),
                       "r"(pack_bf16(O[8 * j + 4] * i0, O[8 * j + 5] * i0)), "r"(pack_bf16(O[8 * j + 6] * i1, O[8 * j + 7] * i1)) : "memory");
      }
      PROF_MARK(1, 4);
    };
    if (!warp_bad) store_out();
    if (__syncthreads_or(warp_bad)) {
      if (threadIdx.x == 0) {
        if (has_tile) { mbar_wait(misc + B_FULL, 1); mbar_wait(misc + B_FULL + 8, 1); }
        for (int i = 0; i < 3 * NSTG; i++) mbar_inval(a.full + 8 * i);
        att_init_bars(a);
        asm volatile("fence.mbarrier_init.release.cluster;" ::: "memory");
        fence_async_smem();
#pragma unroll 1
        for (int i = 0; i < NSTG; i++) att_load_stage(a, i);
      }
      __syncthreads();
      att_pass<true>(a, dQ, O, l0, l1);
      if (warp_bad) store_out();
      __syncthreads();
      if (has_tile) {
        if (threadIdx.x == 32) {
          load_stage(base + OFF_W, misc + B_X, tm, NC);
          load_stage(base + OFF_W + STAGE, misc + B_Q, tm, NC + 1);
        }
        mbar_wait(misc + B_X, 1); mbar_wait(misc + B_Q, 1);
      }
    }
    PROF_MARK(1, 5);
  } else {
    __syncthreads();
  }
  if (dry ? blockIdx.x != 130 : !has_tile) return;

  if (wg >= 2) {
    asm volatile("setmaxnreg.dec.sync.aligned.u32 24;");
    if (threadIdx.x == 256 && !dry) {
      __nanosleep(PROD_NS);
      produce(base + OFF_W, misc + B_FULL, tm, NC + 2, NC + 48);
    }
  } else {
    asm volatile("setmaxnreg.inc.sync.aligned.u32 232;");
    const Ctx c = make_ctx(base, dry);
    if (dry && c.wg == 1) turn_end(c);
    float own[64];
    float a0, b0, a1, b1;
    PROF_MARK(2, 0);
    {
      uint4 af[16];
      const int slab = tile * 4 + (c.tid >> 5);
      const uint4* ap = g_att + slab * 512 + c.lane;
#pragma unroll
      for (int i = 0; i < 16; i++)
        asm volatile("ld.global.ca.v4.u32 {%0,%1,%2,%3}, [%4];" : "=r"(af[i].x), "=r"(af[i].y), "=r"(af[i].z), "=r"(af[i].w) : "l"(ap + i * 32) : "memory");
      load_half(c, c.sX, own);
      uint32_t miss = dry ? 0 : 15;
      for (uint32_t n = 0; n < (1u << 18); n++) {
#pragma unroll
        for (int hh = 0; hh < 4; hh++)
          if ((miss >> hh) & 1) {
            uint32_t mx = 0;
#pragma unroll
            for (int i = 4 * hh; i < 4 * hh + 4; i++) mx = max(mx, max(max(af[i].x, af[i].y), max(af[i].z, af[i].w)));
            if (__any_sync(0xffffffff, mx == ~0u)) {
#pragma unroll
              for (int i = 4 * hh; i < 4 * hh + 4; i++)
                asm volatile("ld.relaxed.gpu.global.v4.u32 {%0,%1,%2,%3}, [%4];" : "=r"(af[i].x), "=r"(af[i].y), "=r"(af[i].z), "=r"(af[i].w) : "l"(ap + i * 32) : "memory");
            } else miss &= ~(1u << hh);
          }
        if (!miss) break;
      }
      PROF_MARK(2, 2);
      const int n = NC + 2 * c.wg;
      uint32_t b = stage_wait(c, n) + ((16384 >> 4) << 16);
      turn_begin(c);
      wg_fence();
#pragma unroll
      for (int kk = 0; kk < 8; kk++) wg_rs_n128_tb1<1>(own, af[kk].x, af[kk].y, af[kk].z, af[kk].w, b + kk * 128);
      wg_commit();
      b = stage_wait(c, n + 1) + ((16384 >> 4) << 16);
      wg_fence();
#pragma unroll
      for (int kk = 0; kk < 8; kk++) wg_rs_n128_tb1<1>(own, af[8 + kk].x, af[8 + kk].y, af[8 + kk].z, af[8 + kk].w, b + kk * 128);
      wg_commit();
      turn_end(c);
      wg_wait<1>(); stage_release(c, n);
      wg_wait<0>(); stage_release(c, n + 1);
    }
    PROF_MARK(2, 3);
    ln_stats(c, own, 0.5f, a0, b0, a1, b1);
    store_half(c, c.sA, own, a0, b0, a1, b1);
    fence_async_smem();
    bar_sync(1, 256);
    PROF_MARK(2, 4);
    uint4 dwr[5];
#pragma unroll
    for (int i = 0; i < 5; i++) dwr[i] = __ldg(dw + i * 32 + c.wg * 16 + (c.lane & 15));
    const bool top = c.tid < 8, pub = (top || c.tid >= 120) && !dry;
    uint32_t* halo_out = (uint32_t*)g_halo + (tile * 4 + (top ? (c.tid >> 2) : ((c.tid >> 2) - 28))) * 128 + c.wg * 64 + (c.lane & 3);
#pragma unroll 1
    for (int q = dry; q < 2; q++) {
      float ab[64];
      gemm256<1>(c, ab, NC + 4 + 4 * q + 2 * c.wg);
#pragma unroll
      for (int j = 0; j < 4; j++) {
        float g[8];
#pragma unroll
        for (int i = 0; i < 8; i++) g[i] = fmaf(ab[8 * j + i], tanh_fast(ab[32 + 8 * j + i]), ab[8 * j + i]);
        const uint32_t p0 = pack_bf16(g[0], g[1]), p1 = pack_bf16(g[2], g[3]), p2 = pack_bf16(g[4], g[5]), p3 = pack_bf16(g[6], g[7]);
        if (pub) {
          uint32_t* hp = halo_out + q * 32 + j * 8;
          asm volatile("st.relaxed.gpu.global.u32 [%0], %1;" :: "l"(hp), "r"(top ? p0 : p1) : "memory");
          asm volatile("st.relaxed.gpu.global.u32 [%0], %1;" :: "l"(hp + 4), "r"(top ? p2 : p3) : "memory");
        }
        stsm_x4(c.sX + (2 * c.wg + q) * 8192 + c.frag + (((j * 2 + c.hi) ^ c.rsw) << 4), p0, p1, p2, p3);
      }
    }
    bar_sync(3 + c.wg, 128);
    PROF_MARK(2, 5);
    {
      const int wi = c.tid >> 4;
      const uint32_t col = (2 * c.wg + ((c.lane >> 3) & 1)) * 8192, ch = c.lane & 7;
      uint4 r[12];
      const int R0 = tile * 64 + wi * 8;
      const bool first = (R0 % T_) == 0, last = ((R0 + 8) % T_) == 0;
      const bool far = ((wi == 0 && !first) || (wi == 7 && !last)) && !dry;
      const uint4* sp = g_halo + (wi == 0 ? (tile - 1) * 4 + 2 : (tile + 1) * 4) * 32 + c.wg * 16 + (c.lane & 15);
      uint4 h0 = make_uint4(0, 0, 0, 0), h1 = h0;
      auto ld_halo = [&]() {
        asm volatile("ld.relaxed.gpu.global.v4.u32 {%0,%1,%2,%3}, [%4];" : "=r"(h0.x), "=r"(h0.y), "=r"(h0.z), "=r"(h0.w) : "l"(sp) : "memory");
        asm volatile("ld.relaxed.gpu.global.v4.u32 {%0,%1,%2,%3}, [%4];" : "=r"(h1.x), "=r"(h1.y), "=r"(h1.z), "=r"(h1.w) : "l"(sp + 32) : "memory");
      };
      if (far) ld_halo();
#pragma unroll
      for (int i = 0; i < 12; i++) {
        const int row = (wi * 8 - 2 + i) & 63;
        r[i] = lds128(c.sX + col + row * 128 + ((ch ^ (row & 7)) << 4));
      }
      uint32_t w[5][4];
#pragma unroll
      for (int k = 0; k < 5; k++) {
        w[k][0] = bmul2(dwr[k].x, 0x3F003F00u); w[k][1] = bmul2(dwr[k].y, 0x3F003F00u);
        w[k][2] = bmul2(dwr[k].z, 0x3F003F00u); w[k][3] = bmul2(dwr[k].w, 0x3F003F00u);
      }
      auto conv4 = [&](int i0, int i1, int i2, int i3, bool sync) {
        const int rows[4] = {i0, i1, i2, i3};
        uint32_t acc[4][4];
#pragma unroll
        for (int k = 0; k < 5; k++)
#pragma unroll
          for (int j = 0; j < 4; j++) {
            const uint4 x = r[rows[j] + k];
            acc[j][0] = k ? bfma2(x.x, w[k][0], acc[j][0]) : bmul2(x.x, w[0][0]);
            acc[j][1] = k ? bfma2(x.y, w[k][1], acc[j][1]) : bmul2(x.y, w[0][1]);
            acc[j][2] = k ? bfma2(x.z, w[k][2], acc[j][2]) : bmul2(x.z, w[0][2]);
            acc[j][3] = k ? bfma2(x.w, w[k][3], acc[j][3]) : bmul2(x.w, w[0][3]);
          }
#pragma unroll
        for (int j = 0; j < 4; j++)
#pragma unroll
          for (int q = 0; q < 4; q++) acc[j][q] = pack_bf16(silu_half(bf_lo(acc[j][q])), silu_half(bf_hi(acc[j][q])));
        if (sync) bar_sync(3 + c.wg, 128);
#pragma unroll
        for (int j = 0; j < 4; j++)
          sts128(c.sX + col + (wi * 8 + rows[j]) * 128 + ((ch ^ rows[j]) << 4), make_uint4(acc[j][0], acc[j][1], acc[j][2], acc[j][3]));
      };
      conv4(2, 3, 4, 5, true);
      if (far) {
        for (uint32_t n = 0; n < (1u << 18); n++) {
          const uint32_t mx = max(max(max(h0.x, h0.y), max(h0.z, h0.w)), max(max(h1.x, h1.y), max(h1.z, h1.w)));
          if (mx != ~0u) break;
          ld_halo();
        }
      }
      __syncwarp();
      if (first || (far && wi == 0)) { r[0] = h0; r[1] = h1; }
      if (last || (far && wi == 7)) { r[10] = h0; r[11] = h1; }
      conv4(0, 1, 6, 7, false);
    }
    fence_async_smem();
    bar_sync(c.wg == 0 ? 3 : 1, c.wg == 0 ? 128 : 256);
    PROF_MARK(2, 6);
    {
      uint32_t b = stage_wait(c, NC + 12 + c.wg);
      turn_begin(c);
      wg_fence(); piece_ss<0, 0>(c, own, dlo(c.sX, 16), b); wg_commit();
      if (c.wg == 0) { turn_end(c); bar_sync(1, 256); turn_begin(c); }
      b = stage_wait(c, NC + 14 + c.wg);
      wg_fence(); piece_ss<0, 1>(c, own, dlo(c.sX, 16) + 1024, b); wg_commit();
    }
    wg_wait<1>(); stage_release(c, NC + 12 + c.wg);
    wg_wait<0>(); stage_release(c, NC + 14 + c.wg);
    PROF_MARK(2, 7);
    ln_stats(c, own, 0.5f, a0, b0, a1, b1);
    if (c.wg == 1) { turn_begin(c); turn_end(c); }
    store_half(c, c.sA, own, a0, b0, a1, b1);
    fence_async_smem();
    bar_sync(1, 256);
    PROF_MARK(2, 8);
    ff_block(c, NC + 16, own);
    PROF_MARK(2, 9);
    ln_stats(c, own, 1.f, a0, b0, a1, b1);
    store_half(c, c.sX, own, a0, b0, a1, b1);
    fence_async_smem();
    bar_sync(3 + c.wg, 128);
    if (c.tid == 0 && !dry) { tma_store_3d(&tm.Out, c.sX + c.wg * 16384, 0, tile * 64, 2 * c.wg); bulk_commit(); PROF_MARK(2, 10); bulk_wait_read(); }
    PROF_MARK(2, 11);
  }
}

typedef CUresult (*EncodeFn)(CUtensorMap*, CUtensorMapDataType, cuuint32_t, void*, const cuuint64_t*, const cuuint64_t*, const cuuint32_t*,
                             const cuuint32_t*, CUtensorMapInterleave, CUtensorMapSwizzle, CUtensorMapL2promotion, CUtensorMapFloatOOBfill);

CUtensorMap make_map(EncodeFn enc, const void* p, uint64_t d0, uint64_t d1, uint64_t d2, uint64_t s1, uint64_t s2, uint32_t b1, uint32_t b2) {
  CUtensorMap tm;
  cuuint64_t dims[3] = {d0, d1, d2};
  cuuint64_t strides[2] = {s1, s2};
  cuuint32_t box[3] = {64, b1, b2};
  cuuint32_t es[3] = {1, 1, 1};
  enc(&tm, CU_TENSOR_MAP_DATA_TYPE_BFLOAT16, 3, const_cast<void*>(p), dims, strides, box, es, CU_TENSOR_MAP_INTERLEAVE_NONE,
      CU_TENSOR_MAP_SWIZZLE_128B, CU_TENSOR_MAP_L2_PROMOTION_L2_256B, CU_TENSOR_MAP_FLOAT_OOB_FILL_NONE);
  return tm;
}
CUtensorMap blk_map(EncodeFn enc, const void* p, uint64_t rows, uint64_t cols, uint32_t boxrows, uint32_t boxblks) {
  return make_map(enc, p, 64, rows, cols / 64, cols * 2, 128, boxrows, boxblks);
}
CUtensorMap seq_map(EncodeFn enc, const void* p, uint64_t cols, uint32_t boxrows) {
  return make_map(enc, p, cols, T_, 2, cols * 2, cols * 2 * T_, boxrows, 1);
}

}

extern "C" void kernel_launch(void* const* d_in, const int* in_sizes, int n_in, void* d_out, int out_size) {
  (void)in_sizes; (void)n_in; (void)out_size;
  const void *x = d_in[0], *w1a = d_in[1], *w1b = d_in[2], *wqkv = d_in[3], *wo = d_in[4], *pw1 = d_in[5], *dw = d_in[6], *pw2 = d_in[7],
             *w2a = d_in[8], *w2b = d_in[9];
  void* fn = nullptr;
  cudaDriverEntryPointQueryResult qr;
  cudaGetDriverEntryPoint("cuTensorMapEncodeTiled", &fn, cudaEnableDefault, &qr);
  EncodeFn enc = (EncodeFn)fn;
  void* qkv;
  cudaGetSymbolAddress(&qkv, g_qkv);
  cudaFuncSetAttribute(conformer_kernel, cudaFuncAttributeMaxDynamicSharedMemorySize, SMEM_BYTES);

  Wptrs wp;
  const void* ws[8] = {w1a, w1b, wqkv, wo, pw1, pw2, w2a, w2b};
  const uint32_t wb[8] = {524288, 524288, 393216, 131072, 262144, 131072, 524288, 524288};
  for (int i = 0; i < 8; i++) { wp.p[i] = ws[i]; wp.bytes[i] = wb[i]; }
  Maps tm;
  tm.X = blk_map(enc, x, ROWS, 256, 64, 4);
  tm.W1a = blk_map(enc, w1a, 256, 1024, 256, 1);
  tm.W1b = blk_map(enc, w1b, 1024, 256, 64, 4);
  tm.Wqkv = blk_map(enc, wqkv, 256, 768, 128, 2);
  tm.QKVst = blk_map(enc, qkv, ROWS, 768, 64, 2);
  tm.Q = seq_map(enc, qkv, 768, 256);
  tm.KV = seq_map(enc, qkv, 768, 160);
  tm.Wo = blk_map(enc, wo, 256, 256, 128, 2);
  tm.Pw1 = make_map(enc, pw1, 256, 256, 2, 1024, 512, 128, 2);
  tm.Pw2 = blk_map(enc, pw2, 256, 256, 128, 2);
  tm.W2a = blk_map(enc, w2a, 256, 1024, 256, 1);
  tm.W2b = blk_map(enc, w2b, 1024, 256, 64, 4);
  tm.Out = blk_map(enc, d_out, ROWS, 256, 64, 2);
  conformer_kernel<<<NCTA, 512, SMEM_BYTES, cudaStreamPerThread>>>(tm, wp, (const uint4*)dw);
}
```

```cpp
#include <cuda_runtime.h>
#include <cuda_bf16.h>
#include <cuda.h>
#include <stdint.h>

namespace {

constexpr int T_ = 4000;
constexpr int TPB = 63;
constexpr int NTILE = 2 * TPB;
#define NDRY 3
constexpr int NCTA = NTILE + NDRY;

__device__ __nv_bfloat16 g_kv[2 * T_ * 512];
__device__ uint4 g_x1[NTILE * 2048];
__device__ uint4 g_halo[NTILE * 4 * 32];
__device__ uint32_t g_start;
__device__ uint32_t g_cnt[2 * 32];

#define PROF_MARK(k, i) do {} while (0)
#define PROF_STG(n, i) do {} while (0)

__device__ __forceinline__ uint32_t smem_u32(const void* p) { return (uint32_t)__cvta_generic_to_shared(p); }
__device__ __forceinline__ void mbar_init(uint32_t bar, uint32_t cnt) { asm volatile("mbarrier.init.shared::cta.b64 [%0], %1;" :: "r"(bar), "r"(cnt) : "memory"); }
__device__ __forceinline__ void mbar_expect_tx(uint32_t bar, uint32_t bytes) { asm volatile("mbarrier.arrive.expect_tx.shared::cta.b64 _, [%0], %1;" :: "r"(bar), "r"(bytes) : "memory"); }
__device__ __forceinline__ void mbar_arrive(uint32_t bar) { asm volatile("mbarrier.arrive.shared::cta.b64 _, [%0];" :: "r"(bar) : "memory"); }
__device__ __forceinline__ void mbar_wait(uint32_t bar, uint32_t parity) {
  asm volatile("{\n.reg .pred p;\n.reg .u32 n;\n"
               "mbarrier.try_wait.parity.shared::cta.b64 p, [%0], %1;\n@p bra DONE_%=;\nmov.u32 n, 0;\n"
               "LOOP_%=:\nmbarrier.try_wait.parity.shared::cta.b64 p, [%0], %1;\n@p bra DONE_%=;\n"
               "add.u32 n, n, 1;\nsetp.lt.u32 p, n, 262144;\n@p bra LOOP_%=;\ntrap;\nDONE_%=:\n}\n" :: "r"(bar), "r"(parity) : "memory");
}
__device__ __forceinline__ void cnt_wait(const uint32_t* p, uint32_t target) {
  asm volatile("{\n.reg .pred p;\n.reg .u32 n, v;\nmov.u32 n, 0;\n"
               "LOOP_%=:\nld.relaxed.gpu.global.u32 v, [%0];\nsub.u32 v, v, %1;\nsetp.ge.s32 p, v, 0;\n@p bra DONE_%=;\n"
               "nanosleep.u32 40;\nadd.u32 n, n, 1;\nsetp.lt.u32 p, n, 262144;\n@p bra LOOP_%=;\ntrap;\nDONE_%=:\n}\n" :: "l"(p), "r"(target) : "memory");
}
__device__ __forceinline__ void cnt_signal(uint32_t* p) {
  asm volatile("red.relaxed.gpu.global.add.u32 [%0], 1;" :: "l"(p) : "memory");
}
__device__ __forceinline__ void tma_load_3d(uint32_t dst, const CUtensorMap* tm, uint32_t bar, int c0, int c1, int c2) {
  asm volatile("cp.async.bulk.tensor.3d.shared::cluster.global.mbarrier::complete_tx::bytes [%0], [%1, {%3, %4, %5}], [%2];"
    :: "r"(dst), "l"(tm), "r"(bar), "r"(c0), "r"(c1), "r"(c2) : "memory");
}
__device__ __forceinline__ void tma_load_4d(uint32_t dst, const CUtensorMap* tm, uint32_t bar, int c0, int c1, int c2, int c3) {
  asm volatile("cp.async.bulk.tensor.4d.shared::cluster.global.mbarrier::complete_tx::bytes [%0], [%1, {%3, %4, %5, %6}], [%2];"
    :: "r"(dst), "l"(tm), "r"(bar), "r"(c0), "r"(c1), "r"(c2), "r"(c3) : "memory");
}
__device__ __forceinline__ void bulk_load(uint32_t dst, const void* src, uint32_t bytes, uint32_t bar) {
  asm volatile("cp.async.bulk.shared::cluster.global.mbarrier::complete_tx::bytes [%0], [%1], %2, [%3];" :: "r"(dst), "l"(src), "r"(bytes), "r"(bar) : "memory");
}
__device__ __forceinline__ void bulk_store(void* dst, uint32_t src, uint32_t bytes) {
  asm volatile("cp.async.bulk.global.shared::cta.bulk_group [%0], [%1], %2;" :: "l"(dst), "r"(src), "r"(bytes) : "memory");
}
__device__ __forceinline__ void tma_store_4d(const CUtensorMap* tm, uint32_t src, int c0, int c1, int c2, int c3) {
  asm volatile("cp.async.bulk.tensor.4d.global.shared::cta.bulk_group [%0, {%2, %3, %4, %5}], [%1];" :: "l"(tm), "r"(src), "r"(c0), "r"(c1), "r"(c2), "r"(c3) : "memory");
}
__device__ __forceinline__ void bulk_commit() { asm volatile("cp.async.bulk.commit_group;" ::: "memory"); }
__device__ __forceinline__ void bulk_wait_read() { asm volatile("cp.async.bulk.wait_group.read 0;" ::: "memory"); }
__device__ __forceinline__ void bulk_wait_all() { asm volatile("cp.async.bulk.wait_group 0;" ::: "memory"); }
__device__ __forceinline__ void l2_prefetch(const void* p, uint32_t bytes) { asm volatile("cp.async.bulk.prefetch.L2.global [%0], %1;" :: "l"(p), "r"(bytes) : "memory"); }
__device__ __forceinline__ void prefetch_tmap(const CUtensorMap* tm) { asm volatile("prefetch.tensormap [%0];" :: "l"(tm) : "memory"); }
__device__ __forceinline__ void fence_async_smem() { asm volatile("fence.proxy.async.shared::cta;" ::: "memory"); }
__device__ __forceinline__ void wg_fence() { asm volatile("wgmma.fence.sync.aligned;" ::: "memory"); }
__device__ __forceinline__ void wg_commit() { asm volatile("wgmma.commit_group.sync.aligned;" ::: "memory"); }
template<int N> __device__ __forceinline__ void wg_wait() { asm volatile("wgmma.wait_group.sync.aligned %0;" :: "n"(N) : "memory"); }
__device__ __forceinline__ void bar_sync(int id, int n) { asm volatile("bar.sync %0, %1;" :: "r"(id), "r"(n) : "memory"); }
__device__ __forceinline__ void bar_arrive(int id, int n) { asm volatile("bar.arrive %0, %1;" :: "r"(id), "r"(n) : "memory"); }
__device__ __forceinline__ float ex2(float x) { float y; asm("ex2.approx.ftz.f32 %0, %1;" : "=f"(y) : "f"(x)); return y; }
__device__ __forceinline__ float tanh_fast(float x) { float y; asm("tanh.approx.f32 %0, %1;" : "=f"(y) : "f"(x)); return y; }
__device__ __forceinline__ uint32_t pack_bf16(float lo, float hi) { uint32_t r; asm("cvt.rn.bf16x2.f32 %0, %1, %2;" : "=r"(r) : "f"(hi), "f"(lo)); return r; }
__device__ __forceinline__ uint32_t bmul2(uint32_t a, uint32_t b) { uint32_t d; asm("mul.rn.bf16x2 %0, %1, %2;" : "=r"(d) : "r"(a), "r"(b)); return d; }
__device__ __forceinline__ uint32_t bfma2(uint32_t a, uint32_t b, uint32_t c) { uint32_t d; asm("fma.rn.bf16x2 %0, %1, %2, %3;" : "=r"(d) : "r"(a), "r"(b), "r"(c)); return d; }
__device__ __forceinline__ float bf_lo(uint32_t u) { return __uint_as_float(u << 16); }
__device__ __forceinline__ float bf_hi(uint32_t u) { return __uint_as_float(u & 0xffff0000u); }
__device__ __forceinline__ void ldsm_x4(uint32_t addr, uint32_t& r0, uint32_t& r1, uint32_t& r2, uint32_t& r3) {
  asm volatile("ldmatrix.sync.aligned.m8n8.x4.shared.b16 {%0,%1,%2,%3}, [%4];" : "=r"(r0), "=r"(r1), "=r"(r2), "=r"(r3) : "r"(addr) : "memory");
}
__device__ __forceinline__ void stsm_x4(uint32_t addr, uint32_t r0, uint32_t r1, uint32_t r2, uint32_t r3) {
  asm volatile("stmatrix.sync.aligned.m8n8.x4.shared.b16 [%0], {%1,%2,%3,%4};" :: "r"(addr), "r"(r0), "r"(r1), "r"(r2), "r"(r3) : "memory");
}
__device__ __forceinline__ void sts128(uint32_t addr, uint4 v) { asm volatile("st.shared.v4.b32 [%0], {%1,%2,%3,%4};" :: "r"(addr), "r"(v.x), "r"(v.y), "r"(v.z), "r"(v.w) : "memory"); }
__device__ __forceinline__ uint4 lds128(uint32_t addr) { uint4 v; asm volatile("ld.shared.v4.b32 {%0,%1,%2,%3}, [%4];" : "=r"(v.x), "=r"(v.y), "=r"(v.z), "=r"(v.w) : "r"(addr) : "memory"); return v; }
__device__ __forceinline__ void sts64f(uint32_t addr, float a, float b) { asm volatile("st.shared.v2.f32 [%0], {%1,%2};" :: "r"(addr), "f"(a), "f"(b) : "memory"); }
__device__ __forceinline__ float2 lds64f(uint32_t addr) { float2 v; asm volatile("ld.shared.v2.f32 {%0,%1}, [%2];" : "=f"(v.x), "=f"(v.y) : "r"(addr) : "memory"); return v; }
__device__ __forceinline__ uint32_t dlo(uint32_t addr, uint32_t lbo) { return ((addr & 0x3FFFF) >> 4) | ((lbo >> 4) << 16); }

template<int SD> __device__ __forceinline__ void wg_ss_n128_tb1(float (&d)[64], uint32_t da, uint32_t db) {
  asm volatile("{\n.reg .b64 da, db;\nmov.b64 da, {%64, 0x40000040};\nmov.b64 db, {%65, 0x40000040};\n"
    "wgmma.mma_async.sync.aligned.m64n128k16.f32.bf16.bf16 {%0, %1, %2, %3, %4, %5, %6, %7, %8, %9, %10, %11, %12, %13, %14, %15, %16, %17, %18, %19, %20, %21, %22, %23, %24, %25, %26, %27, %28, %29, %30, %31, %32, %33, %34, %35, %36, %37, %38, %39, %40, %41, %42, %43, %44, %45, %46, %47, %48, %49, %50, %51, %52, %53, %54, %55, %56, %57, %58, %59, %60, %61, %62, %63}, da, db, %66, 1, 1, 0, 1;\n}\n"
    : "+f"(d[0]), "+f"(d[1]), "+f"(d[2]), "+f"(d[3]), "+f"(d[4]), "+f"(d[5]), "+f"(d[6]), "+f"(d[7]), "+f"(d[8]), "+f"(d[9]), "+f"(d[10]), "+f"(d[11]), "+f"(d[12]), "+f"(d[13]), "+f"(d[14]), "+f"(d[15]), "+f"(d[16]), "+f"(d[17]), "+f"(d[18]), "+f"(d[19]), "+f"(d[20]), "+f"(d[21]), "+f"(d[22]), "+f"(d[23]), "+f"(d[24]), "+f"(d[25]), "+f"(d[26]), "+f"(d[27]), "+f"(d[28]), "+f"(d[29]), "+f"(d[30]), "+f"(d[31]), "+f"(d[32]), "+f"(d[33]), "+f"(d[34]), "+f"(d[35]), "+f"(d[36]), "+f"(d[37]), "+f"(d[38]), "+f"(d[39]), "+f"(d[40]), "+f"(d[41]), "+f"(d[42]), "+f"(d[43]), "+f"(d[44]), "+f"(d[45]), "+f"(d[46]), "+f"(d[47]), "+f"(d[48]), "+f"(d[49]), "+f"(d[50]), "+f"(d[51]), "+f"(d[52]), "+f"(d[53]), "+f"(d[54]), "+f"(d[55]), "+f"(d[56]), "+f"(d[57]), "+f"(d[58]), "+f"(d[59]), "+f"(d[60]), "+f"(d[61]), "+f"(d[62]), "+f"(d[63])
    : "r"(da), "r"(db), "n"(SD));
}
template<int SD> __device__ __forceinline__ void wg_rs_n128_tb1(float (&d)[64], uint32_t a0, uint32_t a1, uint32_t a2, uint32_t a3, uint32_t db) {
  asm volatile("{\n.reg .b64 db;\nmov.b64 db, {%68, 0x40000040};\n"
    "wgmma.mma_async.sync.aligned.m64n128k16.f32.bf16.bf16 {%0, %1, %2, %3, %4, %5, %6, %7, %8, %9, %10, %11, %12, %13, %14, %15, %16, %17, %18, %19, %20, %21, %22, %23, %24, %25, %26, %27, %28, %29, %30, %31, %32, %33, %34, %35, %36, %37, %38, %39, %40, %41, %42, %43, %44, %45, %46, %47, %48, %49, %50, %51, %52, %53, %54, %55, %56, %57, %58, %59, %60, %61, %62, %63}, {%64, %65, %66, %67}, db, %69, 1, 1, 1;\n}\n"
    : "+f"(d[0]), "+f"(d[1]), "+f"(d[2]), "+f"(d[3]), "+f"(d[4]), "+f"(d[5]), "+f"(d[6]), "+f"(d[7]), "+f"(d[8]), "+f"(d[9]), "+f"(d[10]), "+f"(d[11]), "+f"(d[12]), "+f"(d[13]), "+f"(d[14]), "+f"(d[15]), "+f"(d[16]), "+f"(d[17]), "+f"(d[18]), "+f"(d[19]), "+f"(d[20]), "+f"(d[21]), "+f"(d[22]), "+f"(d[23]), "+f"(d[24]), "+f"(d[25]), "+f"(d[26]), "+f"(d[27]), "+f"(d[28]), "+f"(d[29]), "+f"(d[30]), "+f"(d[31]), "+f"(d[32]), "+f"(d[33]), "+f"(d[34]), "+f"(d[35]), "+f"(d[36]), "+f"(d[37]), "+f"(d[38]), "+f"(d[39]), "+f"(d[40]), "+f"(d[41]), "+f"(d[42]), "+f"(d[43]), "+f"(d[44]), "+f"(d[45]), "+f"(d[46]), "+f"(d[47]), "+f"(d[48]), "+f"(d[49]), "+f"(d[50]), "+f"(d[51]), "+f"(d[52]), "+f"(d[53]), "+f"(d[54]), "+f"(d[55]), "+f"(d[56]), "+f"(d[57]), "+f"(d[58]), "+f"(d[59]), "+f"(d[60]), "+f"(d[61]), "+f"(d[62]), "+f"(d[63])
    : "r"(a0), "r"(a1), "r"(a2), "r"(a3), "r"(db), "n"(SD));
}
template<int SD> __device__ __forceinline__ void wg_ss_n64_tb1(float (&d)[32], uint32_t da, uint32_t db) {
  asm volatile("{\n.reg .b64 da, db;\nmov.b64 da, {%32, 0x40000040};\nmov.b64 db, {%33, 0x40000040};\n"
    "wgmma.mma_async.sync.aligned.m64n64k16.f32.bf16.bf16 {%0, %1, %2, %3, %4, %5, %6, %7, %8, %9, %10, %11, %12, %13, %14, %15, %16, %17, %18, %19, %20, %21, %22, %23, %24, %25, %26, %27, %28, %29, %30, %31}, da, db, %34, 1, 1, 0, 1;\n}\n"
    : "+f"(d[0]), "+f"(d[1]), "+f"(d[2]), "+f"(d[3]), "+f"(d[4]), "+f"(d[5]), "+f"(d[6]), "+f"(d[7]), "+f"(d[8]), "+f"(d[9]), "+f"(d[10]), "+f"(d[11]), "+f"(d[12]), "+f"(d[13]), "+f"(d[14]), "+f"(d[15]), "+f"(d[16]), "+f"(d[17]), "+f"(d[18]), "+f"(d[19]), "+f"(d[20]), "+f"(d[21]), "+f"(d[22]), "+f"(d[23]), "+f"(d[24]), "+f"(d[25]), "+f"(d[26]), "+f"(d[27]), "+f"(d[28]), "+f"(d[29]), "+f"(d[30]), "+f"(d[31])
    : "r"(da), "r"(db), "n"(SD));
}
template<int SD> __device__ __forceinline__ void wg_ss_n80_tb0(float (&d)[40], uint32_t da, uint32_t db) {
  asm volatile("{\n.reg .b64 da, db;\nmov.b64 da, {%40, 0x40000040};\nmov.b64 db, {%41, 0x40000040};\n"
    "wgmma.mma_async.sync.aligned.m64n80k16.f32.bf16.bf16 {%0, %1, %2, %3, %4, %5, %6, %7, %8, %9, %10, %11, %12, %13, %14, %15, %16, %17, %18, %19, %20, %21, %22, %23, %24, %25, %26, %27, %28, %29, %30, %31, %32, %33, %34, %35, %36, %37, %38, %39}, da, db, %42, 1, 1, 0, 0;\n}\n"
    : "+f"(d[0]), "+f"(d[1]), "+f"(d[2]), "+f"(d[3]), "+f"(d[4]), "+f"(d[5]), "+f"(d[6]), "+f"(d[7]), "+f"(d[8]), "+f"(d[9]), "+f"(d[10]), "+f"(d[11]), "+f"(d[12]), "+f"(d[13]), "+f"(d[14]), "+f"(d[15]), "+f"(d[16]), "+f"(d[17]), "+f"(d[18]), "+f"(d[19]), "+f"(d[20]), "+f"(d[21]), "+f"(d[22]), "+f"(d[23]), "+f"(d[24]), "+f"(d[25]), "+f"(d[26]), "+f"(d[27]), "+f"(d[28]), "+f"(d[29]), "+f"(d[30]), "+f"(d[31]), "+f"(d[32]), "+f"(d[33]), "+f"(d[34]), "+f"(d[35]), "+f"(d[36]), "+f"(d[37]), "+f"(d[38]), "+f"(d[39])
    : "r"(da), "r"(db), "n"(SD));
}
template<int SD> __device__ __forceinline__ void wg_rs_n64_tb1(float (&d)[32], uint32_t a0, uint32_t a1, uint32_t a2, uint32_t a3, uint32_t db) {
  asm volatile("{\n.reg .b64 db;\nmov.b64 db, {%36, 0x40000040};\n"
    "wgmma.mma_async.sync.aligned.m64n64k16.f32.bf16.bf16 {%0, %1, %2, %3, %4, %5, %6, %7, %8, %9, %10, %11, %12, %13, %14, %15, %16, %17, %18, %19, %20, %21, %22, %23, %24, %25, %26, %27, %28, %29, %30, %31}, {%32, %33, %34, %35}, db, %37, 1, 1, 1;\n}\n"
    : "+f"(d[0]), "+f"(d[1]), "+f"(d[2]), "+f"(d[3]), "+f"(d[4]), "+f"(d[5]), "+f"(d[6]), "+f"(d[7]), "+f"(d[8]), "+f"(d[9]), "+f"(d[10]), "+f"(d[11]), "+f"(d[12]), "+f"(d[13]), "+f"(d[14]), "+f"(d[15]), "+f"(d[16]), "+f"(d[17]), "+f"(d[18]), "+f"(d[19]), "+f"(d[20]), "+f"(d[21]), "+f"(d[22]), "+f"(d[23]), "+f"(d[24]), "+f"(d[25]), "+f"(d[26]), "+f"(d[27]), "+f"(d[28]), "+f"(d[29]), "+f"(d[30]), "+f"(d[31])
    : "r"(a0), "r"(a1), "r"(a2), "r"(a3), "r"(db), "n"(SD));
}

constexpr int RING = 5;
constexpr uint32_t STAGE = 32768;
constexpr uint32_t OFF_X = 32768, OFF_W = 65536, OFF_MISC = OFF_W + RING * STAGE;
constexpr int SMEM_BYTES = OFF_MISC + 256 + 1024 + 1024;

struct Ctx {
  uint32_t sA, sX, sW, full, empty, stats;
  uint32_t frag;
  uint32_t rsw;
  uint32_t hi;
  int wg, tid, lane;
  int pk;
  uint32_t dry;
};
__device__ __forceinline__ uint32_t stage_wait(const Ctx& c, int n) {
  const int q = n / RING, s = n - q * RING;
  if (c.tid == 0) PROF_STG(n + c.pk, 1);
  mbar_wait(c.full + 8 * s, (q | c.dry) & 1);
  if (c.tid == 0) PROF_STG(n + c.pk, 2);
  return dlo(c.sW + s * STAGE, 0);
}
__device__ __forceinline__ void stage_release(const Ctx& c, int n) {
  const int s = n % RING;
  if (c.tid == 0) { mbar_arrive(c.empty + 8 * s); PROF_STG(n + c.pk, 3); }
}
__device__ __forceinline__ void turn_begin(const Ctx& c) { bar_sync(5 + c.wg, 256); }
__device__ __forceinline__ void turn_end(const Ctx& c) { bar_arrive(5 + (c.wg ^ 1), 256); }
template<int FIRST, int LAST> __device__ __forceinline__ void piece_ss(const Ctx& c, float (&acc)[64], uint32_t dA, uint32_t dB) {
  dB += (16384 >> 4) << 16;
  wg_ss_n128_tb1<FIRST ? 0 : 1>(acc, dA, dB);
#pragma unroll
  for (int kk = 1; kk < 8; kk++) {
    wg_ss_n128_tb1<1>(acc, dA + (kk >> 2) * 512 + (kk & 3) * 2, dB + kk * 128);
  }
  if (LAST) turn_end(c);
}
__device__ __forceinline__ void ff_g1(const Ctx& c, float (&h)[32], uint32_t dA, uint32_t dB) {
  wg_ss_n64_tb1<0>(h, dA, dB);
#pragma unroll
  for (int kk = 1; kk < 16; kk++) {
    wg_ss_n64_tb1<1>(h, dA + (kk >> 2) * 512 + (kk & 3) * 2, dB + kk * 128);
  }
}
__device__ __forceinline__ void ff_g2(float (&acc)[64], const uint32_t (&P)[16], uint32_t dB, int half) {
  dB += ((8192 >> 4) << 16) + half * 1024;
#pragma unroll
  for (int kk = 0; kk < 4; kk++) wg_rs_n128_tb1<1>(acc, P[4 * kk], P[4 * kk + 1], P[4 * kk + 2], P[4 * kk + 3], dB + kk * 128);
}
struct NoHook { __device__ __forceinline__ void operator()() const {} };
template<int FIRST, class Hook = NoHook> __device__ __forceinline__ void gemm256(const Ctx& c, uint32_t sA, float (&acc)[64], int n, Hook hook = Hook()) {
  const uint32_t dA = dlo(sA, 16);
  uint32_t b = stage_wait(c, n);
  turn_begin(c);
  wg_fence(); piece_ss<FIRST, 0>(c, acc, dA, b); wg_commit();
  b = stage_wait(c, n + 1);
  wg_fence(); piece_ss<0, 1>(c, acc, dA + 1024, b); wg_commit();
  hook();
  wg_wait<1>(); stage_release(c, n);
  wg_wait<0>(); stage_release(c, n + 1);
}
__device__ __forceinline__ uint32_t frag_addr(const Ctx& c, uint32_t tile, int j) {
  return tile + (2 * c.wg + (j >> 2)) * 8192 + c.frag + ((((j & 3) * 2 + c.hi) ^ c.rsw) << 4);
}
__device__ __forceinline__ void load_half(const Ctx& c, uint32_t tile, float (&v)[64]) {
#pragma unroll
  for (int j = 0; j < 8; j++) {
    uint32_t r0, r1, r2, r3;
    ldsm_x4(frag_addr(c, tile, j), r0, r1, r2, r3);
    v[8 * j] = bf_lo(r0); v[8 * j + 1] = bf_hi(r0); v[8 * j + 2] = bf_lo(r1); v[8 * j + 3] = bf_hi(r1);
    v[8 * j + 4] = bf_lo(r2); v[8 * j + 5] = bf_hi(r2); v[8 * j + 6] = bf_lo(r3); v[8 * j + 7] = bf_hi(r3);
  }
}
__device__ __forceinline__ void store_half(const Ctx& c, uint32_t tile, const float (&v)[64], float a0, float b0, float a1, float b1) {
#pragma unroll
  for (int j = 0; j < 8; j++)
    stsm_x4(frag_addr(c, tile, j),
            pack_bf16(fmaf(v[8 * j], a0, b0), fmaf(v[8 * j + 1], a0, b0)), pack_bf16(fmaf(v[8 * j + 2], a1, b1), fmaf(v[8 * j + 3], a1, b1)),
            pack_bf16(fmaf(v[8 * j + 4], a0, b0), fmaf(v[8 * j + 5], a0, b0)), pack_bf16(fmaf(v[8 * j + 6], a1, b1), fmaf(v[8 * j + 7], a1, b1)));
}
__device__ __forceinline__ void store_half_raw(const Ctx& c, uint32_t tile, const float (&v)[64]) {
#pragma unroll
  for (int j = 0; j < 8; j++)
    stsm_x4(frag_addr(c, tile, j), pack_bf16(v[8 * j], v[8 * j + 1]), pack_bf16(v[8 * j + 2], v[8 * j + 3]),
            pack_bf16(v[8 * j + 4], v[8 * j + 5]), pack_bf16(v[8 * j + 6], v[8 * j + 7]));
}
__device__ __forceinline__ void ln_stats(const Ctx& c, const float (&v)[64], float scale, float& a0, float& b0, float& a1, float& b1) {
  float s0 = 0.f, s1 = 0.f, q0 = 0.f, q1 = 0.f, s2 = 0.f, s3 = 0.f, q2 = 0.f, q3 = 0.f;
#pragma unroll
  for (int i = 0; i < 16; i++) {
    s0 += v[4 * i]; q0 = fmaf(v[4 * i], v[4 * i], q0);
    s2 += v[4 * i + 1]; q2 = fmaf(v[4 * i + 1], v[4 * i + 1], q2);
    s1 += v[4 * i + 2]; q1 = fmaf(v[4 * i + 2], v[4 * i + 2], q1);
    s3 += v[4 * i + 3]; q3 = fmaf(v[4 * i + 3], v[4 * i + 3], q3);
  }
  s0 += s2; q0 += q2; s1 += s3; q1 += q3;
  s0 += __shfl_xor_sync(0xffffffff, s0, 1); q0 += __shfl_xor_sync(0xffffffff, q0, 1);
  s1 += __shfl_xor_sync(0xffffffff, s1, 1); q1 += __shfl_xor_sync(0xffffffff, q1, 1);
  s0 += __shfl_xor_sync(0xffffffff, s0, 2); q0 += __shfl_xor_sync(0xffffffff, q0, 2);
  s1 += __shfl_xor_sync(0xffffffff, s1, 2); q1 += __shfl_xor_sync(0xffffffff, q1, 2);
  const uint32_t row = (c.tid >> 5) * 16 + (c.lane >> 2);
  if ((c.lane & 3) == 0) {
    sts64f(c.stats + c.wg * 512 + row * 8, s0, q0);
    sts64f(c.stats + c.wg * 512 + (row + 8) * 8, s1, q1);
  }
  bar_sync(1, 256);
  const float2 o0 = lds64f(c.stats + (c.wg ^ 1) * 512 + row * 8), o1 = lds64f(c.stats + (c.wg ^ 1) * 512 + (row + 8) * 8);
  const float m0 = (s0 + o0.x) * (1.f / 256.f), m1 = (s1 + o1.x) * (1.f / 256.f);
  const float var0 = fmaxf(fmaf(-m0, m0, (q0 + o0.y) * (1.f / 256.f)), 0.f), var1 = fmaxf(fmaf(-m1, m1, (q1 + o1.y) * (1.f / 256.f)), 0.f);
  a0 = rsqrtf(var0 + 1e-5f) * scale; a1 = rsqrtf(var1 + 1e-5f) * scale;
  b0 = -m0 * a0; b1 = -m1 * a1;
}
__device__ __forceinline__ float silu_half(float h) { return fmaf(h, tanh_fast(h), h); }
__device__ __forceinline__ float silu_quarter(float h) { const float q = 0.5f * h; return fmaf(q, tanh_fast(h), q); }
__device__ __forceinline__ void silu_pack(const float (&acc)[32], uint32_t (&P)[16]) {
#pragma unroll
  for (int i = 0; i < 16; i++) P[i] = pack_bf16(silu_quarter(acc[2 * i]), silu_quarter(acc[2 * i + 1]));
}
__device__ __forceinline__ void ff_block(const Ctx& c, int n0, float (&own)[64]) {
  float oth[64], h[32];
  uint32_t P[16];
#pragma unroll
  for (int i = 0; i < 64; i++) oth[i] = 0.f;
  const uint32_t dA = dlo(c.sA, 16);
  {
    const uint32_t b = stage_wait(c, n0 + c.wg);
    turn_begin(c);
    wg_fence(); ff_g1(c, h, dA, b); wg_commit();
    turn_end(c);
    wg_wait<0>(); stage_release(c, n0 + c.wg);
    silu_pack(h, P);
  }
#pragma unroll 1
  for (int it = c.dry ? 7 : 1; it < 8; it++) {
    const int n = n0 + 4 * it - 2 + 2 * c.wg;
    uint32_t b = stage_wait(c, n);
    turn_begin(c);
    wg_fence(); ff_g2(own, P, b, c.wg); ff_g2(oth, P, b, c.wg ^ 1); wg_commit();
    b = stage_wait(c, n + 1);
    wg_fence(); ff_g1(c, h, dA, b); wg_commit();
    turn_end(c);
    wg_wait<1>(); stage_release(c, n);
    wg_wait<0>(); stage_release(c, n + 1);
    silu_pack(h, P);
  }
  if (c.wg == 0) bar_arrive(2, 256);
  {
    const int n = n0 + 30 + c.wg;
    const uint32_t b = stage_wait(c, n);
    turn_begin(c);
    wg_fence(); ff_g2(oth, P, b, c.wg ^ 1); wg_commit();
    ff_g2(own, P, b, c.wg); wg_commit();
    turn_end(c);
    wg_wait<1>();
    if (c.wg == 1) bar_sync(2, 256);
    const uint32_t e = (c.wg == 0 ? c.sX : c.sA) + c.tid * 16;
#pragma unroll
    for (int i = 0; i < 16; i++)
      sts128(e + i * 2048, make_uint4(__float_as_uint(oth[4 * i]), __float_as_uint(oth[4 * i + 1]), __float_as_uint(oth[4 * i + 2]), __float_as_uint(oth[4 * i + 3])));
    wg_wait<0>(); stage_release(c, n);
  }
  bar_sync(1, 256);
  const uint32_t e = (c.wg == 0 ? c.sA : c.sX) + c.tid * 16;
#pragma unroll
  for (int i = 0; i < 16; i++) {
    const uint4 u = lds128(e + i * 2048);
    own[4 * i] += __uint_as_float(u.x); own[4 * i + 1] += __uint_as_float(u.y);
    own[4 * i + 2] += __uint_as_float(u.z); own[4 * i + 3] += __uint_as_float(u.w);
  }
}
struct Maps { CUtensorMap X, W1a, W1b, Wqkv, KVst, KV, Wo, Pw1, Pw2, W2a, W2b, Out; uint16_t stage[92]; };
constexpr int NA = 44;
constexpr int NC = 45;
#define STAGE_TABLE {0x1, 0x11, 0x2, 0x21, 0x102, 0x31, 0x202, 0x41, 0x302, 0x51, 0x402, 0x61, 0x502, 0x71, 0x602, 0x81, 0x702, 0x91, 0x802, 0xa1, 0x902, 0xb1, 0xa02, 0xc1, 0xb02, 0xd1, 0xc02, 0xe1, 0xd02, 0xf1, 0xe02, 0xf02, 0x43, 0x243, 0x63, 0x263, 0x83, 0x283, 0xa3, 0x2a3, 0x3, 0x203, 0x23, 0x223, 0x6, 0x206, 0x26, 0x226, 0x7, 0x207, 0x2007, 0x2207, 0x1007, 0x1207, 0x3007, 0x3207, 0x8, 0x28, 0x208, 0x228, 0x9, 0x19, 0xa, 0x29, 0x10a, 0x39, 0x20a, 0x49, 0x30a, 0x59, 0x40a, 0x69, 0x50a, 0x79, 0x60a, 0x89, 0x70a, 0x99, 0x80a, 0xa9, 0x90a, 0xb9, 0xa0a, 0xc9, 0xb0a, 0xd9, 0xc0a, 0xe9, 0xd0a, 0xf9, 0xe0a, 0xf0a}
__device__ __forceinline__ void load_stage(uint32_t dst, uint32_t bar, const Maps& tm, int n) {
  const uint32_t e = tm.stage[n - (n > NA)];
  mbar_expect_tx(bar, STAGE);
  tma_load_3d(dst, &tm.X + (e & 15), bar, (e >> 12) * 64, ((e >> 8) & 15) * 64, (e >> 4) & 15);
}
__device__ __forceinline__ void produce(uint32_t sW, uint32_t full, const Maps& tm, int n0, int n1) {
  uint32_t s = n0 % RING, ph = ((n0 / RING) & 1) ^ 1;
#pragma unroll 1
  for (int n = n0; n < n1; n++) {
    mbar_wait(full + 8 * RING + 8 * s, ph);
    PROF_STG(n, 0);
    load_stage(sW + s * STAGE, full + 8 * s, tm, n);
    if (++s == RING) { s = 0; ph ^= 1; }
  }
}
__device__ __forceinline__ Ctx make_ctx(uint32_t base, uint32_t dry, int pk = 0) {
  Ctx c; c.pk = pk; c.dry = dry;
  c.sA = base; c.sX = base + OFF_X; c.sW = base + OFF_W;
  c.full = base + OFF_MISC; c.empty = c.full + 8 * RING; c.stats = base + OFF_MISC + 256;
  c.wg = __shfl_sync(0xffffffff, (int)(threadIdx.x >> 7), 0);
  c.tid = threadIdx.x & 127; c.lane = threadIdx.x & 31;
  const uint32_t r = (c.tid >> 5) * 16 + (c.lane & 7) + ((c.lane >> 3) & 1) * 8;
  c.frag = r * 128; c.rsw = r & 7; c.hi = c.lane >> 4;
  return c;
}

constexpr int NB = T_ / 80;
constexpr uint32_t TB = 80 * 128;
static_assert(16 * TB == RING * STAGE, "the K/V buffers reuse the weight ring");
struct AttCtx { uint32_t ring, bars, dry; const Maps* tm; int b; };
__device__ __forceinline__ uint32_t kv_addr(const AttCtx& a, int h, int v) { return a.ring + (v ? 14 - 2 * h : 2 * h) * TB; }
__device__ __forceinline__ void att_load(const AttCtx& a, int h, int j, int v) {
  const uint32_t bar = a.bars + h * 32 + v * 16 + (j & 1) * 8;
  mbar_expect_tx(bar, TB);
  tma_load_3d(kv_addr(a, h, v) + (j & 1) * TB, &a.tm->KV, bar, v * 256 + h * 64, j * 80, a.b);
}
__device__ __forceinline__ void att_qk(float (&S)[40], uint32_t dQ, uint32_t kd) {
  wg_ss_n80_tb0<0>(S, dQ, kd);
#pragma unroll
  for (int kk = 1; kk < 4; kk++) wg_ss_n80_tb0<1>(S, dQ + kk * 2, kd + kk * 2);
}
__device__ __forceinline__ void att_pv(float (&O)[32], const uint32_t (&P)[20], uint32_t vd) {
#pragma unroll
  for (int kk = 0; kk < 5; kk++) wg_rs_n64_tb1<1>(O, P[kk * 4], P[kk * 4 + 1], P[kk * 4 + 2], P[kk * 4 + 3], vd + kk * 128);
}
template<bool SAFE>
__device__ __forceinline__ void att_softmax(const float (&S)[40], uint32_t (&P)[20], float (&O)[32], float& m0, float& m1, float& l0, float& l1) {
  if (SAFE) {
    float x0 = fmaxf(S[0], S[1]), x1 = fmaxf(S[2], S[3]);
#pragma unroll
    for (int i = 1; i < 10; i++) { x0 = fmaxf(x0, fmaxf(S[4 * i], S[4 * i + 1])); x1 = fmaxf(x1, fmaxf(S[4 * i + 2], S[4 * i + 3])); }
    x0 = fmaxf(x0, __shfl_xor_sync(0xffffffff, x0, 1)); x1 = fmaxf(x1, __shfl_xor_sync(0xffffffff, x1, 1));
    x0 = fmaxf(x0, __shfl_xor_sync(0xffffffff, x0, 2)); x1 = fmaxf(x1, __shfl_xor_sync(0xffffffff, x1, 2));
    const float n0 = fmaxf(m0, x0), n1 = fmaxf(m1, x1);
    const float f0 = ex2(m0 - n0), f1 = ex2(m1 - n1);
    m0 = n0; m1 = n1; l0 *= f0; l1 *= f1;
#pragma unroll
    for (int i = 0; i < 8; i++) { O[4 * i] *= f0; O[4 * i + 1] *= f0; O[4 * i + 2] *= f1; O[4 * i + 3] *= f1; }
  }
#pragma unroll
  for (int i = 0; i < 10; i++) {
    float p0, p1, p2, p3;
    if (SAFE) { p0 = ex2(S[4 * i] - m0); p1 = ex2(S[4 * i + 1] - m0); p2 = ex2(S[4 * i + 2] - m1); p3 = ex2(S[4 * i + 3] - m1); }
    else { p0 = ex2(S[4 * i]); p1 = ex2(S[4 * i + 1]); p2 = ex2(S[4 * i + 2]); p3 = ex2(S[4 * i + 3]); }
    l0 += p0 + p1; l1 += p2 + p3;
    P[2 * i] = pack_bf16(p0, p1); P[2 * i + 1] = pack_bf16(p2, p3);
  }
}
template<bool SAFE, class Hook>
__device__ __forceinline__ void att_pass(const AttCtx& a, int h, uint32_t dQ, float (&O)[32], float& l0, float& l1, Hook k_done) {
  float S[40];
  uint32_t P[20];
  float m0 = -INFINITY, m1 = -INFINITY;
  l0 = 0.f; l1 = 0.f;
#pragma unroll
  for (int i = 0; i < 32; i++) O[i] = 0.f;
  constexpr uint32_t TD = TB / 16;
  const uint32_t dK = dlo(kv_addr(a, h, 0), 16), dV = dlo(kv_addr(a, h, 1), 16), bK = a.bars + h * 32, bV = bK + 16;
  const bool el = (threadIdx.x & 127) == 0 && !a.dry;
  if (SAFE) {
    if (el) { att_load(a, h, 0, 0); att_load(a, h, 0, 1); att_load(a, h, 1, 0); att_load(a, h, 1, 1); }
    __syncwarp();
#pragma unroll 1
    for (int j = 0; j < NB; j++) {
      const uint32_t par = ((j >> 1) & 1) ^ 1, s = j & 1;
      mbar_wait(bK + 8 * s, par);
      wg_fence(); att_qk(S, dQ, dK + s * TD); wg_commit(); wg_wait<0>();
      att_softmax<true>(S, P, O, m0, m1, l0, l1);
      mbar_wait(bV + 8 * s, par);
      wg_fence(); att_pv(O, P, dV + s * TD); wg_commit(); wg_wait<0>();
      if (el && j + 2 < NB) { att_load(a, h, j + 2, 0); att_load(a, h, j + 2, 1); }
      __syncwarp();
    }
  } else {
    mbar_wait(bK, a.dry);
    wg_fence(); att_qk(S, dQ, dK); wg_commit(); wg_wait<0>();
    if (el) att_load(a, h, 2, 0);
    __syncwarp();
#pragma unroll 1
    for (int j = a.dry ? NB - 4 : 0; j < NB - 2; j += 2) {
      const uint32_t par = ((j >> 1) | a.dry) & 1;
      att_softmax<false>(S, P, O, m0, m1, l0, l1);
      mbar_wait(bV, par); mbar_wait(bK + 8, par);
      wg_fence(); att_pv(O, P, dV); att_qk(S, dQ, dK + TD); wg_commit(); wg_wait<0>();
      if (el) { att_load(a, h, j + 2, 1); att_load(a, h, j + 3, 0); }
      __syncwarp();
      att_softmax<false>(S, P, O, m0, m1, l0, l1);
      mbar_wait(bV + 8, par); mbar_wait(bK, (par ^ 1) | a.dry);
      wg_fence(); att_pv(O, P, dV + TD); att_qk(S, dQ, dK); wg_commit(); wg_wait<0>();
      if (el) { att_load(a, h, j + 3, 1); if (j + 4 < NB) att_load(a, h, j + 4, 0); }
      __syncwarp();
    }
    att_softmax<false>(S, P, O, m0, m1, l0, l1);
    mbar_wait(bV, a.dry); mbar_wait(bK + 8, a.dry);
    wg_fence(); att_pv(O, P, dV); att_qk(S, dQ, dK + TD); wg_commit(); wg_wait<0>();
    if (el) k_done();
    __syncwarp();
    att_softmax<false>(S, P, O, m0, m1, l0, l1);
    mbar_wait(bV + 8, a.dry);
    wg_fence(); att_pv(O, P, dV + TD); wg_commit(); wg_wait<0>();
  }
  l0 += __shfl_xor_sync(0xffffffff, l0, 1); l1 += __shfl_xor_sync(0xffffffff, l1, 1);
  l0 += __shfl_xor_sync(0xffffffff, l0, 2); l1 += __shfl_xor_sync(0xffffffff, l1, 2);
}

struct Wptrs { const void* p[8]; uint32_t bytes[8]; };

constexpr uint32_t B_FULL = 0, B_EMPTY = 8 * RING, B_X = 16 * RING, B_ADONE = B_X + 8, B_X1 = B_X + 16, B_EP = B_X + 24, B_W = B_X + 32,
                   B_ATT = B_X + 40  , O_EPOCH = 248, O_KDONE = 252;

__global__ void __launch_bounds__(512, 1) conformer_kernel(const __grid_constant__ Maps tm, const __grid_constant__ Wptrs wp, const uint4* __restrict__ dw) {
  extern __shared__ uint8_t smem_raw[];
  const uint32_t base = (smem_u32(smem_raw) + 1023) & ~1023u, misc = base + OFF_MISC;
  const uint32_t dry = blockIdx.x >= NTILE;
  const int tile = dry ? 0 : blockIdx.x;
  const int wg = __shfl_sync(0xffffffff, (int)(threadIdx.x >> 7), 0);
  AttCtx a;
  a.ring = base + OFF_W; a.bars = misc + B_ATT; a.dry = dry; a.tm = &tm; a.b = tile >= TPB;
  const int row0 = (tile - a.b * TPB) * 64;

  if (threadIdx.x == 256) {
    mbar_init(misc + B_X, 1);
    for (int i = 0; i < 2 * RING; i++) mbar_init(misc + B_FULL + 8 * i, 1);
    asm volatile("fence.mbarrier_init.release.cluster;" ::: "memory");
    if (!dry) { mbar_expect_tx(misc + B_X, 32768); tma_load_4d(base + OFF_X, &tm.X, misc + B_X, 0, row0, 0, a.b); }
  } else if (threadIdx.x >= 288 && threadIdx.x < 308) {
    mbar_init(misc + B_ADONE + 8 * (threadIdx.x - 288), threadIdx.x == 288 ? 2 : threadIdx.x == 291 ? 2 : 1);
    if (threadIdx.x == 288) asm volatile("st.shared.u32 [%0], %1;" :: "r"(misc + O_KDONE), "r"(0) : "memory");
    asm volatile("fence.mbarrier_init.release.cluster;" ::: "memory");
  } else if (threadIdx.x >= 320 && threadIdx.x < 332) {
    prefetch_tmap(&tm.X + (threadIdx.x - 320));
  }
  __syncthreads();
  if ((threadIdx.x & 31) == 0 && threadIdx.x >= 256 && threadIdx.x < 256 + 32 * RING && !dry) {
    const int i = (threadIdx.x - 256) >> 5;
    load_stage(base + OFF_W + i * STAGE, misc + B_FULL + 8 * i, tm, i);
  }
  __syncwarp();

  if (wg < 2) {
    asm volatile("setmaxnreg.inc.sync.aligned.u32 232;");
    if (blockIdx.x <= NTILE) {
      const Ctx c = make_ctx(base, dry);
      if (c.wg == 1) turn_end(c);
      float own[64];
      float a0, b0, a1, b1;
      PROF_MARK(0, 0);
#pragma unroll 1
      for (int rep = 0; rep < 2; rep++) {
        if (rep) mbar_wait(misc + B_X, dry);
        PROF_MARK(0, 1);
        load_half(c, c.sX, own);
        ln_stats(c, own, 0.5f, a0, b0, a1, b1);
        store_half(c, c.sA, own, a0, b0, a1, b1);
        fence_async_smem();
        bar_sync(1, 256);
      }
      PROF_MARK(0, 2);
      ff_block(c, 0, own);
      PROF_MARK(0, 3);
      ln_stats(c, own, 1.f, a0, b0, a1, b1);
      store_half(c, c.sA, own, a0, b0, a1, b1);
      fence_async_smem();
      bar_sync(1, 256);
      PROF_MARK(0, 4);
      const bool el = c.tid == 0 && !dry;
      const uint32_t stg = c.sX + c.wg * 16384;
#pragma unroll 1
      for (int cc = 0; cc < 3; cc += 1 + dry) {
        float acc[64];
        gemm256<1>(c, c.sA, acc, 32 + 4 * cc + 2 * c.wg, [&]() {
          if (cc == 0) {
            store_half_raw(c, c.sX, own);
            fence_async_smem();
            bar_sync(3 + c.wg, 128);
            if (el) { bulk_store(g_x1 + tile * 2048 + c.wg * 1024, stg, 16384); bulk_commit(); }
          }
          if (el) {
            if (cc == 2) { bulk_wait_all(); cnt_signal(g_cnt + a.b * 32); }
            else bulk_wait_read();
          }
          bar_sync(3 + c.wg, 128);
        });
        if (cc == 2) {
          if (!dry) bar_arrive(10, 288);
          if (el) mbar_arrive(misc + B_ADONE);
#pragma unroll
          for (int i = 0; i < 64; i++) acc[i] *= 0.125f * 1.4426950408889634f;
        }
        store_half_raw(c, c.sX, acc);
        fence_async_smem();
        bar_sync(3 + c.wg, 128);
        if (el && cc < 2) { tma_store_4d(&tm.KVst, stg, 0, row0, 4 * cc + 2 * c.wg, a.b); bulk_commit(); }
      }
      if (c.wg == 0) bar_arrive(9, 256); else bar_sync(9, 256);
      PROF_MARK(0, 5);
    } else {
      bar_sync(3 + wg, 128);
    }
    asm volatile("setmaxnreg.dec.sync.aligned.u32 128;");
    bar_arrive(7, 384); bar_arrive(8, 384);
    PROF_MARK(0, 6);
  } else {
    asm volatile("setmaxnreg.dec.sync.aligned.u32 24;");
    const uint32_t full = misc + B_FULL;
    if (threadIdx.x == 320) {
      const uint32_t e = atomicAdd(&g_start, 1) / NCTA;
      asm volatile("st.shared.u32 [%0], %1;" :: "r"(misc + O_EPOCH), "r"(e + 1) : "memory");
      mbar_arrive(misc + B_EP);
    }
    auto kv_ready = [&]() {
      uint32_t e;
      mbar_wait(misc + B_EP, 0);
      asm volatile("ld.shared.u32 %0, [%1];" : "=r"(e) : "r"(misc + O_EPOCH) : "memory");
      cnt_wait(g_cnt + a.b * 32, 2 * TPB * e);
    };
    if (dry) {
    } else if (threadIdx.x == 256) {
      produce(base + OFF_W, full, tm, RING, NA);
      mbar_wait(full + 8 * RING + 8 * 4, 1);
      mbar_arrive(full + 8 * 4); mbar_arrive(full + 8 * RING + 8 * 4);
      kv_ready();
      mbar_wait(full + 8 * RING, 0);
      att_load(a, 0, 0, 0); att_load(a, 0, 0, 1); att_load(a, 0, 1, 0); att_load(a, 0, 1, 1);
      mbar_wait(misc + B_ADONE, 0);
      att_load(a, 2, 0, 0); att_load(a, 2, 0, 1); att_load(a, 2, 1, 0); att_load(a, 2, 1, 1);
      mbar_expect_tx(misc + B_X1, 32768);
      bulk_load(base, g_x1 + tile * 2048, 32768, misc + B_X1);
    } else if ((threadIdx.x >> 5) == 12) {
      bar_sync(10, 288);
      if (threadIdx.x == 384) {
        kv_ready();
        att_load(a, 1, 0, 0); att_load(a, 3, 0, 0); att_load(a, 1, 0, 1); att_load(a, 3, 0, 1);
        att_load(a, 1, 1, 0); att_load(a, 3, 1, 0); att_load(a, 1, 1, 1); att_load(a, 3, 1, 1);
      }
    } else if (threadIdx.x >= 288 && threadIdx.x < 296) {
      const int w = threadIdx.x - 288;
      mbar_wait(misc + B_X, 0);
      const uint32_t bytes = wp.bytes[w], per = ((bytes / NTILE) + 127) & ~127u, off = per * tile;
      if (off < bytes) l2_prefetch((const uint8_t*)wp.p[w] + off, min(per, bytes - off));
    } else if (threadIdx.x >= 448) {
      g_halo[tile * 128 + threadIdx.x - 448] = make_uint4(~0u, ~0u, ~0u, ~0u);
      g_halo[tile * 128 + threadIdx.x - 384] = make_uint4(~0u, ~0u, ~0u, ~0u);
    }
    __syncwarp();
    bar_sync(5 + wg, 384);
    asm volatile("setmaxnreg.inc.sync.aligned.u32 128;");
  }

  if (blockIdx.x == NTILE) return;
  if (blockIdx.x != NTILE + 2) {
    const int lane = threadIdx.x & 31;
    const uint32_t sQ = base + OFF_X + wg * 8192, dQ = dlo(sQ, 16);
    float O[32], l0, l1;
    PROF_MARK(1, 2);
    att_pass<false>(a, wg, dQ, O, l0, l1, [&]() {
      uint32_t old;
      asm volatile("atom.shared.add.u32 %0, [%1], 1;" : "=r"(old) : "r"(misc + O_KDONE) : "memory");
      if (old == 3) { load_stage(a.ring, misc + B_FULL, tm, NC); load_stage(a.ring + STAGE, misc + B_FULL + 8, tm, NC + 1); }
    });
    PROF_MARK(1, 3);
    float z = 0.f;
#pragma unroll
    for (int i = 0; i < 32; i++) z = fmaf(O[i], 0.f, z);
    const bool ok = ((l0 >= 0x1p-80f) && (l0 <= 0x1p100f) && (l1 >= 0x1p-80f) && (l1 <= 0x1p100f) && (z == 0.f)) || dry;
    uint32_t bad;
    asm volatile("{\n.reg .pred p, q;\nsetp.eq.u32 p, %1, 0;\nbar.red.or.pred q, %2, 128, p;\nselp.u32 %0, 1, 0, q;\n}\n"
                 : "=r"(bad) : "r"((uint32_t)ok), "r"(11 + wg) : "memory");
    auto store_out = [&]() {
      const float i0 = 1.f / l0, i1 = 1.f / l1;
      const int r = ((threadIdx.x >> 5) & 3) * 16 + (lane & 7) + ((lane >> 3) & 1) * 8;
#pragma unroll
      for (int j = 0; j < 4; j++)
        stsm_x4(sQ + r * 128 + (((j * 2 + (lane >> 4)) ^ (r & 7)) << 4),
                pack_bf16(O[8 * j] * i0, O[8 * j + 1] * i0), pack_bf16(O[8 * j + 2] * i1, O[8 * j + 3] * i1),
                pack_bf16(O[8 * j + 4] * i0, O[8 * j + 5] * i0), pack_bf16(O[8 * j + 6] * i1, O[8 * j + 7] * i1));
      fence_async_smem();
    };
    if (!bad) store_out();
    PROF_MARK(1, 4);
    if (__syncthreads_or(bad)) {
      mbar_wait(misc + B_FULL, 1); mbar_wait(misc + B_FULL + 8, 1);
      if (bad) { att_pass<true>(a, wg, dQ, O, l0, l1, NoHook()); store_out(); }
      __syncthreads();
      if (threadIdx.x == 0) {
        load_stage(a.ring, misc + B_W, tm, NC);
        load_stage(a.ring + STAGE, misc + B_W, tm, NC + 1);
      }
      mbar_wait(misc + B_W, 0);
    }
    PROF_MARK(1, 5);
  } else {
    __syncthreads();
  }
  if (blockIdx.x == NTILE + 1) return;

  if (wg < 2) {
    asm volatile("setmaxnreg.inc.sync.aligned.u32 232;");
    const Ctx c = make_ctx(base, dry);
    if (dry && c.wg == 1) turn_end(c);
    float own[64];
    float a0, b0, a1, b1;
    PROF_MARK(2, 0);
    mbar_wait(misc + B_X1, dry);
    load_half(c, c.sA, own);
    PROF_MARK(2, 2);
    gemm256<0>(c, c.sX, own, NC + 2 * c.wg);
    PROF_MARK(2, 3);
    ln_stats(c, own, 0.5f, a0, b0, a1, b1);
    store_half(c, c.sA, own, a0, b0, a1, b1);
    fence_async_smem();
    bar_sync(1, 256);
    PROF_MARK(2, 4);
    uint4 dwr[5];
#pragma unroll
    for (int i = 0; i < 5; i++) dwr[i] = __ldg(dw + i * 32 + c.wg * 16 + (c.lane & 15));
    const bool top = c.tid < 8, pub = (top || c.tid >= 120) && !dry;
    uint32_t* halo_out = (uint32_t*)g_halo + (tile * 4 + (top ? (c.tid >> 2) : ((c.tid >> 2) - 28))) * 128 + c.wg * 64 + (c.lane & 3);
#pragma unroll 1
    for (int q = dry; q < 2; q++) {
      float ab[64];
      gemm256<1>(c, c.sA, ab, NC + 4 + 4 * q + 2 * c.wg);
#pragma unroll
      for (int j = 0; j < 4; j++) {
        float g[8];
#pragma unroll
        for (int i = 0; i < 8; i++) g[i] = fmaf(ab[8 * j + i], tanh_fast(ab[32 + 8 * j + i]), ab[8 * j + i]);
        const uint32_t p0 = pack_bf16(g[0], g[1]), p1 = pack_bf16(g[2], g[3]), p2 = pack_bf16(g[4], g[5]), p3 = pack_bf16(g[6], g[7]);
        if (pub) {
          uint32_t* hp = halo_out + q * 32 + j * 8;
          asm volatile("st.relaxed.gpu.global.u32 [%0], %1;" :: "l"(hp), "r"(top ? p0 : p1) : "memory");
          asm volatile("st.relaxed.gpu.global.u32 [%0], %1;" :: "l"(hp + 4), "r"(top ? p2 : p3) : "memory");
        }
        stsm_x4(c.sX + (2 * c.wg + q) * 8192 + c.frag + (((j * 2 + c.hi) ^ c.rsw) << 4), p0, p1, p2, p3);
      }
    }
    bar_sync(3 + c.wg, 128);
    PROF_MARK(2, 5);
    {
      const int wi = c.tid >> 4;
      const uint32_t col = (2 * c.wg + ((c.lane >> 3) & 1)) * 8192, ch = c.lane & 7;
      uint4 r[12];
      const int R0 = row0 + wi * 8;
      const bool first = R0 == 0, last = R0 + 8 == T_;
      const bool far = ((wi == 0 && !first) || (wi == 7 && R0 + 8 < T_)) && !dry;
      const uint4* sp = g_halo + (wi == 0 ? (tile - 1) * 4 + 2 : (tile + 1) * 4) * 32 + c.wg * 16 + (c.lane & 15);
      uint4 h0 = make_uint4(0, 0, 0, 0), h1 = h0;
      auto ld_halo = [&]() {
        asm volatile("ld.relaxed.gpu.global.v4.u32 {%0,%1,%2,%3}, [%4];" : "=r"(h0.x), "=r"(h0.y), "=r"(h0.z), "=r"(h0.w) : "l"(sp) : "memory");
        asm volatile("ld.relaxed.gpu.global.v4.u32 {%0,%1,%2,%3}, [%4];" : "=r"(h1.x), "=r"(h1.y), "=r"(h1.z), "=r"(h1.w) : "l"(sp + 32) : "memory");
      };
      if (far) ld_halo();
#pragma unroll
      for (int i = 0; i < 12; i++) {
        const int row = (wi * 8 - 2 + i) & 63;
        r[i] = lds128(c.sX + col + row * 128 + ((ch ^ (row & 7)) << 4));
      }
      uint32_t w[5][4];
#pragma unroll
      for (int k = 0; k < 5; k++) {
        w[k][0] = bmul2(dwr[k].x, 0x3F003F00u); w[k][1] = bmul2(dwr[k].y, 0x3F003F00u);
        w[k][2] = bmul2(dwr[k].z, 0x3F003F00u); w[k][3] = bmul2(dwr[k].w, 0x3F003F00u);
      }
      auto conv4 = [&](int i0, int i1, int i2, int i3, bool sync) {
        const int rows[4] = {i0, i1, i2, i3};
        uint32_t acc[4][4];
#pragma unroll
        for (int k = 0; k < 5; k++)
#pragma unroll
          for (int j = 0; j < 4; j++) {
            const uint4 x = r[rows[j] + k];
            acc[j][0] = k ? bfma2(x.x, w[k][0], acc[j][0]) : bmul2(x.x, w[0][0]);
            acc[j][1] = k ? bfma2(x.y, w[k][1], acc[j][1]) : bmul2(x.y, w[0][1]);
            acc[j][2] = k ? bfma2(x.z, w[k][2], acc[j][2]) : bmul2(x.z, w[0][2]);
            acc[j][3] = k ? bfma2(x.w, w[k][3], acc[j][3]) : bmul2(x.w, w[0][3]);
          }
#pragma unroll
        for (int j = 0; j < 4; j++)
#pragma unroll
          for (int q = 0; q < 4; q++) acc[j][q] = pack_bf16(silu_half(bf_lo(acc[j][q])), silu_half(bf_hi(acc[j][q])));
        if (sync) bar_sync(3 + c.wg, 128);
#pragma unroll
        for (int j = 0; j < 4; j++)
          sts128(c.sX + col + (wi * 8 + rows[j]) * 128 + ((ch ^ rows[j]) << 4), make_uint4(acc[j][0], acc[j][1], acc[j][2], acc[j][3]));
      };
      conv4(2, 3, 4, 5, true);
      if (far) {
        for (uint32_t n = 0; n < (1u << 18); n++) {
          const uint32_t mx = max(max(max(h0.x, h0.y), max(h0.z, h0.w)), max(max(h1.x, h1.y), max(h1.z, h1.w)));
          if (mx != ~0u) break;
          ld_halo();
        }
      }
      __syncwarp();
      if (first || (far && wi == 0)) { r[0] = h0; r[1] = h1; }
      if (last || (far && wi == 7)) { r[10] = h0; r[11] = h1; }
      conv4(0, 1, 6, 7, false);
    }
    fence_async_smem();
    bar_sync(c.wg == 0 ? 3 : 1, c.wg == 0 ? 128 : 256);
    PROF_MARK(2, 6);
    {
      uint32_t b = stage_wait(c, NC + 12 + c.wg);
      turn_begin(c);
      wg_fence(); piece_ss<0, 0>(c, own, dlo(c.sX, 16), b); wg_commit();
      if (c.wg == 0) { turn_end(c); bar_sync(1, 256); turn_begin(c); }
      b = stage_wait(c, NC + 14 + c.wg);
      wg_fence(); piece_ss<0, 1>(c, own, dlo(c.sX, 16) + 1024, b); wg_commit();
    }
    wg_wait<1>(); stage_release(c, NC + 12 + c.wg);
    wg_wait<0>(); stage_release(c, NC + 14 + c.wg);
    PROF_MARK(2, 7);
    ln_stats(c, own, 0.5f, a0, b0, a1, b1);
    if (c.wg == 1) { turn_begin(c); turn_end(c); }
    store_half(c, c.sA, own, a0, b0, a1, b1);
    fence_async_smem();
    bar_sync(1, 256);
    PROF_MARK(2, 8);
    ff_block(c, NC + 16, own);
    PROF_MARK(2, 9);
    ln_stats(c, own, 1.f, a0, b0, a1, b1);
    store_half(c, c.sX, own, a0, b0, a1, b1);
    fence_async_smem();
    bar_sync(3 + c.wg, 128);
    if (c.tid == 0 && !dry) { tma_store_4d(&tm.Out, c.sX + c.wg * 16384, 0, row0, 2 * c.wg, a.b); bulk_commit(); PROF_MARK(2, 10); bulk_wait_read(); }
    PROF_MARK(2, 11);
  } else {
    asm volatile("setmaxnreg.dec.sync.aligned.u32 24;");
    if (threadIdx.x == 256 && !dry) produce(base + OFF_W, misc + B_FULL, tm, NC + 2, NC + 48);
  }
}

typedef CUresult (*EncodeFn)(CUtensorMap*, CUtensorMapDataType, cuuint32_t, void*, const cuuint64_t*, const cuuint64_t*, const cuuint32_t*,
                             const cuuint32_t*, CUtensorMapInterleave, CUtensorMapSwizzle, CUtensorMapL2promotion, CUtensorMapFloatOOBfill);

CUtensorMap make_map(EncodeFn enc, const void* p, uint64_t d0, uint64_t d1, uint64_t d2, uint64_t s1, uint64_t s2, uint32_t b1, uint32_t b2) {
  CUtensorMap tm;
  cuuint64_t dims[3] = {d0, d1, d2};
  cuuint64_t strides[2] = {s1, s2};
  cuuint32_t box[3] = {64, b1, b2};
  cuuint32_t es[3] = {1, 1, 1};
  enc(&tm, CU_TENSOR_MAP_DATA_TYPE_BFLOAT16, 3, const_cast<void*>(p), dims, strides, box, es, CU_TENSOR_MAP_INTERLEAVE_NONE,
      CU_TENSOR_MAP_SWIZZLE_128B, CU_TENSOR_MAP_L2_PROMOTION_L2_256B, CU_TENSOR_MAP_FLOAT_OOB_FILL_NONE);
  return tm;
}
CUtensorMap blk_map(EncodeFn enc, const void* p, uint64_t rows, uint64_t cols, uint32_t boxrows, uint32_t boxblks) {
  return make_map(enc, p, 64, rows, cols / 64, cols * 2, 128, boxrows, boxblks);
}
CUtensorMap seq_blk_map(EncodeFn enc, const void* p, uint64_t cols, uint32_t boxblks) {
  CUtensorMap tm;
  cuuint64_t dims[4] = {64, T_, cols / 64, 2};
  cuuint64_t strides[3] = {cols * 2, 128, cols * 2 * T_};
  cuuint32_t box[4] = {64, 64, boxblks, 1};
  cuuint32_t es[4] = {1, 1, 1, 1};
  enc(&tm, CU_TENSOR_MAP_DATA_TYPE_BFLOAT16, 4, const_cast<void*>(p), dims, strides, box, es, CU_TENSOR_MAP_INTERLEAVE_NONE,
      CU_TENSOR_MAP_SWIZZLE_128B, CU_TENSOR_MAP_L2_PROMOTION_L2_256B, CU_TENSOR_MAP_FLOAT_OOB_FILL_NONE);
  return tm;
}
CUtensorMap seq_map(EncodeFn enc, const void* p, uint64_t cols, uint32_t boxrows) {
  return make_map(enc, p, cols, T_, 2, cols * 2, cols * 2 * T_, boxrows, 1);
}

}

extern "C" void kernel_launch(void* const* d_in, const int* in_sizes, int n_in, void* d_out, int out_size) {
  (void)in_sizes; (void)n_in; (void)out_size;
  const void *x = d_in[0], *w1a = d_in[1], *w1b = d_in[2], *wqkv = d_in[3], *wo = d_in[4], *pw1 = d_in[5], *dw = d_in[6], *pw2 = d_in[7],
             *w2a = d_in[8], *w2b = d_in[9];
  void* fn = nullptr;
  cudaDriverEntryPointQueryResult qr;
  cudaGetDriverEntryPoint("cuTensorMapEncodeTiled", &fn, cudaEnableDefault, &qr);
  EncodeFn enc = (EncodeFn)fn;
  void* kv;
  cudaGetSymbolAddress(&kv, g_kv);
  cudaFuncSetAttribute(conformer_kernel, cudaFuncAttributeMaxDynamicSharedMemorySize, SMEM_BYTES);

  Wptrs wp;
  const void* ws[8] = {w1a, w1b, wqkv, wo, pw1, pw2, w2a, w2b};
  const uint32_t wb[8] = {524288, 524288, 393216, 131072, 262144, 131072, 524288, 524288};
  for (int i = 0; i < 8; i++) { wp.p[i] = ws[i]; wp.bytes[i] = wb[i]; }
  Maps tm;
  const uint16_t tab[92] = STAGE_TABLE;
  for (int i = 0; i < 92; i++) tm.stage[i] = tab[i];
  tm.X = seq_blk_map(enc, x, 256, 4);
  tm.W1a = blk_map(enc, w1a, 256, 1024, 256, 1);
  tm.W1b = blk_map(enc, w1b, 1024, 256, 64, 4);
  tm.Wqkv = blk_map(enc, wqkv, 256, 768, 128, 2);
  tm.KVst = seq_blk_map(enc, kv, 512, 2);
  tm.KV = seq_map(enc, kv, 512, 80);
  tm.Wo = blk_map(enc, wo, 256, 256, 128, 2);
  tm.Pw1 = make_map(enc, pw1, 256, 256, 2, 1024, 512, 128, 2);
  tm.Pw2 = blk_map(enc, pw2, 256, 256, 128, 2);
  tm.W2a = blk_map(enc, w2a, 256, 1024, 256, 1);
  tm.W2b = blk_map(enc, w2b, 1024, 256, 64, 4);
  tm.Out = seq_blk_map(enc, d_out, 256, 2);
  conformer_kernel<<<NCTA, 512, SMEM_BYTES, cudaStreamPerThread>>>(tm, wp, (const uint4*)dw);
}
```

```cpp
#include <cuda_runtime.h>
#include <cuda_bf16.h>
#include <cuda.h>
#include <stdint.h>

namespace {

constexpr int T_ = 4000;
constexpr int ROWS = 8000;
constexpr int NTILE = 125;
#define NCTA_ 132
constexpr int NCTA = NCTA_;

__device__ __nv_bfloat16 g_qkv[ROWS * 768];
__device__ uint4 g_att[(ROWS / 16) * 16 * 32];
__device__ uint4 g_halo[NTILE * 4 * 32];
__device__ uint32_t g_start;
__device__ uint32_t g_cnt1[4 * 32];
#define PROD_NS 200
#define POLL_NS 100

#define PROF_MARK(k, i) do {} while (0)
#define PROF_STG(n, i) do {} while (0)

__device__ __forceinline__ uint32_t smem_u32(const void* p) { return (uint32_t)__cvta_generic_to_shared(p); }
__device__ __forceinline__ void mbar_init(uint32_t bar, uint32_t cnt) { asm volatile("mbarrier.init.shared::cta.b64 [%0], %1;" :: "r"(bar), "r"(cnt) : "memory"); }
__device__ __forceinline__ void mbar_inval(uint32_t bar) { asm volatile("mbarrier.inval.shared::cta.b64 [%0];" :: "r"(bar) : "memory"); }
__device__ __forceinline__ void mbar_expect_tx(uint32_t bar, uint32_t bytes) { asm volatile("mbarrier.arrive.expect_tx.shared::cta.b64 _, [%0], %1;" :: "r"(bar), "r"(bytes) : "memory"); }
__device__ __forceinline__ void mbar_arrive(uint32_t bar) { asm volatile("mbarrier.arrive.shared::cta.b64 _, [%0];" :: "r"(bar) : "memory"); }
__device__ __forceinline__ void mbar_wait(uint32_t bar, uint32_t parity) {
  asm volatile("{\n.reg .pred p;\n.reg .u32 n;\n"
               "mbarrier.try_wait.parity.shared::cta.b64 p, [%0], %1;\n@p bra DONE_%=;\nmov.u32 n, 0;\n"
               "LOOP_%=:\nmbarrier.try_wait.parity.shared::cta.b64 p, [%0], %1;\n@p bra DONE_%=;\n"
               "add.u32 n, n, 1;\nsetp.lt.u32 p, n, 262144;\n@p bra LOOP_%=;\ntrap;\nDONE_%=:\n}\n" :: "r"(bar), "r"(parity) : "memory");
}
__device__ __forceinline__ void cnt_wait(const uint32_t* p, uint32_t target) {
  asm volatile("{\n.reg .pred p;\n.reg .u32 n, v;\nmov.u32 n, 0;\n"
               "LOOP_%=:\nld.relaxed.gpu.global.u32 v, [%0];\nsub.u32 v, v, %1;\nsetp.ge.s32 p, v, 0;\n@p bra DONE_%=;\n"
               "nanosleep.u32 40;\nadd.u32 n, n, 1;\nsetp.lt.u32 p, n, 262144;\n@p bra LOOP_%=;\ntrap;\nDONE_%=:\n}\n" :: "l"(p), "r"(target) : "memory");
}
__device__ __forceinline__ void cnt_signal(uint32_t* p) {
  asm volatile("red.relaxed.gpu.global.add.u32 [%0], 1;" :: "l"(p) : "memory");
}
__device__ __forceinline__ void tma_load_3d(uint32_t dst, const CUtensorMap* tm, uint32_t bar, int c0, int c1, int c2) {
  asm volatile("cp.async.bulk.tensor.3d.shared::cluster.global.mbarrier::complete_tx::bytes [%0], [%1, {%3, %4, %5}], [%2];"
    :: "r"(dst), "l"(tm), "r"(bar), "r"(c0), "r"(c1), "r"(c2) : "memory");
}
__device__ __forceinline__ void tma_load_3d_pair(uint32_t dst, const CUtensorMap* tm, uint32_t bar, int c0, int c1, int c2) {
  asm volatile("cp.async.bulk.tensor.3d.shared::cluster.global.mbarrier::complete_tx::bytes.multicast::cluster [%0], [%1, {%3, %4, %5}], [%2], %6;"
    :: "r"(dst), "l"(tm), "r"(bar), "r"(c0), "r"(c1), "r"(c2), "h"((uint16_t)3) : "memory");
}
__device__ __forceinline__ void mbar_arrive_peer(uint32_t bar, uint32_t cta) {
  asm volatile("{\n.reg .b32 ra;\nmapa.shared::cluster.u32 ra, %0, %1;\nmbarrier.arrive.relaxed.cluster.shared::cluster.b64 _, [ra];\n}\n" :: "r"(bar), "r"(cta) : "memory");
}
__device__ __forceinline__ void tma_store_3d(const CUtensorMap* tm, uint32_t src, int c0, int c1, int c2) {
  asm volatile("cp.async.bulk.tensor.3d.global.shared::cta.bulk_group [%0, {%2, %3, %4}], [%1];" :: "l"(tm), "r"(src), "r"(c0), "r"(c1), "r"(c2) : "memory");
}
__device__ __forceinline__ void bulk_commit() { asm volatile("cp.async.bulk.commit_group;" ::: "memory"); }
__device__ __forceinline__ void bulk_wait_read() { asm volatile("cp.async.bulk.wait_group.read 0;" ::: "memory"); }
__device__ __forceinline__ void bulk_wait_all() { asm volatile("cp.async.bulk.wait_group 0;" ::: "memory"); }
__device__ __forceinline__ void l2_prefetch(const void* p, uint32_t bytes) { asm volatile("cp.async.bulk.prefetch.L2.global [%0], %1;" :: "l"(p), "r"(bytes) : "memory"); }
__device__ __forceinline__ void prefetch_tmap(const CUtensorMap* tm) { asm volatile("prefetch.tensormap [%0];" :: "l"(tm) : "memory"); }
__device__ __forceinline__ void fence_async_smem() { asm volatile("fence.proxy.async.shared::cta;" ::: "memory"); }
__device__ __forceinline__ void wg_fence() { asm volatile("wgmma.fence.sync.aligned;" ::: "memory"); }
__device__ __forceinline__ void wg_commit() { asm volatile("wgmma.commit_group.sync.aligned;" ::: "memory"); }
template<int N> __device__ __forceinline__ void wg_wait() { asm volatile("wgmma.wait_group.sync.aligned %0;" :: "n"(N) : "memory"); }
__device__ __forceinline__ void bar_sync(int id, int n) { asm volatile("bar.sync %0, %1;" :: "r"(id), "r"(n) : "memory"); }
__device__ __forceinline__ void bar_arrive(int id, int n) { asm volatile("bar.arrive %0, %1;" :: "r"(id), "r"(n) : "memory"); }
__device__ __forceinline__ float ex2(float x) { float y; asm("ex2.approx.ftz.f32 %0, %1;" : "=f"(y) : "f"(x)); return y; }
__device__ __forceinline__ float tanh_fast(float x) { float y; asm("tanh.approx.f32 %0, %1;" : "=f"(y) : "f"(x)); return y; }
__device__ __forceinline__ uint32_t pack_bf16(float lo, float hi) { uint32_t r; asm("cvt.rn.bf16x2.f32 %0, %1, %2;" : "=r"(r) : "f"(hi), "f"(lo)); return r; }
__device__ __forceinline__ uint32_t bmul2(uint32_t a, uint32_t b) { uint32_t d; asm("mul.rn.bf16x2 %0, %1, %2;" : "=r"(d) : "r"(a), "r"(b)); return d; }
__device__ __forceinline__ uint32_t bfma2(uint32_t a, uint32_t b, uint32_t c) { uint32_t d; asm("fma.rn.bf16x2 %0, %1, %2, %3;" : "=r"(d) : "r"(a), "r"(b), "r"(c)); return d; }
__device__ __forceinline__ float bf_lo(uint32_t u) { return __uint_as_float(u << 16); }
__device__ __forceinline__ float bf_hi(uint32_t u) { return __uint_as_float(u & 0xffff0000u); }
__device__ __forceinline__ void ldsm_x4(uint32_t addr, uint32_t& r0, uint32_t& r1, uint32_t& r2, uint32_t& r3) {
  asm volatile("ldmatrix.sync.aligned.m8n8.x4.shared.b16 {%0,%1,%2,%3}, [%4];" : "=r"(r0), "=r"(r1), "=r"(r2), "=r"(r3) : "r"(addr) : "memory");
}
__device__ __forceinline__ void stsm_x4(uint32_t addr, uint32_t r0, uint32_t r1, uint32_t r2, uint32_t r3) {
  asm volatile("stmatrix.sync.aligned.m8n8.x4.shared.b16 [%0], {%1,%2,%3,%4};" :: "r"(addr), "r"(r0), "r"(r1), "r"(r2), "r"(r3) : "memory");
}
__device__ __forceinline__ void sts128(uint32_t addr, uint4 v) { asm volatile("st.shared.v4.b32 [%0], {%1,%2,%3,%4};" :: "r"(addr), "r"(v.x), "r"(v.y), "r"(v.z), "r"(v.w) : "memory"); }
__device__ __forceinline__ uint4 lds128(uint32_t addr) { uint4 v; asm volatile("ld.shared.v4.b32 {%0,%1,%2,%3}, [%4];" : "=r"(v.x), "=r"(v.y), "=r"(v.z), "=r"(v.w) : "r"(addr) : "memory"); return v; }
__device__ __forceinline__ void sts64f(uint32_t addr, float a, float b) { asm volatile("st.shared.v2.f32 [%0], {%1,%2};" :: "r"(addr), "f"(a), "f"(b) : "memory"); }
__device__ __forceinline__ float2 lds64f(uint32_t addr) { float2 v; asm volatile("ld.shared.v2.f32 {%0,%1}, [%2];" : "=f"(v.x), "=f"(v.y) : "r"(addr) : "memory"); return v; }
__device__ __forceinline__ uint32_t dlo(uint32_t addr, uint32_t lbo) { return ((addr & 0x3FFFF) >> 4) | ((lbo >> 4) << 16); }

template<int SD> __device__ __forceinline__ void wg_ss_n128_tb1(float (&d)[64], uint32_t da, uint32_t db) {
  asm volatile("{\n.reg .b64 da, db;\nmov.b64 da, {%64, 0x40000040};\nmov.b64 db, {%65, 0x40000040};\n"
    "wgmma.mma_async.sync.aligned.m64n128k16.f32.bf16.bf16 {%0, %1, %2, %3, %4, %5, %6, %7, %8, %9, %10, %11, %12, %13, %14, %15, %16, %17, %18, %19, %20, %21, %22, %23, %24, %25, %26, %27, %28, %29, %30, %31, %32, %33, %34, %35, %36, %37, %38, %39, %40, %41, %42, %43, %44, %45, %46, %47, %48, %49, %50, %51, %52, %53, %54, %55, %56, %57, %58, %59, %60, %61, %62, %63}, da, db, %66, 1, 1, 0, 1;\n}\n"
    : "+f"(d[0]), "+f"(d[1]), "+f"(d[2]), "+f"(d[3]), "+f"(d[4]), "+f"(d[5]), "+f"(d[6]), "+f"(d[7]), "+f"(d[8]), "+f"(d[9]), "+f"(d[10]), "+f"(d[11]), "+f"(d[12]), "+f"(d[13]), "+f"(d[14]), "+f"(d[15]), "+f"(d[16]), "+f"(d[17]), "+f"(d[18]), "+f"(d[19]), "+f"(d[20]), "+f"(d[21]), "+f"(d[22]), "+f"(d[23]), "+f"(d[24]), "+f"(d[25]), "+f"(d[26]), "+f"(d[27]), "+f"(d[28]), "+f"(d[29]), "+f"(d[30]), "+f"(d[31]), "+f"(d[32]), "+f"(d[33]), "+f"(d[34]), "+f"(d[35]), "+f"(d[36]), "+f"(d[37]), "+f"(d[38]), "+f"(d[39]), "+f"(d[40]), "+f"(d[41]), "+f"(d[42]), "+f"(d[43]), "+f"(d[44]), "+f"(d[45]), "+f"(d[46]), "+f"(d[47]), "+f"(d[48]), "+f"(d[49]), "+f"(d[50]), "+f"(d[51]), "+f"(d[52]), "+f"(d[53]), "+f"(d[54]), "+f"(d[55]), "+f"(d[56]), "+f"(d[57]), "+f"(d[58]), "+f"(d[59]), "+f"(d[60]), "+f"(d[61]), "+f"(d[62]), "+f"(d[63])
    : "r"(da), "r"(db), "n"(SD));
}
template<int SD> __device__ __forceinline__ void wg_rs_n128_tb1(float (&d)[64], uint32_t a0, uint32_t a1, uint32_t a2, uint32_t a3, uint32_t db) {
  asm volatile("{\n.reg .b64 db;\nmov.b64 db, {%68, 0x40000040};\n"
    "wgmma.mma_async.sync.aligned.m64n128k16.f32.bf16.bf16 {%0, %1, %2, %3, %4, %5, %6, %7, %8, %9, %10, %11, %12, %13, %14, %15, %16, %17, %18, %19, %20, %21, %22, %23, %24, %25, %26, %27, %28, %29, %30, %31, %32, %33, %34, %35, %36, %37, %38, %39, %40, %41, %42, %43, %44, %45, %46, %47, %48, %49, %50, %51, %52, %53, %54, %55, %56, %57, %58, %59, %60, %61, %62, %63}, {%64, %65, %66, %67}, db, %69, 1, 1, 1;\n}\n"
    : "+f"(d[0]), "+f"(d[1]), "+f"(d[2]), "+f"(d[3]), "+f"(d[4]), "+f"(d[5]), "+f"(d[6]), "+f"(d[7]), "+f"(d[8]), "+f"(d[9]), "+f"(d[10]), "+f"(d[11]), "+f"(d[12]), "+f"(d[13]), "+f"(d[14]), "+f"(d[15]), "+f"(d[16]), "+f"(d[17]), "+f"(d[18]), "+f"(d[19]), "+f"(d[20]), "+f"(d[21]), "+f"(d[22]), "+f"(d[23]), "+f"(d[24]), "+f"(d[25]), "+f"(d[26]), "+f"(d[27]), "+f"(d[28]), "+f"(d[29]), "+f"(d[30]), "+f"(d[31]), "+f"(d[32]), "+f"(d[33]), "+f"(d[34]), "+f"(d[35]), "+f"(d[36]), "+f"(d[37]), "+f"(d[38]), "+f"(d[39]), "+f"(d[40]), "+f"(d[41]), "+f"(d[42]), "+f"(d[43]), "+f"(d[44]), "+f"(d[45]), "+f"(d[46]), "+f"(d[47]), "+f"(d[48]), "+f"(d[49]), "+f"(d[50]), "+f"(d[51]), "+f"(d[52]), "+f"(d[53]), "+f"(d[54]), "+f"(d[55]), "+f"(d[56]), "+f"(d[57]), "+f"(d[58]), "+f"(d[59]), "+f"(d[60]), "+f"(d[61]), "+f"(d[62]), "+f"(d[63])
    : "r"(a0), "r"(a1), "r"(a2), "r"(a3), "r"(db), "n"(SD));
}
template<int SD> __device__ __forceinline__ void wg_ss_n64_tb1(float (&d)[32], uint32_t da, uint32_t db) {
  asm volatile("{\n.reg .b64 da, db;\nmov.b64 da, {%32, 0x40000040};\nmov.b64 db, {%33, 0x40000040};\n"
    "wgmma.mma_async.sync.aligned.m64n64k16.f32.bf16.bf16 {%0, %1, %2, %3, %4, %5, %6, %7, %8, %9, %10, %11, %12, %13, %14, %15, %16, %17, %18, %19, %20, %21, %22, %23, %24, %25, %26, %27, %28, %29, %30, %31}, da, db, %34, 1, 1, 0, 1;\n}\n"
    : "+f"(d[0]), "+f"(d[1]), "+f"(d[2]), "+f"(d[3]), "+f"(d[4]), "+f"(d[5]), "+f"(d[6]), "+f"(d[7]), "+f"(d[8]), "+f"(d[9]), "+f"(d[10]), "+f"(d[11]), "+f"(d[12]), "+f"(d[13]), "+f"(d[14]), "+f"(d[15]), "+f"(d[16]), "+f"(d[17]), "+f"(d[18]), "+f"(d[19]), "+f"(d[20]), "+f"(d[21]), "+f"(d[22]), "+f"(d[23]), "+f"(d[24]), "+f"(d[25]), "+f"(d[26]), "+f"(d[27]), "+f"(d[28]), "+f"(d[29]), "+f"(d[30]), "+f"(d[31])
    : "r"(da), "r"(db), "n"(SD));
}
template<int SD> __device__ __forceinline__ void wg_ss_n80_tb0(float (&d)[40], uint32_t da, uint32_t db) {
  asm volatile("{\n.reg .b64 da, db;\nmov.b64 da, {%40, 0x40000040};\nmov.b64 db, {%41, 0x40000040};\n"
    "wgmma.mma_async.sync.aligned.m64n80k16.f32.bf16.bf16 {%0, %1, %2, %3, %4, %5, %6, %7, %8, %9, %10, %11, %12, %13, %14, %15, %16, %17, %18, %19, %20, %21, %22, %23, %24, %25, %26, %27, %28, %29, %30, %31, %32, %33, %34, %35, %36, %37, %38, %39}, da, db, %42, 1, 1, 0, 0;\n}\n"
    : "+f"(d[0]), "+f"(d[1]), "+f"(d[2]), "+f"(d[3]), "+f"(d[4]), "+f"(d[5]), "+f"(d[6]), "+f"(d[7]), "+f"(d[8]), "+f"(d[9]), "+f"(d[10]), "+f"(d[11]), "+f"(d[12]), "+f"(d[13]), "+f"(d[14]), "+f"(d[15]), "+f"(d[16]), "+f"(d[17]), "+f"(d[18]), "+f"(d[19]), "+f"(d[20]), "+f"(d[21]), "+f"(d[22]), "+f"(d[23]), "+f"(d[24]), "+f"(d[25]), "+f"(d[26]), "+f"(d[27]), "+f"(d[28]), "+f"(d[29]), "+f"(d[30]), "+f"(d[31]), "+f"(d[32]), "+f"(d[33]), "+f"(d[34]), "+f"(d[35]), "+f"(d[36]), "+f"(d[37]), "+f"(d[38]), "+f"(d[39])
    : "r"(da), "r"(db), "n"(SD));
}
template<int SD> __device__ __forceinline__ void wg_rs_n64_tb1(float (&d)[32], uint32_t a0, uint32_t a1, uint32_t a2, uint32_t a3, uint32_t db) {
  asm volatile("{\n.reg .b64 db;\nmov.b64 db, {%36, 0x40000040};\n"
    "wgmma.mma_async.sync.aligned.m64n64k16.f32.bf16.bf16 {%0, %1, %2, %3, %4, %5, %6, %7, %8, %9, %10, %11, %12, %13, %14, %15, %16, %17, %18, %19, %20, %21, %22, %23, %24, %25, %26, %27, %28, %29, %30, %31}, {%32, %33, %34, %35}, db, %37, 1, 1, 1;\n}\n"
    : "+f"(d[0]), "+f"(d[1]), "+f"(d[2]), "+f"(d[3]), "+f"(d[4]), "+f"(d[5]), "+f"(d[6]), "+f"(d[7]), "+f"(d[8]), "+f"(d[9]), "+f"(d[10]), "+f"(d[11]), "+f"(d[12]), "+f"(d[13]), "+f"(d[14]), "+f"(d[15]), "+f"(d[16]), "+f"(d[17]), "+f"(d[18]), "+f"(d[19]), "+f"(d[20]), "+f"(d[21]), "+f"(d[22]), "+f"(d[23]), "+f"(d[24]), "+f"(d[25]), "+f"(d[26]), "+f"(d[27]), "+f"(d[28]), "+f"(d[29]), "+f"(d[30]), "+f"(d[31])
    : "r"(a0), "r"(a1), "r"(a2), "r"(a3), "r"(db), "n"(SD));
}

constexpr int RING = 5;
constexpr uint32_t STAGE = 32768;
constexpr uint32_t OFF_X = 32768, OFF_W = 65536, OFF_MISC = OFF_W + RING * STAGE;
constexpr int SMEM_BYTES = OFF_MISC + 256 + 1024 + 1024;

struct Ctx {
  uint32_t sA, sX, sW, full, empty, stats;
  uint32_t frag;
  uint32_t rsw;
  uint32_t hi;
  int wg, tid, lane;
  int pk;
  uint32_t dry;
};
__device__ __forceinline__ uint32_t stage_wait(const Ctx& c, int n) {
  const int q = n / RING, s = n - q * RING;
  if (c.tid == 0) PROF_STG(n + c.pk, 1);
  mbar_wait(c.full + 8 * s, (q | c.dry) & 1);
  if (c.tid == 0) PROF_STG(n + c.pk, 2);
  return dlo(c.sW + s * STAGE, 0);
}
__device__ __forceinline__ void stage_release(const Ctx& c, int n) {
  const int s = n % RING;
  if (c.tid == 0) { mbar_arrive(c.empty + 8 * s); PROF_STG(n + c.pk, 3); }
}
__device__ __forceinline__ void turn_begin(const Ctx& c) { bar_sync(5 + c.wg, 256); }
__device__ __forceinline__ void turn_end(const Ctx& c) { bar_arrive(5 + (c.wg ^ 1), 256); }
template<int FIRST, int LAST> __device__ __forceinline__ void piece_ss(const Ctx& c, float (&acc)[64], uint32_t dA, uint32_t dB) {
  dB += (16384 >> 4) << 16;
  wg_ss_n128_tb1<FIRST ? 0 : 1>(acc, dA, dB);
#pragma unroll
  for (int kk = 1; kk < 8; kk++) {
    wg_ss_n128_tb1<1>(acc, dA + (kk >> 2) * 512 + (kk & 3) * 2, dB + kk * 128);
  }
  if (LAST) turn_end(c);
}
__device__ __forceinline__ void ff_g1(const Ctx& c, float (&h)[32], uint32_t dA, uint32_t dB) {
  wg_ss_n64_tb1<0>(h, dA, dB);
#pragma unroll
  for (int kk = 1; kk < 16; kk++) {
    wg_ss_n64_tb1<1>(h, dA + (kk >> 2) * 512 + (kk & 3) * 2, dB + kk * 128);
  }
}
__device__ __forceinline__ void ff_g2(float (&acc)[64], const uint32_t (&P)[16], uint32_t dB, int half) {
  dB += ((8192 >> 4) << 16) + half * 1024;
#pragma unroll
  for (int kk = 0; kk < 4; kk++) wg_rs_n128_tb1<1>(acc, P[4 * kk], P[4 * kk + 1], P[4 * kk + 2], P[4 * kk + 3], dB + kk * 128);
}
struct NoHook { __device__ __forceinline__ void operator()() const {} };
template<int FIRST, class Hook = NoHook> __device__ __forceinline__ void gemm256(const Ctx& c, float (&acc)[64], int n, Hook hook = Hook()) {
  const uint32_t dA = dlo(c.sA, 16);
  uint32_t b = stage_wait(c, n);
  turn_begin(c);
  wg_fence(); piece_ss<FIRST, 0>(c, acc, dA, b); wg_commit();
  b = stage_wait(c, n + 1);
  wg_fence(); piece_ss<0, 1>(c, acc, dA + 1024, b); wg_commit();
  hook();
  wg_wait<1>(); stage_release(c, n);
  wg_wait<0>(); stage_release(c, n + 1);
}
__device__ __forceinline__ uint32_t frag_addr(const Ctx& c, uint32_t tile, int j) {
  return tile + (2 * c.wg + (j >> 2)) * 8192 + c.frag + ((((j & 3) * 2 + c.hi) ^ c.rsw) << 4);
}
__device__ __forceinline__ void load_half(const Ctx& c, uint32_t tile, float (&v)[64]) {
#pragma unroll
  for (int j = 0; j < 8; j++) {
    uint32_t r0, r1, r2, r3;
    ldsm_x4(frag_addr(c, tile, j), r0, r1, r2, r3);
    v[8 * j] = bf_lo(r0); v[8 * j + 1] = bf_hi(r0); v[8 * j + 2] = bf_lo(r1); v[8 * j + 3] = bf_hi(r1);
    v[8 * j + 4] = bf_lo(r2); v[8 * j + 5] = bf_hi(r2); v[8 * j + 6] = bf_lo(r3); v[8 * j + 7] = bf_hi(r3);
  }
}
__device__ __forceinline__ void store_half(const Ctx& c, uint32_t tile, const float (&v)[64], float a0, float b0, float a1, float b1) {
#pragma unroll
  for (int j = 0; j < 8; j++)
    stsm_x4(frag_addr(c, tile, j),
            pack_bf16(fmaf(v[8 * j], a0, b0), fmaf(v[8 * j + 1], a0, b0)), pack_bf16(fmaf(v[8 * j + 2], a1, b1), fmaf(v[8 * j + 3], a1, b1)),
            pack_bf16(fmaf(v[8 * j + 4], a0, b0), fmaf(v[8 * j + 5], a0, b0)), pack_bf16(fmaf(v[8 * j + 6], a1, b1), fmaf(v[8 * j + 7], a1, b1)));
}
__device__ __forceinline__ void store_half_raw(const Ctx& c, uint32_t tile, const float (&v)[64]) {
#pragma unroll
  for (int j = 0; j < 8; j++)
    stsm_x4(frag_addr(c, tile, j), pack_bf16(v[8 * j], v[8 * j + 1]), pack_bf16(v[8 * j + 2], v[8 * j + 3]),
            pack_bf16(v[8 * j + 4], v[8 * j + 5]), pack_bf16(v[8 * j + 6], v[8 * j + 7]));
}
__device__ __forceinline__ void ln_stats(const Ctx& c, const float (&v)[64], float scale, float& a0, float& b0, float& a1, float& b1) {
  float s0 = 0.f, s1 = 0.f, q0 = 0.f, q1 = 0.f, s2 = 0.f, s3 = 0.f, q2 = 0.f, q3 = 0.f;
#pragma unroll
  for (int i = 0; i < 16; i++) {
    s0 += v[4 * i]; q0 = fmaf(v[4 * i], v[4 * i], q0);
    s2 += v[4 * i + 1]; q2 = fmaf(v[4 * i + 1], v[4 * i + 1], q2);
    s1 += v[4 * i + 2]; q1 = fmaf(v[4 * i + 2], v[4 * i + 2], q1);
    s3 += v[4 * i + 3]; q3 = fmaf(v[4 * i + 3], v[4 * i + 3], q3);
  }
  s0 += s2; q0 += q2; s1 += s3; q1 += q3;
  s0 += __shfl_xor_sync(0xffffffff, s0, 1); q0 += __shfl_xor_sync(0xffffffff, q0, 1);
  s1 += __shfl_xor_sync(0xffffffff, s1, 1); q1 += __shfl_xor_sync(0xffffffff, q1, 1);
  s0 += __shfl_xor_sync(0xffffffff, s0, 2); q0 += __shfl_xor_sync(0xffffffff, q0, 2);
  s1 += __shfl_xor_sync(0xffffffff, s1, 2); q1 += __shfl_xor_sync(0xffffffff, q1, 2);
  const uint32_t row = (c.tid >> 5) * 16 + (c.lane >> 2);
  if ((c.lane & 3) == 0) {
    sts64f(c.stats + c.wg * 512 + row * 8, s0, q0);
    sts64f(c.stats + c.wg * 512 + (row + 8) * 8, s1, q1);
  }
  bar_sync(1, 256);
  const float2 o0 = lds64f(c.stats + (c.wg ^ 1) * 512 + row * 8), o1 = lds64f(c.stats + (c.wg ^ 1) * 512 + (row + 8) * 8);
  const float m0 = (s0 + o0.x) * (1.f / 256.f), m1 = (s1 + o1.x) * (1.f / 256.f);
  const float var0 = fmaxf(fmaf(-m0, m0, (q0 + o0.y) * (1.f / 256.f)), 0.f), var1 = fmaxf(fmaf(-m1, m1, (q1 + o1.y) * (1.f / 256.f)), 0.f);
  a0 = rsqrtf(var0 + 1e-5f) * scale; a1 = rsqrtf(var1 + 1e-5f) * scale;
  b0 = -m0 * a0; b1 = -m1 * a1;
}
__device__ __forceinline__ float silu_half(float h) { return fmaf(h, tanh_fast(h), h); }
__device__ __forceinline__ float silu_quarter(float h) { const float q = 0.5f * h; return fmaf(q, tanh_fast(h), q); }
__device__ __forceinline__ void silu_pack(const float (&acc)[32], uint32_t (&P)[16]) {
#pragma unroll
  for (int i = 0; i < 16; i++) P[i] = pack_bf16(silu_quarter(acc[2 * i]), silu_quarter(acc[2 * i + 1]));
}
__device__ __forceinline__ void ff_block(const Ctx& c, int n0, float (&own)[64]) {
  float oth[64], h[32];
  uint32_t P[16];
#pragma unroll
  for (int i = 0; i < 64; i++) oth[i] = 0.f;
  const uint32_t dA = dlo(c.sA, 16);
  {
    const uint32_t b = stage_wait(c, n0 + c.wg);
    turn_begin(c);
    wg_fence(); ff_g1(c, h, dA, b); wg_commit();
    turn_end(c);
    wg_wait<0>(); stage_release(c, n0 + c.wg);
    silu_pack(h, P);
  }
#pragma unroll 1
  for (int it = c.dry ? 7 : 1; it < 8; it++) {
    const int n = n0 + 4 * it - 2 + 2 * c.wg;
    uint32_t b = stage_wait(c, n);
    turn_begin(c);
    wg_fence(); ff_g2(own, P, b, c.wg); ff_g2(oth, P, b, c.wg ^ 1); wg_commit();
    b = stage_wait(c, n + 1);
    wg_fence(); ff_g1(c, h, dA, b); wg_commit();
    turn_end(c);
    wg_wait<1>(); stage_release(c, n);
    wg_wait<0>(); stage_release(c, n + 1);
    silu_pack(h, P);
  }
  if (c.wg == 0) bar_arrive(2, 256);
  {
    const int n = n0 + 30 + c.wg;
    const uint32_t b = stage_wait(c, n);
    turn_begin(c);
    wg_fence(); ff_g2(oth, P, b, c.wg ^ 1); wg_commit();
    ff_g2(own, P, b, c.wg); wg_commit();
    turn_end(c);
    wg_wait<1>();
    if (c.wg == 1) bar_sync(2, 256);
    const uint32_t e = (c.wg == 0 ? c.sX : c.sA) + c.tid * 16;
#pragma unroll
    for (int i = 0; i < 16; i++)
      sts128(e + i * 2048, make_uint4(__float_as_uint(oth[4 * i]), __float_as_uint(oth[4 * i + 1]), __float_as_uint(oth[4 * i + 2]), __float_as_uint(oth[4 * i + 3])));
    wg_wait<0>(); stage_release(c, n);
  }
  bar_sync(1, 256);
  const uint32_t e = (c.wg == 0 ? c.sA : c.sX) + c.tid * 16;
#pragma unroll
  for (int i = 0; i < 16; i++) {
    const uint4 u = lds128(e + i * 2048);
    own[4 * i] += __uint_as_float(u.x); own[4 * i + 1] += __uint_as_float(u.y);
    own[4 * i + 2] += __uint_as_float(u.z); own[4 * i + 3] += __uint_as_float(u.w);
  }
}
#define WDIV 1
struct Maps { CUtensorMap X, W1a, W1b, Wqkv, QKVst, Q, KV, Wo, Pw1, Pw2, W2a, W2b, Out; uint16_t stage[92]; };
constexpr int NA = 44;
constexpr int NC = 45;
#define STAGE_TABLE {0x1, 0x11, 0x2, 0x21, 0x102, 0x31, 0x202, 0x41, 0x302, 0x51, 0x402, 0x61, 0x502, 0x71, 0x602, 0x81, 0x702, 0x91, 0x802, 0xa1, 0x902, 0xb1, 0xa02, 0xc1, 0xb02, 0xd1, 0xc02, 0xe1, 0xd02, 0xf1, 0xe02, 0xf02, 0x3, 0x203, 0x23, 0x223, 0x43, 0x243, 0x63, 0x263, 0x83, 0x283, 0xa3, 0x2a3, 0x7, 0x207, 0x27, 0x227, 0x8, 0x208, 0x2008, 0x2208, 0x1008, 0x1208, 0x3008, 0x3208, 0x9, 0x29, 0x209, 0x229, 0xa, 0x1a, 0xb, 0x2a, 0x10b, 0x3a, 0x20b, 0x4a, 0x30b, 0x5a, 0x40b, 0x6a, 0x50b, 0x7a, 0x60b, 0x8a, 0x70b, 0x9a, 0x80b, 0xaa, 0x90b, 0xba, 0xa0b, 0xca, 0xb0b, 0xda, 0xc0b, 0xea, 0xd0b, 0xfa, 0xe0b, 0xf0b}
__device__ __forceinline__ void load_stage(uint32_t dst, uint32_t bar, const Maps& tm, int n) {
  const uint32_t e = tm.stage[n - (n > NA)];
  mbar_expect_tx(bar, STAGE / WDIV);
  tma_load_3d(dst, &tm.X + (e & 15), bar, (e >> 12) * 64, ((e >> 8) & 15) * 64, (e >> 4) & 15);
}
#define MC_SEL(n) 1
__device__ __forceinline__ void produce(uint32_t sW, uint32_t full, uint32_t pfree, bool pair, const Maps& tm, int n0, int n1) {
  const uint32_t rank = blockIdx.x & 1;
  uint32_t s = n0 % RING, ph = ((n0 / RING) & 1) ^ 1, pf = 0;
  if (n0 > NA)
    for (int n = RING; n < NA; n++) if (MC_SEL(n) && (n & 1) == rank) pf ^= 1u << (n % RING);
#pragma unroll 1
  for (int n = n0; n < n1; n++) {
    mbar_wait(full + 8 * RING + 8 * s, ph);
    PROF_STG(n, 0);
    if (!pair || !(MC_SEL(n))) {
      load_stage(sW + s * STAGE, full + 8 * s, tm, n);
    } else {
      mbar_expect_tx(full + 8 * s, STAGE);
      if ((n & 1) == rank) {
        const uint32_t e = tm.stage[n - (n > NA)];
        mbar_wait(pfree + 8 * s, (pf >> s) & 1);
        pf ^= 1u << s;
        tma_load_3d_pair(sW + s * STAGE, &tm.X + (e & 15), full + 8 * s, (e >> 12) * 64, ((e >> 8) & 15) * 64, (e >> 4) & 15);
      } else {
        mbar_arrive_peer(pfree + 8 * s, rank ^ 1);
      }
    }
    if (++s == RING) { s = 0; ph ^= 1; }
  }
}
__device__ __forceinline__ Ctx make_ctx(uint32_t base, uint32_t dry, int pk = 0) {
  Ctx c; c.pk = pk; c.dry = dry;
  c.sA = base; c.sX = base + OFF_X; c.sW = base + OFF_W;
  c.full = base + OFF_MISC; c.empty = c.full + 8 * RING; c.stats = base + OFF_MISC + 256;
  c.wg = __shfl_sync(0xffffffff, (int)(threadIdx.x >> 7), 0);
  c.tid = threadIdx.x & 127; c.lane = threadIdx.x & 31;
  const uint32_t r = (c.tid >> 5) * 16 + (c.lane & 7) + ((c.lane >> 3) & 1) * 8;
  c.frag = r * 128; c.rsw = r & 7; c.hi = c.lane >> 4;
  return c;
}

constexpr int NSTG = 4;
constexpr int KVB = 160 * 128;
constexpr int NKV = T_ / 160;
static_assert(NSTG * 2 * KVB == RING * STAGE, "the K/V ring reuses the weight ring");

struct AttCtx { uint32_t sKV, full, empty, dry, wfull; const Maps* tm; int h, b, wg; };
__device__ __forceinline__ int kv_slot(int i) { return (i + 3) & 3; }
__device__ __forceinline__ void att_load(const AttCtx& a, int i, int v) {
  const int s = i & 3;
  mbar_expect_tx(a.full + 8 * (s + v * NSTG), KVB);
  tma_load_3d(a.sKV + kv_slot(i) * 2 * KVB + v * KVB, &a.tm->KV, a.full + 8 * (s + v * NSTG), 256 + v * 256 + a.h * 64, i * 160, a.b);
}
__device__ __forceinline__ void att_load_stage(const AttCtx& a, int i) { att_load(a, i, 0); att_load(a, i, 1); }
__device__ __forceinline__ void att_init_bars(const AttCtx& a) {
  for (int i = 0; i < NSTG; i++) { mbar_init(a.full + 8 * i, 1); mbar_init(a.full + 8 * (NSTG + i), 1); mbar_init(a.empty + 8 * i, 4); }
}
__device__ __forceinline__ void att_qk(float (&S)[40], uint32_t dQ, uint32_t kd) {
  wg_ss_n80_tb0<0>(S, dQ, kd);
#pragma unroll
  for (int kk = 1; kk < 4; kk++) wg_ss_n80_tb0<1>(S, dQ + kk * 2, kd + kk * 2);
}
__device__ __forceinline__ void att_pv(float (&O)[32], const uint32_t (&P)[20], uint32_t vd) {
#pragma unroll
  for (int kk = 0; kk < 5; kk++) wg_rs_n64_tb1<1>(O, P[kk * 4], P[kk * 4 + 1], P[kk * 4 + 2], P[kk * 4 + 3], vd + kk * 128);
}
template<bool SAFE>
__device__ __forceinline__ void att_softmax(const float (&S)[40], uint32_t (&P)[20], float (&O)[32], float& m0, float& m1, float& l0, float& l1) {
  if (SAFE) {
    float x0 = fmaxf(S[0], S[1]), x1 = fmaxf(S[2], S[3]);
#pragma unroll
    for (int i = 1; i < 10; i++) { x0 = fmaxf(x0, fmaxf(S[4 * i], S[4 * i + 1])); x1 = fmaxf(x1, fmaxf(S[4 * i + 2], S[4 * i + 3])); }
    x0 = fmaxf(x0, __shfl_xor_sync(0xffffffff, x0, 1)); x1 = fmaxf(x1, __shfl_xor_sync(0xffffffff, x1, 1));
    x0 = fmaxf(x0, __shfl_xor_sync(0xffffffff, x0, 2)); x1 = fmaxf(x1, __shfl_xor_sync(0xffffffff, x1, 2));
    const float n0 = fmaxf(m0, x0), n1 = fmaxf(m1, x1);
    const float f0 = ex2(m0 - n0), f1 = ex2(m1 - n1);
    m0 = n0; m1 = n1; l0 *= f0; l1 *= f1;
#pragma unroll
    for (int i = 0; i < 8; i++) { O[4 * i] *= f0; O[4 * i + 1] *= f0; O[4 * i + 2] *= f1; O[4 * i + 3] *= f1; }
  }
#pragma unroll
  for (int i = 0; i < 10; i++) {
    float p0, p1, p2, p3;
    if (SAFE) { p0 = ex2(S[4 * i] - m0); p1 = ex2(S[4 * i + 1] - m0); p2 = ex2(S[4 * i + 2] - m1); p3 = ex2(S[4 * i + 3] - m1); }
    else { p0 = ex2(S[4 * i]); p1 = ex2(S[4 * i + 1]); p2 = ex2(S[4 * i + 2]); p3 = ex2(S[4 * i + 3]); }
    l0 += p0 + p1; l1 += p2 + p3;
    P[2 * i] = pack_bf16(p0, p1); P[2 * i + 1] = pack_bf16(p2, p3);
  }
}
template<bool SAFE>
__device__ __forceinline__ void att_refill(const AttCtx& a, int it) {
  if ((threadIdx.x & 127) == 0) {
    mbar_arrive(a.empty + 8 * (it & 3));
    if (a.wg == (it & 3) && it >= 1 && !a.dry) {
      const bool kv = it - 1 + NSTG < NKV;
      if (kv || (!SAFE && a.wfull)) {
        mbar_wait(a.empty + 8 * ((it - 1) & 3), ((it - 1) >> 2) & 1);
        if (kv) att_load_stage(a, it - 1 + NSTG);
        else load_stage(a.sKV + (it - 22) * STAGE, a.wfull + 8 * (it - 22), *a.tm, NC + it - 22);
      }
    }
  }
  __syncwarp();
}
constexpr uint32_t KV_STG = 2 * KVB / 16, KV_VOFF = KVB / 16, KV_HALF = 80 * 128 / 16;
template<bool SAFE>
__device__ __forceinline__ void att_pass(const AttCtx& a, uint32_t dQ, float (&O)[32], float& l0, float& l1) {
  float S[40];
  uint32_t P[20];
  float m0 = -INFINITY, m1 = -INFINITY;
  l0 = 0.f; l1 = 0.f;
#pragma unroll
  for (int i = 0; i < 32; i++) O[i] = 0.f;
  const uint32_t dKV = dlo(a.sKV, 16);
  if (SAFE) {
#pragma unroll 1
    for (int j = 0; j < 2 * NKV; j++) {
      const int it = j >> 1, s = it & 3;
      const uint32_t kb = dKV + kv_slot(it) * KV_STG + (j & 1) * KV_HALF;
      mbar_wait(a.full + 8 * s, (it >> 2) & 1);
      wg_fence(); att_qk(S, dQ, kb); wg_commit(); wg_wait<0>();
      att_softmax<true>(S, P, O, m0, m1, l0, l1);
      mbar_wait(a.full + 8 * (NSTG + s), (it >> 2) & 1);
      wg_fence(); att_pv(O, P, kb + KV_VOFF); wg_commit(); wg_wait<0>();
      if (j & 1) att_refill<true>(a, it);
    }
  } else {
    mbar_wait(a.full, a.dry);
    wg_fence(); att_qk(S, dQ, dKV + 3 * KV_STG); wg_commit(); wg_wait<0>();
    att_softmax<false>(S, P, O, m0, m1, l0, l1);
    mbar_wait(a.full + 8 * NSTG, a.dry);
    wg_fence(); att_pv(O, P, dKV + 3 * KV_STG + KV_VOFF); att_qk(S, dQ, dKV + 3 * KV_STG + KV_HALF); wg_commit(); wg_wait<0>();
#pragma unroll 1
    for (int it = a.dry ? NKV - 2 : 0; it < NKV - 1; it++) {
      const int sn = (it + 1) & 3;
      const uint32_t kb = dKV + kv_slot(it) * KV_STG, kn = dKV + kv_slot(it + 1) * KV_STG, par = (((it + 1) >> 2) | a.dry) & 1;
      att_softmax<false>(S, P, O, m0, m1, l0, l1);
      mbar_wait(a.full + 8 * sn, par);
      wg_fence(); att_pv(O, P, kb + KV_VOFF + KV_HALF); att_qk(S, dQ, kn); wg_commit(); wg_wait<0>();
      att_refill<false>(a, it);
      att_softmax<false>(S, P, O, m0, m1, l0, l1);
      mbar_wait(a.full + 8 * (NSTG + sn), par);
      wg_fence(); att_pv(O, P, kn + KV_VOFF); att_qk(S, dQ, kn + KV_HALF); wg_commit(); wg_wait<0>();
    }
    att_softmax<false>(S, P, O, m0, m1, l0, l1);
    wg_fence(); att_pv(O, P, dKV + 3 * KV_STG + KV_VOFF + KV_HALF); wg_commit(); wg_wait<0>();
  }
  l0 += __shfl_xor_sync(0xffffffff, l0, 1); l1 += __shfl_xor_sync(0xffffffff, l1, 1);
  l0 += __shfl_xor_sync(0xffffffff, l0, 2); l1 += __shfl_xor_sync(0xffffffff, l1, 2);
}

struct Wptrs { const void* p[8]; uint32_t bytes[8]; };

constexpr uint32_t B_FULL = 0, B_EMPTY = 8 * RING, B_X = 16 * RING, B_ADONE = B_X + 8, B_Q = B_X + 16, B_EP = B_X + 24, B_ATT = B_X + 32  , B_PF = B_ATT + 96;

__global__ void __cluster_dims__(2, 1, 1) __launch_bounds__(512, 1) conformer_kernel(const __grid_constant__ Maps tm, const __grid_constant__ Wptrs wp, const uint4* __restrict__ dw) {
  extern __shared__ uint8_t smem_raw[];
  const uint32_t base = (smem_u32(smem_raw) + 1023) & ~1023u, misc = base + OFF_MISC;
  const uint32_t dry = blockIdx.x >= 128;
  const int tile = dry ? 0 : blockIdx.x;
  const bool has_tile = dry ? blockIdx.x == 128 : tile < NTILE;
  const int wg = __shfl_sync(0xffffffff, (int)(threadIdx.x >> 7), 0);
  AttCtx a;
  a.sKV = base + OFF_W; a.full = misc + B_ATT; a.empty = a.full + 16 * NSTG; a.tm = &tm;
  a.h = (blockIdx.x >> 4) & 3; a.b = (blockIdx.x >> 6) & 1; a.wg = wg; a.dry = dry; a.wfull = has_tile ? misc + B_FULL : 0;
  const int qt = blockIdx.x & 15;

  if (threadIdx.x == 256) {
    mbar_init(misc + B_X, 1);
    for (int i = 0; i < RING; i++) { mbar_init(misc + B_FULL + 8 * i, 1); mbar_init(misc + B_EMPTY + 8 * i, 1); }
    asm volatile("fence.mbarrier_init.release.cluster;" ::: "memory");
    if (has_tile && !dry) {
      mbar_expect_tx(misc + B_X, 32768);
      tma_load_3d(base + OFF_X, &tm.X, misc + B_X, 0, tile * 64, 0);
    }
  } else if (threadIdx.x == 288) {
    mbar_init(misc + B_ADONE, 2);
    mbar_init(misc + B_Q, 1);
    mbar_init(misc + B_EP, 1);
    att_init_bars(a);
    for (int i = 0; i < RING; i++) mbar_init(misc + B_PF + 8 * i, 1);
    asm volatile("fence.mbarrier_init.release.cluster;" ::: "memory");
  } else if (threadIdx.x >= 320 && threadIdx.x < 333) {
    prefetch_tmap(&tm.X + (threadIdx.x - 320));
  }
  __syncthreads();
  asm volatile("barrier.cluster.arrive.release.aligned;" ::: "memory");
  const bool pair = (blockIdx.x | 1) < NTILE;
  if ((threadIdx.x & 31) == 0 && threadIdx.x >= 256 && threadIdx.x < 256 + 32 * RING && has_tile && !dry) {
    const int i = (threadIdx.x - 256) >> 5;
    load_stage(base + OFF_W + i * STAGE, misc + B_FULL + 8 * i, tm, i);
  }
  __syncwarp();
  auto get_epoch = [&]() {
    uint32_t e;
    mbar_wait(misc + B_EP, 0);
    asm volatile("ld.shared.u32 %0, [%1];" : "=r"(e) : "r"(misc + 248) : "memory");
    return e;
  };

  if (wg < 2) {
    asm volatile("setmaxnreg.inc.sync.aligned.u32 232;");
    if (has_tile) {
      const Ctx c = make_ctx(base, dry);
      if (c.wg == 1) turn_end(c);
      float own[64];
      float a0, b0, a1, b1;
      PROF_MARK(0, 0);
#pragma unroll 1
      for (int rep = 0; rep < 2; rep++) {
        if (rep) mbar_wait(misc + B_X, dry);
        PROF_MARK(0, 1);
        load_half(c, c.sX, own);
        ln_stats(c, own, 0.5f, a0, b0, a1, b1);
        store_half(c, c.sA, own, a0, b0, a1, b1);
        fence_async_smem();
        bar_sync(1, 256);
      }
      PROF_MARK(0, 2);
      ff_block(c, 0, own);
      PROF_MARK(0, 3);
      ln_stats(c, own, 1.f, a0, b0, a1, b1);
      store_half(c, c.sA, own, a0, b0, a1, b1);
      fence_async_smem();
      bar_sync(1, 256);
      PROF_MARK(0, 4);
#pragma unroll 1
      for (int cc = dry ? 2 : 0; cc < 3; cc++) {
        float acc[64];
        const int j = 2 * cc + c.wg;
        gemm256<1>(c, acc, 32 + 2 * j, [&]() {
          if (c.tid == 0 && !dry) {
            if (cc == 2) {
              bulk_wait_all();
              if (tile <= 62) cnt_signal(g_cnt1);
              if (tile >= 62) cnt_signal(g_cnt1 + 64);
            } else bulk_wait_read();
          }
          bar_sync(3 + c.wg, 128);
        });
        if (cc == 2 && !dry) { bar_arrive(9, 288); if (c.tid == 0) mbar_arrive(misc + B_ADONE); }
        if (cc == 0) {
#pragma unroll
          for (int i = 0; i < 64; i++) acc[i] *= 0.125f * 1.4426950408889634f;
        }
        store_half_raw(c, c.sX, acc);
        fence_async_smem();
        bar_sync(3 + c.wg, 128);
        if (c.tid == 0 && !dry) { tma_store_3d(&tm.QKVst, c.sX + c.wg * 16384, 0, tile * 64, 2 * j); bulk_commit(); }
      }
      PROF_MARK(0, 5);
      if (c.tid == 0) bulk_wait_read();
      bar_sync(3 + c.wg, 128);
      store_half_raw(c, c.sX, own);
    }
    else bar_sync(3 + wg, 128);
    asm volatile("setmaxnreg.dec.sync.aligned.u32 128;");
    bar_arrive(7, 384); bar_arrive(8, 384);
    asm volatile("barrier.cluster.wait.acquire.aligned;" ::: "memory");
    if (has_tile && !dry && (threadIdx.x & 127) == 0) {
      bulk_wait_all();
      if (tile <= 62) cnt_signal(g_cnt1 + 32);
      if (tile >= 62) cnt_signal(g_cnt1 + 96);
    }
    __syncwarp();
    PROF_MARK(0, 6);
  } else {
    asm volatile("setmaxnreg.dec.sync.aligned.u32 24;");
    asm volatile("barrier.cluster.wait.acquire.aligned;" ::: "memory");
    const uint32_t full = misc + B_FULL;
    if (threadIdx.x == 320) {
      const uint32_t e = atomicAdd(&g_start, 1) / NCTA;
      asm volatile("st.shared.u32 [%0], %1;" :: "r"(misc + 248), "r"(e + 1) : "memory");
      mbar_arrive(misc + B_EP);
    }
    if (dry) {
    } else if (threadIdx.x == 256) {
      if (has_tile) {
        produce(base + OFF_W, full, misc + B_PF, pair, tm, RING, NA);
        mbar_wait(full + 8 * RING + 8 * 4, 1);
        mbar_arrive(full + 8 * 4); mbar_arrive(full + 8 * RING + 8 * 4);
        mbar_wait(misc + B_ADONE, 0);
      }
      cnt_wait(g_cnt1 + a.b * 64, 126 * get_epoch());
      mbar_expect_tx(misc + B_Q, 32768);
      tma_load_3d(base, &tm.Q, misc + B_Q, a.h * 64, qt * 256, a.b);
      att_load(a, 0, 0);
      mbar_wait(misc + B_Q, 0);
#pragma unroll 1
      for (int i = 1; i < NSTG; i++) att_load(a, i, 0);
    } else if ((threadIdx.x >> 5) == 12) {
      if (has_tile) bar_sync(9, 288);
      if (threadIdx.x == 384) {
        cnt_wait(g_cnt1 + a.b * 64 + 32, 126 * get_epoch());
        att_load(a, 0, 1);
        mbar_wait(a.full + 8 * NSTG, 0);
#pragma unroll 1
        for (int i = 1; i < NSTG; i++) att_load(a, i, 1);
      }
    } else if (has_tile && threadIdx.x >= 288 && threadIdx.x < 296) {
      const int w = threadIdx.x - 288;
      mbar_wait(misc + B_X, 0);
      const uint32_t bytes = wp.bytes[w], per = ((bytes / NTILE) + 127) & ~127u, off = per * tile;
      if (off < bytes) l2_prefetch((const uint8_t*)wp.p[w] + off, min(per, bytes - off));
    } else if (has_tile && threadIdx.x >= 416) {
      mbar_wait(full, 0);
      const int t = threadIdx.x - 416;
#pragma unroll 2
      for (int i = t; i < 2048; i += 96) g_att[tile * 2048 + i] = make_uint4(~0u, ~0u, ~0u, ~0u);
      g_halo[tile * 128 + t] = make_uint4(~0u, ~0u, ~0u, ~0u);
      if (t < 32) g_halo[tile * 128 + 96 + t] = make_uint4(~0u, ~0u, ~0u, ~0u);
    }
    __syncwarp();
    bar_sync(5 + wg, 384);
    asm volatile("setmaxnreg.inc.sync.aligned.u32 128;");
  }

  if (blockIdx.x == 128 || blockIdx.x == 131) return;
  if (blockIdx.x != 130) {
    const int lane = threadIdx.x & 31, wq = (threadIdx.x >> 5) & 3;
    const uint32_t dQ = dlo(base + wg * 8192, 16);
    float O[32], l0, l1;
    PROF_MARK(1, 1);
    mbar_wait(misc + B_Q, dry);
    PROF_MARK(1, 2);
    att_pass<false>(a, dQ, O, l0, l1);
    PROF_MARK(1, 3);
    float z = 0.f;
#pragma unroll
    for (int i = 0; i < 32; i++) z = fmaf(O[i], 0.f, z);
    const bool ok = (l0 >= 0x1p-80f) && (l0 <= 0x1p100f) && (l1 >= 0x1p-80f) && (l1 <= 0x1p100f) && (z == 0.f);
    const bool warp_bad = !__all_sync(0xffffffff, ok) && !dry;
    auto store_out = [&]() {
      const float i0 = 1.f / l0, i1 = 1.f / l1;
      const int row = qt * 256 + wg * 64 + wq * 16;
      if (row < T_ && !dry) {
        const int slab = (a.b * T_ + row) / 16;
        uint4* op = g_att + (slab * 16 + a.h * 4) * 32 + lane;
#pragma unroll
        for (int j = 0; j < 4; j++)
          asm volatile("st.relaxed.gpu.global.v4.u32 [%0], {%1,%2,%3,%4};" :: "l"(op + j * 32),
                       "r"(pack_bf16(O[8 * j] * i0, O[8 * j + 1] * i0)), "r"(pack_bf16(O[8 * j + 2] * i1, O[8 * j + 3] * i1)),
                       "r"(pack_bf16(O[8 * j + 4] * i0, O[8 * j + 5] * i0)), "r"(pack_bf16(O[8 * j + 6] * i1, O[8 * j + 7] * i1)) : "memory");
      }
      PROF_MARK(1, 4);
    };
    if (!warp_bad) store_out();
    if (__syncthreads_or(warp_bad)) {
      if (threadIdx.x == 0) {
        if (has_tile) { mbar_wait(misc + B_FULL, 1); mbar_wait(misc + B_FULL + 8, 1); }
        for (int i = 0; i < 3 * NSTG; i++) mbar_inval(a.full + 8 * i);
        att_init_bars(a);
        asm volatile("fence.mbarrier_init.release.cluster;" ::: "memory");
        fence_async_smem();
#pragma unroll 1
        for (int i = 0; i < NSTG; i++) att_load_stage(a, i);
      }
      __syncthreads();
      att_pass<true>(a, dQ, O, l0, l1);
      if (warp_bad) store_out();
      __syncthreads();
      if (has_tile) {
        if (threadIdx.x == 32) {
          load_stage(base + OFF_W, misc + B_X, tm, NC);
          load_stage(base + OFF_W + STAGE, misc + B_Q, tm, NC + 1);
        }
        mbar_wait(misc + B_X, 1); mbar_wait(misc + B_Q, 1);
      }
    }
    PROF_MARK(1, 5);
  } else {
    __syncthreads();
  }
  if (dry ? blockIdx.x != 130 : !has_tile) return;

  if (wg < 2) {
    asm volatile("setmaxnreg.inc.sync.aligned.u32 232;");
    const Ctx c = make_ctx(base, dry);
    if (dry && c.wg == 1) turn_end(c);
    float own[64];
    float a0, b0, a1, b1;
    PROF_MARK(2, 0);
    {
      uint4 af[16];
      const int slab = tile * 4 + (c.tid >> 5);
      const uint4* ap = g_att + slab * 512 + c.lane;
#pragma unroll
      for (int i = 0; i < 16; i++)
        asm volatile("ld.global.ca.v4.u32 {%0,%1,%2,%3}, [%4];" : "=r"(af[i].x), "=r"(af[i].y), "=r"(af[i].z), "=r"(af[i].w) : "l"(ap + i * 32) : "memory");
      load_half(c, c.sX, own);
      uint32_t miss = dry ? 0 : 15;
      for (uint32_t n = 0; n < (1u << 18); n++) {
#pragma unroll
        for (int hh = 0; hh < 4; hh++)
          if ((miss >> hh) & 1) {
            uint32_t mx = 0;
#pragma unroll
            for (int i = 4 * hh; i < 4 * hh + 4; i++) mx = max(mx, max(max(af[i].x, af[i].y), max(af[i].z, af[i].w)));
            if (__any_sync(0xffffffff, mx == ~0u)) {
#pragma unroll
              for (int i = 4 * hh; i < 4 * hh + 4; i++)
                asm volatile("ld.relaxed.gpu.global.v4.u32 {%0,%1,%2,%3}, [%4];" : "=r"(af[i].x), "=r"(af[i].y), "=r"(af[i].z), "=r"(af[i].w) : "l"(ap + i * 32) : "memory");
            } else miss &= ~(1u << hh);
          }
        if (!miss) break;
      }
      PROF_MARK(2, 2);
      const int n = NC + 2 * c.wg;
      uint32_t b = stage_wait(c, n) + ((16384 >> 4) << 16);
      turn_begin(c);
      wg_fence();
#pragma unroll
      for (int kk = 0; kk < 8; kk++) wg_rs_n128_tb1<1>(own, af[kk].x, af[kk].y, af[kk].z, af[kk].w, b + kk * 128);
      wg_commit();
      b = stage_wait(c, n + 1) + ((16384 >> 4) << 16);
      wg_fence();
#pragma unroll
      for (int kk = 0; kk < 8; kk++) wg_rs_n128_tb1<1>(own, af[8 + kk].x, af[8 + kk].y, af[8 + kk].z, af[8 + kk].w, b + kk * 128);
      wg_commit();
      turn_end(c);
      wg_wait<1>(); stage_release(c, n);
      wg_wait<0>(); stage_release(c, n + 1);
    }
    PROF_MARK(2, 3);
    ln_stats(c, own, 0.5f, a0, b0, a1, b1);
    store_half(c, c.sA, own, a0, b0, a1, b1);
    fence_async_smem();
    bar_sync(1, 256);
    PROF_MARK(2, 4);
    uint4 dwr[5];
#pragma unroll
    for (int i = 0; i < 5; i++) dwr[i] = __ldg(dw + i * 32 + c.wg * 16 + (c.lane & 15));
    const bool top = c.tid < 8, pub = (top || c.tid >= 120) && !dry;
    uint32_t* halo_out = (uint32_t*)g_halo + (tile * 4 + (top ? (c.tid >> 2) : ((c.tid >> 2) - 28))) * 128 + c.wg * 64 + (c.lane & 3);
#pragma unroll 1
    for (int q = dry; q < 2; q++) {
      float ab[64];
      gemm256<1>(c, ab, NC + 4 + 4 * q + 2 * c.wg);
#pragma unroll
      for (int j = 0; j < 4; j++) {
        float g[8];
#pragma unroll
        for (int i = 0; i < 8; i++) g[i] = fmaf(ab[8 * j + i], tanh_fast(ab[32 + 8 * j + i]), ab[8 * j + i]);
        const uint32_t p0 = pack_bf16(g[0], g[1]), p1 = pack_bf16(g[2], g[3]), p2 = pack_bf16(g[4], g[5]), p3 = pack_bf16(g[6], g[7]);
        if (pub) {
          uint32_t* hp = halo_out + q * 32 + j * 8;
          asm volatile("st.relaxed.gpu.global.u32 [%0], %1;" :: "l"(hp), "r"(top ? p0 : p1) : "memory");
          asm volatile("st.relaxed.gpu.global.u32 [%0], %1;" :: "l"(hp + 4), "r"(top ? p2 : p3) : "memory");
        }
        stsm_x4(c.sX + (2 * c.wg + q) * 8192 + c.frag + (((j * 2 + c.hi) ^ c.rsw) << 4), p0, p1, p2, p3);
      }
    }
    bar_sync(3 + c.wg, 128);
    PROF_MARK(2, 5);
    {
      const int wi = c.tid >> 4;
      const uint32_t col = (2 * c.wg + ((c.lane >> 3) & 1)) * 8192, ch = c.lane & 7;
      uint4 r[12];
      const int R0 = tile * 64 + wi * 8;
      const bool first = (R0 % T_) == 0, last = ((R0 + 8) % T_) == 0;
      const bool far = ((wi == 0 && !first) || (wi == 7 && !last)) && !dry;
      const uint4* sp = g_halo + (wi == 0 ? (tile - 1) * 4 + 2 : (tile + 1) * 4) * 32 + c.wg * 16 + (c.lane & 15);
      uint4 h0 = make_uint4(0, 0, 0, 0), h1 = h0;
      auto ld_halo = [&]() {
        asm volatile("ld.relaxed.gpu.global.v4.u32 {%0,%1,%2,%3}, [%4];" : "=r"(h0.x), "=r"(h0.y), "=r"(h0.z), "=r"(h0.w) : "l"(sp) : "memory");
        asm volatile("ld.relaxed.gpu.global.v4.u32 {%0,%1,%2,%3}, [%4];" : "=r"(h1.x), "=r"(h1.y), "=r"(h1.z), "=r"(h1.w) : "l"(sp + 32) : "memory");
      };
      if (far) ld_halo();
#pragma unroll
      for (int i = 0; i < 12; i++) {
        const int row = (wi * 8 - 2 + i) & 63;
        r[i] = lds128(c.sX + col + row * 128 + ((ch ^ (row & 7)) << 4));
      }
      uint32_t w[5][4];
#pragma unroll
      for (int k = 0; k < 5; k++) {
        w[k][0] = bmul2(dwr[k].x, 0x3F003F00u); w[k][1] = bmul2(dwr[k].y, 0x3F003F00u);
        w[k][2] = bmul2(dwr[k].z, 0x3F003F00u); w[k][3] = bmul2(dwr[k].w, 0x3F003F00u);
      }
      auto conv4 = [&](int i0, int i1, int i2, int i3, bool sync) {
        const int rows[4] = {i0, i1, i2, i3};
        uint32_t acc[4][4];
#pragma unroll
        for (int k = 0; k < 5; k++)
#pragma unroll
          for (int j = 0; j < 4; j++) {
            const uint4 x = r[rows[j] + k];
            acc[j][0] = k ? bfma2(x.x, w[k][0], acc[j][0]) : bmul2(x.x, w[0][0]);
            acc[j][1] = k ? bfma2(x.y, w[k][1], acc[j][1]) : bmul2(x.y, w[0][1]);
            acc[j][2] = k ? bfma2(x.z, w[k][2], acc[j][2]) : bmul2(x.z, w[0][2]);
            acc[j][3] = k ? bfma2(x.w, w[k][3], acc[j][3]) : bmul2(x.w, w[0][3]);
          }
#pragma unroll
        for (int j = 0; j < 4; j++)
#pragma unroll
          for (int q = 0; q < 4; q++) acc[j][q] = pack_bf16(silu_half(bf_lo(acc[j][q])), silu_half(bf_hi(acc[j][q])));
        if (sync) bar_sync(3 + c.wg, 128);
#pragma unroll
        for (int j = 0; j < 4; j++)
          sts128(c.sX + col + (wi * 8 + rows[j]) * 128 + ((ch ^ rows[j]) << 4), make_uint4(acc[j][0], acc[j][1], acc[j][2], acc[j][3]));
      };
      conv4(2, 3, 4, 5, true);
      if (far) {
        for (uint32_t n = 0; n < (1u << 18); n++) {
          const uint32_t mx = max(max(max(h0.x, h0.y), max(h0.z, h0.w)), max(max(h1.x, h1.y), max(h1.z, h1.w)));
          if (mx != ~0u) break;
          ld_halo();
        }
      }
      __syncwarp();
      if (first || (far && wi == 0)) { r[0] = h0; r[1] = h1; }
      if (last || (far && wi == 7)) { r[10] = h0; r[11] = h1; }
      conv4(0, 1, 6, 7, false);
    }
    fence_async_smem();
    bar_sync(c.wg == 0 ? 3 : 1, c.wg == 0 ? 128 : 256);
    PROF_MARK(2, 6);
    {
      uint32_t b = stage_wait(c, NC + 12 + c.wg);
      turn_begin(c);
      wg_fence(); piece_ss<0, 0>(c, own, dlo(c.sX, 16), b); wg_commit();
      if (c.wg == 0) { turn_end(c); bar_sync(1, 256); turn_begin(c); }
      b = stage_wait(c, NC + 14 + c.wg);
      wg_fence(); piece_ss<0, 1>(c, own, dlo(c.sX, 16) + 1024, b); wg_commit();
    }
    wg_wait<1>(); stage_release(c, NC + 12 + c.wg);
    wg_wait<0>(); stage_release(c, NC + 14 + c.wg);
    PROF_MARK(2, 7);
    ln_stats(c, own, 0.5f, a0, b0, a1, b1);
    if (c.wg == 1) { turn_begin(c); turn_end(c); }
    store_half(c, c.sA, own, a0, b0, a1, b1);
    fence_async_smem();
    bar_sync(1, 256);
    PROF_MARK(2, 8);
    ff_block(c, NC + 16, own);
    PROF_MARK(2, 9);
    ln_stats(c, own, 1.f, a0, b0, a1, b1);
    store_half(c, c.sX, own, a0, b0, a1, b1);
    fence_async_smem();
    bar_sync(3 + c.wg, 128);
    if (c.tid == 0 && !dry) { tma_store_3d(&tm.Out, c.sX + c.wg * 16384, 0, tile * 64, 2 * c.wg); bulk_commit(); PROF_MARK(2, 10); bulk_wait_read(); }
    PROF_MARK(2, 11);
  } else {
    asm volatile("setmaxnreg.dec.sync.aligned.u32 24;");
    if (threadIdx.x == 256 && !dry) {
      __nanosleep(PROD_NS);
      produce(base + OFF_W, misc + B_FULL, misc + B_PF, pair, tm, NC + 2, NC + 48);
    }
  }
}

typedef CUresult (*EncodeFn)(CUtensorMap*, CUtensorMapDataType, cuuint32_t, void*, const cuuint64_t*, const cuuint64_t*, const cuuint32_t*,
                             const cuuint32_t*, CUtensorMapInterleave, CUtensorMapSwizzle, CUtensorMapL2promotion, CUtensorMapFloatOOBfill);

CUtensorMap make_map(EncodeFn enc, const void* p, uint64_t d0, uint64_t d1, uint64_t d2, uint64_t s1, uint64_t s2, uint32_t b1, uint32_t b2) {
  CUtensorMap tm;
  cuuint64_t dims[3] = {d0, d1, d2};
  cuuint64_t strides[2] = {s1, s2};
  cuuint32_t box[3] = {64, b1, b2};
  cuuint32_t es[3] = {1, 1, 1};
  enc(&tm, CU_TENSOR_MAP_DATA_TYPE_BFLOAT16, 3, const_cast<void*>(p), dims, strides, box, es, CU_TENSOR_MAP_INTERLEAVE_NONE,
      CU_TENSOR_MAP_SWIZZLE_128B, CU_TENSOR_MAP_L2_PROMOTION_L2_256B, CU_TENSOR_MAP_FLOAT_OOB_FILL_NONE);
  return tm;
}
CUtensorMap blk_map(EncodeFn enc, const void* p, uint64_t rows, uint64_t cols, uint32_t boxrows, uint32_t boxblks) {
  return make_map(enc, p, 64, rows, cols / 64, cols * 2, 128, boxrows, boxblks);
}
CUtensorMap seq_map(EncodeFn enc, const void* p, uint64_t cols, uint32_t boxrows) {
  return make_map(enc, p, cols, T_, 2, cols * 2, cols * 2 * T_, boxrows, 1);
}

}

extern "C" void kernel_launch(void* const* d_in, const int* in_sizes, int n_in, void* d_out, int out_size) {
  (void)in_sizes; (void)n_in; (void)out_size;
  const void *x = d_in[0], *w1a = d_in[1], *w1b = d_in[2], *wqkv = d_in[3], *wo = d_in[4], *pw1 = d_in[5], *dw = d_in[6], *pw2 = d_in[7],
             *w2a = d_in[8], *w2b = d_in[9];
  void* fn = nullptr;
  cudaDriverEntryPointQueryResult qr;
  cudaGetDriverEntryPoint("cuTensorMapEncodeTiled", &fn, cudaEnableDefault, &qr);
  EncodeFn enc = (EncodeFn)fn;
  void* qkv;
  cudaGetSymbolAddress(&qkv, g_qkv);
  cudaFuncSetAttribute(conformer_kernel, cudaFuncAttributeMaxDynamicSharedMemorySize, SMEM_BYTES);

  Wptrs wp;
  const void* ws[8] = {w1a, w1b, wqkv, wo, pw1, pw2, w2a, w2b};
  const uint32_t wb[8] = {524288, 524288, 393216, 131072, 262144, 131072, 524288, 524288};
  for (int i = 0; i < 8; i++) { wp.p[i] = ws[i]; wp.bytes[i] = wb[i]; }
  Maps tm;
  const uint16_t tab[92] = STAGE_TABLE;
  for (int i = 0; i < 92; i++) tm.stage[i] = tab[i];
  tm.X = blk_map(enc, x, ROWS, 256, 64, 4);
  tm.W1a = blk_map(enc, w1a, 256, 1024, 256 / WDIV, 1);
  tm.W1b = blk_map(enc, w1b, 1024, 256, 64 / WDIV, 4);
  tm.Wqkv = blk_map(enc, wqkv, 256, 768, 128 / WDIV, 2);
  tm.QKVst = blk_map(enc, qkv, ROWS, 768, 64, 2);
  tm.Q = seq_map(enc, qkv, 768, 256);
  tm.KV = seq_map(enc, qkv, 768, 160);
  tm.Wo = blk_map(enc, wo, 256, 256, 128 / WDIV, 2);
  tm.Pw1 = make_map(enc, pw1, 256, 256, 2, 1024, 512, 128 / WDIV, 2);
  tm.Pw2 = blk_map(enc, pw2, 256, 256, 128 / WDIV, 2);
  tm.W2a = blk_map(enc, w2a, 256, 1024, 256 / WDIV, 1);
  tm.W2b = blk_map(enc, w2b, 1024, 256, 64 / WDIV, 4);
  tm.Out = blk_map(enc, d_out, ROWS, 256, 64, 2);
  conformer_kernel<<<NCTA, 512, SMEM_BYTES, cudaStreamPerThread>>>(tm, wp, (const uint4*)dw);
}
```

```cpp
#include <cuda_runtime.h>
#include <cuda_bf16.h>
#include <cuda.h>
#include <stdint.h>

namespace {

constexpr int T_ = 4000;
constexpr int ROWS = 8000;
constexpr int NTILE = 125;
constexpr int NCTA = 131;

__device__ __nv_bfloat16 g_qkv[ROWS * 768];
__device__ uint4 g_att[(ROWS / 16) * 16 * 32];
__device__ uint4 g_halo[NTILE * 4 * 32];
__device__ uint32_t g_start;
__device__ uint32_t g_cnt1[4 * 32];


__device__ __forceinline__ uint32_t smem_u32(const void* p) { return (uint32_t)__cvta_generic_to_shared(p); }
__device__ __forceinline__ void mbar_init(uint32_t bar, uint32_t cnt) { asm volatile("mbarrier.init.shared::cta.b64 [%0], %1;" :: "r"(bar), "r"(cnt) : "memory"); }
__device__ __forceinline__ void mbar_inval(uint32_t bar) { asm volatile("mbarrier.inval.shared::cta.b64 [%0];" :: "r"(bar) : "memory"); }
__device__ __forceinline__ void mbar_expect_tx(uint32_t bar, uint32_t bytes) { asm volatile("mbarrier.arrive.expect_tx.shared::cta.b64 _, [%0], %1;" :: "r"(bar), "r"(bytes) : "memory"); }
__device__ __forceinline__ void mbar_arrive(uint32_t bar) { asm volatile("mbarrier.arrive.shared::cta.b64 _, [%0];" :: "r"(bar) : "memory"); }
__device__ __forceinline__ void mbar_wait(uint32_t bar, uint32_t parity) {
  asm volatile("{\n.reg .pred p;\n.reg .u32 n;\n"
               "mbarrier.try_wait.parity.shared::cta.b64 p, [%0], %1;\n@p bra DONE_%=;\nmov.u32 n, 0;\n"
               "LOOP_%=:\nmbarrier.try_wait.parity.shared::cta.b64 p, [%0], %1;\n@p bra DONE_%=;\n"
               "add.u32 n, n, 1;\nsetp.lt.u32 p, n, 262144;\n@p bra LOOP_%=;\ntrap;\nDONE_%=:\n}\n" :: "r"(bar), "r"(parity) : "memory");
}
__device__ __forceinline__ void cnt_wait(const uint32_t* p, uint32_t target) {
  asm volatile("{\n.reg .pred p;\n.reg .u32 n, v;\nmov.u32 n, 0;\n"
               "LOOP_%=:\nld.relaxed.gpu.global.u32 v, [%0];\nsub.u32 v, v, %1;\nsetp.ge.s32 p, v, 0;\n@p bra DONE_%=;\n"
               "nanosleep.u32 40;\nadd.u32 n, n, 1;\nsetp.lt.u32 p, n, 262144;\n@p bra LOOP_%=;\ntrap;\nDONE_%=:\n}\n" :: "l"(p), "r"(target) : "memory");
}
__device__ __forceinline__ void cnt_signal(uint32_t* p) {
  asm volatile("red.relaxed.gpu.global.add.u32 [%0], 1;" :: "l"(p) : "memory");
}
__device__ __forceinline__ void tma_load_3d(uint32_t dst, const CUtensorMap* tm, uint32_t bar, int c0, int c1, int c2) {
  asm volatile("cp.async.bulk.tensor.3d.shared::cluster.global.mbarrier::complete_tx::bytes [%0], [%1, {%3, %4, %5}], [%2];"
    :: "r"(dst), "l"(tm), "r"(bar), "r"(c0), "r"(c1), "r"(c2) : "memory");
}
__device__ __forceinline__ void tma_store_3d(const CUtensorMap* tm, uint32_t src, int c0, int c1, int c2) {
  asm volatile("cp.async.bulk.tensor.3d.global.shared::cta.bulk_group [%0, {%2, %3, %4}], [%1];" :: "l"(tm), "r"(src), "r"(c0), "r"(c1), "r"(c2) : "memory");
}
__device__ __forceinline__ void bulk_commit() { asm volatile("cp.async.bulk.commit_group;" ::: "memory"); }
__device__ __forceinline__ void bulk_wait_read() { asm volatile("cp.async.bulk.wait_group.read 0;" ::: "memory"); }
__device__ __forceinline__ void bulk_wait_all() { asm volatile("cp.async.bulk.wait_group 0;" ::: "memory"); }
__device__ __forceinline__ void l2_prefetch(const void* p, uint32_t bytes) { asm volatile("cp.async.bulk.prefetch.L2.global [%0], %1;" :: "l"(p), "r"(bytes) : "memory"); }
__device__ __forceinline__ void prefetch_tmap(const CUtensorMap* tm) { asm volatile("prefetch.tensormap [%0];" :: "l"(tm) : "memory"); }
__device__ __forceinline__ void fence_async_smem() { asm volatile("fence.proxy.async.shared::cta;" ::: "memory"); }
__device__ __forceinline__ void wg_fence() { asm volatile("wgmma.fence.sync.aligned;" ::: "memory"); }
__device__ __forceinline__ void wg_commit() { asm volatile("wgmma.commit_group.sync.aligned;" ::: "memory"); }
template<int N> __device__ __forceinline__ void wg_wait() { asm volatile("wgmma.wait_group.sync.aligned %0;" :: "n"(N) : "memory"); }
__device__ __forceinline__ void bar_sync(int id, int n) { asm volatile("bar.sync %0, %1;" :: "r"(id), "r"(n) : "memory"); }
__device__ __forceinline__ void bar_arrive(int id, int n) { asm volatile("bar.arrive %0, %1;" :: "r"(id), "r"(n) : "memory"); }
__device__ __forceinline__ float ex2(float x) { float y; asm("ex2.approx.ftz.f32 %0, %1;" : "=f"(y) : "f"(x)); return y; }
__device__ __forceinline__ float tanh_fast(float x) { float y; asm("tanh.approx.f32 %0, %1;" : "=f"(y) : "f"(x)); return y; }
__device__ __forceinline__ uint32_t pack_bf16(float lo, float hi) { uint32_t r; asm("cvt.rn.bf16x2.f32 %0, %1, %2;" : "=r"(r) : "f"(hi), "f"(lo)); return r; }
__device__ __forceinline__ uint32_t bmul2(uint32_t a, uint32_t b) { uint32_t d; asm("mul.rn.bf16x2 %0, %1, %2;" : "=r"(d) : "r"(a), "r"(b)); return d; }
__device__ __forceinline__ uint32_t bfma2(uint32_t a, uint32_t b, uint32_t c) { uint32_t d; asm("fma.rn.bf16x2 %0, %1, %2, %3;" : "=r"(d) : "r"(a), "r"(b), "r"(c)); return d; }
__device__ __forceinline__ float bf_lo(uint32_t u) { return __uint_as_float(u << 16); }
__device__ __forceinline__ float bf_hi(uint32_t u) { return __uint_as_float(u & 0xffff0000u); }
__device__ __forceinline__ void ldsm_x4(uint32_t addr, uint32_t& r0, uint32_t& r1, uint32_t& r2, uint32_t& r3) {
  asm volatile("ldmatrix.sync.aligned.m8n8.x4.shared.b16 {%0,%1,%2,%3}, [%4];" : "=r"(r0), "=r"(r1), "=r"(r2), "=r"(r3) : "r"(addr) : "memory");
}
__device__ __forceinline__ void stsm_x4(uint32_t addr, uint32_t r0, uint32_t r1, uint32_t r2, uint32_t r3) {
  asm volatile("stmatrix.sync.aligned.m8n8.x4.shared.b16 [%0], {%1,%2,%3,%4};" :: "r"(addr), "r"(r0), "r"(r1), "r"(r2), "r"(r3) : "memory");
}
__device__ __forceinline__ void sts128(uint32_t addr, uint4 v) { asm volatile("st.shared.v4.b32 [%0], {%1,%2,%3,%4};" :: "r"(addr), "r"(v.x), "r"(v.y), "r"(v.z), "r"(v.w) : "memory"); }
__device__ __forceinline__ uint4 lds128(uint32_t addr) { uint4 v; asm volatile("ld.shared.v4.b32 {%0,%1,%2,%3}, [%4];" : "=r"(v.x), "=r"(v.y), "=r"(v.z), "=r"(v.w) : "r"(addr) : "memory"); return v; }
__device__ __forceinline__ void sts64f(uint32_t addr, float a, float b) { asm volatile("st.shared.v2.f32 [%0], {%1,%2};" :: "r"(addr), "f"(a), "f"(b) : "memory"); }
__device__ __forceinline__ float2 lds64f(uint32_t addr) { float2 v; asm volatile("ld.shared.v2.f32 {%0,%1}, [%2];" : "=f"(v.x), "=f"(v.y) : "r"(addr) : "memory"); return v; }
__device__ __forceinline__ uint32_t dlo(uint32_t addr, uint32_t lbo) { return ((addr & 0x3FFFF) >> 4) | ((lbo >> 4) << 16); }

template<int SD> __device__ __forceinline__ void wg_ss_n128_tb1(float (&d)[64], uint32_t da, uint32_t db) {
  asm volatile("{\n.reg .b64 da, db;\nmov.b64 da, {%64, 0x40000040};\nmov.b64 db, {%65, 0x40000040};\n"
    "wgmma.mma_async.sync.aligned.m64n128k16.f32.bf16.bf16 {%0, %1, %2, %3, %4, %5, %6, %7, %8, %9, %10, %11, %12, %13, %14, %15, %16, %17, %18, %19, %20, %21, %22, %23, %24, %25, %26, %27, %28, %29, %30, %31, %32, %33, %34, %35, %36, %37, %38, %39, %40, %41, %42, %43, %44, %45, %46, %47, %48, %49, %50, %51, %52, %53, %54, %55, %56, %57, %58, %59, %60, %61, %62, %63}, da, db, %66, 1, 1, 0, 1;\n}\n"
    : "+f"(d[0]), "+f"(d[1]), "+f"(d[2]), "+f"(d[3]), "+f"(d[4]), "+f"(d[5]), "+f"(d[6]), "+f"(d[7]), "+f"(d[8]), "+f"(d[9]), "+f"(d[10]), "+f"(d[11]), "+f"(d[12]), "+f"(d[13]), "+f"(d[14]), "+f"(d[15]), "+f"(d[16]), "+f"(d[17]), "+f"(d[18]), "+f"(d[19]), "+f"(d[20]), "+f"(d[21]), "+f"(d[22]), "+f"(d[23]), "+f"(d[24]), "+f"(d[25]), "+f"(d[26]), "+f"(d[27]), "+f"(d[28]), "+f"(d[29]), "+f"(d[30]), "+f"(d[31]), "+f"(d[32]), "+f"(d[33]), "+f"(d[34]), "+f"(d[35]), "+f"(d[36]), "+f"(d[37]), "+f"(d[38]), "+f"(d[39]), "+f"(d[40]), "+f"(d[41]), "+f"(d[42]), "+f"(d[43]), "+f"(d[44]), "+f"(d[45]), "+f"(d[46]), "+f"(d[47]), "+f"(d[48]), "+f"(d[49]), "+f"(d[50]), "+f"(d[51]), "+f"(d[52]), "+f"(d[53]), "+f"(d[54]), "+f"(d[55]), "+f"(d[56]), "+f"(d[57]), "+f"(d[58]), "+f"(d[59]), "+f"(d[60]), "+f"(d[61]), "+f"(d[62]), "+f"(d[63])
    : "r"(da), "r"(db), "n"(SD));
}
template<int SD> __device__ __forceinline__ void wg_rs_n128_tb1(float (&d)[64], uint32_t a0, uint32_t a1, uint32_t a2, uint32_t a3, uint32_t db) {
  asm volatile("{\n.reg .b64 db;\nmov.b64 db, {%68, 0x40000040};\n"
    "wgmma.mma_async.sync.aligned.m64n128k16.f32.bf16.bf16 {%0, %1, %2, %3, %4, %5, %6, %7, %8, %9, %10, %11, %12, %13, %14, %15, %16, %17, %18, %19, %20, %21, %22, %23, %24, %25, %26, %27, %28, %29, %30, %31, %32, %33, %34, %35, %36, %37, %38, %39, %40, %41, %42, %43, %44, %45, %46, %47, %48, %49, %50, %51, %52, %53, %54, %55, %56, %57, %58, %59, %60, %61, %62, %63}, {%64, %65, %66, %67}, db, %69, 1, 1, 1;\n}\n"
    : "+f"(d[0]), "+f"(d[1]), "+f"(d[2]), "+f"(d[3]), "+f"(d[4]), "+f"(d[5]), "+f"(d[6]), "+f"(d[7]), "+f"(d[8]), "+f"(d[9]), "+f"(d[10]), "+f"(d[11]), "+f"(d[12]), "+f"(d[13]), "+f"(d[14]), "+f"(d[15]), "+f"(d[16]), "+f"(d[17]), "+f"(d[18]), "+f"(d[19]), "+f"(d[20]), "+f"(d[21]), "+f"(d[22]), "+f"(d[23]), "+f"(d[24]), "+f"(d[25]), "+f"(d[26]), "+f"(d[27]), "+f"(d[28]), "+f"(d[29]), "+f"(d[30]), "+f"(d[31]), "+f"(d[32]), "+f"(d[33]), "+f"(d[34]), "+f"(d[35]), "+f"(d[36]), "+f"(d[37]), "+f"(d[38]), "+f"(d[39]), "+f"(d[40]), "+f"(d[41]), "+f"(d[42]), "+f"(d[43]), "+f"(d[44]), "+f"(d[45]), "+f"(d[46]), "+f"(d[47]), "+f"(d[48]), "+f"(d[49]), "+f"(d[50]), "+f"(d[51]), "+f"(d[52]), "+f"(d[53]), "+f"(d[54]), "+f"(d[55]), "+f"(d[56]), "+f"(d[57]), "+f"(d[58]), "+f"(d[59]), "+f"(d[60]), "+f"(d[61]), "+f"(d[62]), "+f"(d[63])
    : "r"(a0), "r"(a1), "r"(a2), "r"(a3), "r"(db), "n"(SD));
}
template<int SD> __device__ __forceinline__ void wg_ss_n64_tb1(float (&d)[32], uint32_t da, uint32_t db) {
  asm volatile("{\n.reg .b64 da, db;\nmov.b64 da, {%32, 0x40000040};\nmov.b64 db, {%33, 0x40000040};\n"
    "wgmma.mma_async.sync.aligned.m64n64k16.f32.bf16.bf16 {%0, %1, %2, %3, %4, %5, %6, %7, %8, %9, %10, %11, %12, %13, %14, %15, %16, %17, %18, %19, %20, %21, %22, %23, %24, %25, %26, %27, %28, %29, %30, %31}, da, db, %34, 1, 1, 0, 1;\n}\n"
    : "+f"(d[0]), "+f"(d[1]), "+f"(d[2]), "+f"(d[3]), "+f"(d[4]), "+f"(d[5]), "+f"(d[6]), "+f"(d[7]), "+f"(d[8]), "+f"(d[9]), "+f"(d[10]), "+f"(d[11]), "+f"(d[12]), "+f"(d[13]), "+f"(d[14]), "+f"(d[15]), "+f"(d[16]), "+f"(d[17]), "+f"(d[18]), "+f"(d[19]), "+f"(d[20]), "+f"(d[21]), "+f"(d[22]), "+f"(d[23]), "+f"(d[24]), "+f"(d[25]), "+f"(d[26]), "+f"(d[27]), "+f"(d[28]), "+f"(d[29]), "+f"(d[30]), "+f"(d[31])
    : "r"(da), "r"(db), "n"(SD));
}
template<int SD> __device__ __forceinline__ void wg_ss_n80_tb0(float (&d)[40], uint32_t da, uint32_t db) {
  asm volatile("{\n.reg .b64 da, db;\nmov.b64 da, {%40, 0x40000040};\nmov.b64 db, {%41, 0x40000040};\n"
    "wgmma.mma_async.sync.aligned.m64n80k16.f32.bf16.bf16 {%0, %1, %2, %3, %4, %5, %6, %7, %8, %9, %10, %11, %12, %13, %14, %15, %16, %17, %18, %19, %20, %21, %22, %23, %24, %25, %26, %27, %28, %29, %30, %31, %32, %33, %34, %35, %36, %37, %38, %39}, da, db, %42, 1, 1, 0, 0;\n}\n"
    : "+f"(d[0]), "+f"(d[1]), "+f"(d[2]), "+f"(d[3]), "+f"(d[4]), "+f"(d[5]), "+f"(d[6]), "+f"(d[7]), "+f"(d[8]), "+f"(d[9]), "+f"(d[10]), "+f"(d[11]), "+f"(d[12]), "+f"(d[13]), "+f"(d[14]), "+f"(d[15]), "+f"(d[16]), "+f"(d[17]), "+f"(d[18]), "+f"(d[19]), "+f"(d[20]), "+f"(d[21]), "+f"(d[22]), "+f"(d[23]), "+f"(d[24]), "+f"(d[25]), "+f"(d[26]), "+f"(d[27]), "+f"(d[28]), "+f"(d[29]), "+f"(d[30]), "+f"(d[31]), "+f"(d[32]), "+f"(d[33]), "+f"(d[34]), "+f"(d[35]), "+f"(d[36]), "+f"(d[37]), "+f"(d[38]), "+f"(d[39])
    : "r"(da), "r"(db), "n"(SD));
}
template<int SD> __device__ __forceinline__ void wg_rs_n64_tb1(float (&d)[32], uint32_t a0, uint32_t a1, uint32_t a2, uint32_t a3, uint32_t db) {
  asm volatile("{\n.reg .b64 db;\nmov.b64 db, {%36, 0x40000040};\n"
    "wgmma.mma_async.sync.aligned.m64n64k16.f32.bf16.bf16 {%0, %1, %2, %3, %4, %5, %6, %7, %8, %9, %10, %11, %12, %13, %14, %15, %16, %17, %18, %19, %20, %21, %22, %23, %24, %25, %26, %27, %28, %29, %30, %31}, {%32, %33, %34, %35}, db, %37, 1, 1, 1;\n}\n"
    : "+f"(d[0]), "+f"(d[1]), "+f"(d[2]), "+f"(d[3]), "+f"(d[4]), "+f"(d[5]), "+f"(d[6]), "+f"(d[7]), "+f"(d[8]), "+f"(d[9]), "+f"(d[10]), "+f"(d[11]), "+f"(d[12]), "+f"(d[13]), "+f"(d[14]), "+f"(d[15]), "+f"(d[16]), "+f"(d[17]), "+f"(d[18]), "+f"(d[19]), "+f"(d[20]), "+f"(d[21]), "+f"(d[22]), "+f"(d[23]), "+f"(d[24]), "+f"(d[25]), "+f"(d[26]), "+f"(d[27]), "+f"(d[28]), "+f"(d[29]), "+f"(d[30]), "+f"(d[31])
    : "r"(a0), "r"(a1), "r"(a2), "r"(a3), "r"(db), "n"(SD));
}


constexpr int RING = 5;
constexpr uint32_t STAGE = 32768;
constexpr uint32_t OFF_X = 32768, OFF_W = 65536, OFF_MISC = OFF_W + RING * STAGE;
constexpr int SMEM_BYTES = OFF_MISC + 256 + 1024 + 1024;

struct Ctx {
  uint32_t sA, sX, sW, full, empty, stats;
  uint32_t frag;
  uint32_t rsw;
  uint32_t hi;
  int wg, tid, lane;
  uint32_t dry;
};
__device__ __forceinline__ uint32_t stage_wait(const Ctx& c, int n) {
  const int q = n / RING, s = n - q * RING;
  mbar_wait(c.full + 8 * s, (q | c.dry) & 1);
  return dlo(c.sW + s * STAGE, 0);
}
__device__ __forceinline__ void stage_release(const Ctx& c, int n) {
  const int s = n % RING;
  if (c.tid == 0) mbar_arrive(c.empty + 8 * s);
}
__device__ __forceinline__ void turn_begin(const Ctx& c) { bar_sync(5 + c.wg, 256); }
__device__ __forceinline__ void turn_end(const Ctx& c) { bar_arrive(5 + (c.wg ^ 1), 256); }
template<int FIRST, int LAST> __device__ __forceinline__ void piece_ss(const Ctx& c, float (&acc)[64], uint32_t dA, uint32_t dB) {
  dB += (16384 >> 4) << 16;
  wg_ss_n128_tb1<FIRST ? 0 : 1>(acc, dA, dB);
#pragma unroll
  for (int kk = 1; kk < 8; kk++) {
    wg_ss_n128_tb1<1>(acc, dA + (kk >> 2) * 512 + (kk & 3) * 2, dB + kk * 128);
  }
  if (LAST) turn_end(c);
}
__device__ __forceinline__ void ff_g1(const Ctx& c, float (&h)[32], uint32_t dA, uint32_t dB) {
  wg_ss_n64_tb1<0>(h, dA, dB);
#pragma unroll
  for (int kk = 1; kk < 16; kk++) {
    wg_ss_n64_tb1<1>(h, dA + (kk >> 2) * 512 + (kk & 3) * 2, dB + kk * 128);
  }
}
__device__ __forceinline__ void ff_g2(float (&acc)[64], const uint32_t (&P)[16], uint32_t dB, int half) {
  dB += ((8192 >> 4) << 16) + half * 1024;
#pragma unroll
  for (int kk = 0; kk < 4; kk++) wg_rs_n128_tb1<1>(acc, P[4 * kk], P[4 * kk + 1], P[4 * kk + 2], P[4 * kk + 3], dB + kk * 128);
}
struct NoHook { __device__ __forceinline__ void operator()() const {} };
template<int FIRST, class Hook = NoHook> __device__ __forceinline__ void gemm256(const Ctx& c, float (&acc)[64], int n, Hook hook = Hook()) {
  const uint32_t dA = dlo(c.sA, 16);
  uint32_t b = stage_wait(c, n);
  turn_begin(c);
  wg_fence(); piece_ss<FIRST, 0>(c, acc, dA, b); wg_commit();
  b = stage_wait(c, n + 1);
  wg_fence(); piece_ss<0, 1>(c, acc, dA + 1024, b); wg_commit();
  hook();
  wg_wait<1>(); stage_release(c, n);
  wg_wait<0>(); stage_release(c, n + 1);
}
__device__ __forceinline__ uint32_t frag_addr(const Ctx& c, uint32_t tile, int j) {
  return tile + (2 * c.wg + (j >> 2)) * 8192 + c.frag + ((((j & 3) * 2 + c.hi) ^ c.rsw) << 4);
}
__device__ __forceinline__ void load_half(const Ctx& c, uint32_t tile, float (&v)[64]) {
#pragma unroll
  for (int j = 0; j < 8; j++) {
    uint32_t r0, r1, r2, r3;
    ldsm_x4(frag_addr(c, tile, j), r0, r1, r2, r3);
    v[8 * j] = bf_lo(r0); v[8 * j + 1] = bf_hi(r0); v[8 * j + 2] = bf_lo(r1); v[8 * j + 3] = bf_hi(r1);
    v[8 * j + 4] = bf_lo(r2); v[8 * j + 5] = bf_hi(r2); v[8 * j + 6] = bf_lo(r3); v[8 * j + 7] = bf_hi(r3);
  }
}
__device__ __forceinline__ void store_half(const Ctx& c, uint32_t tile, const float (&v)[64], float a0, float b0, float a1, float b1) {
#pragma unroll
  for (int j = 0; j < 8; j++)
    stsm_x4(frag_addr(c, tile, j),
            pack_bf16(fmaf(v[8 * j], a0, b0), fmaf(v[8 * j + 1], a0, b0)), pack_bf16(fmaf(v[8 * j + 2], a1, b1), fmaf(v[8 * j + 3], a1, b1)),
            pack_bf16(fmaf(v[8 * j + 4], a0, b0), fmaf(v[8 * j + 5], a0, b0)), pack_bf16(fmaf(v[8 * j + 6], a1, b1), fmaf(v[8 * j + 7], a1, b1)));
}
__device__ __forceinline__ void store_half_raw(const Ctx& c, uint32_t tile, const float (&v)[64]) {
#pragma unroll
  for (int j = 0; j < 8; j++)
    stsm_x4(frag_addr(c, tile, j), pack_bf16(v[8 * j], v[8 * j + 1]), pack_bf16(v[8 * j + 2], v[8 * j + 3]),
            pack_bf16(v[8 * j + 4], v[8 * j + 5]), pack_bf16(v[8 * j + 6], v[8 * j + 7]));
}
__device__ __forceinline__ void ln_stats(const Ctx& c, const float (&v)[64], float scale, float& a0, float& b0, float& a1, float& b1) {
  float s0 = 0.f, s1 = 0.f, q0 = 0.f, q1 = 0.f, s2 = 0.f, s3 = 0.f, q2 = 0.f, q3 = 0.f;
#pragma unroll
  for (int i = 0; i < 16; i++) {
    s0 += v[4 * i]; q0 = fmaf(v[4 * i], v[4 * i], q0);
    s2 += v[4 * i + 1]; q2 = fmaf(v[4 * i + 1], v[4 * i + 1], q2);
    s1 += v[4 * i + 2]; q1 = fmaf(v[4 * i + 2], v[4 * i + 2], q1);
    s3 += v[4 * i + 3]; q3 = fmaf(v[4 * i + 3], v[4 * i + 3], q3);
  }
  s0 += s2; q0 += q2; s1 += s3; q1 += q3;
  s0 += __shfl_xor_sync(0xffffffff, s0, 1); q0 += __shfl_xor_sync(0xffffffff, q0, 1);
  s1 += __shfl_xor_sync(0xffffffff, s1, 1); q1 += __shfl_xor_sync(0xffffffff, q1, 1);
  s0 += __shfl_xor_sync(0xffffffff, s0, 2); q0 += __shfl_xor_sync(0xffffffff, q0, 2);
  s1 += __shfl_xor_sync(0xffffffff, s1, 2); q1 += __shfl_xor_sync(0xffffffff, q1, 2);
  const uint32_t row = (c.tid >> 5) * 16 + (c.lane >> 2);
  if ((c.lane & 3) == 0) {
    sts64f(c.stats + c.wg * 512 + row * 8, s0, q0);
    sts64f(c.stats + c.wg * 512 + (row + 8) * 8, s1, q1);
  }
  bar_sync(1, 256);
  const float2 o0 = lds64f(c.stats + (c.wg ^ 1) * 512 + row * 8), o1 = lds64f(c.stats + (c.wg ^ 1) * 512 + (row + 8) * 8);
  const float m0 = (s0 + o0.x) * (1.f / 256.f), m1 = (s1 + o1.x) * (1.f / 256.f);
  const float var0 = fmaxf(fmaf(-m0, m0, (q0 + o0.y) * (1.f / 256.f)), 0.f), var1 = fmaxf(fmaf(-m1, m1, (q1 + o1.y) * (1.f / 256.f)), 0.f);
  a0 = rsqrtf(var0 + 1e-5f) * scale; a1 = rsqrtf(var1 + 1e-5f) * scale;
  b0 = -m0 * a0; b1 = -m1 * a1;
}
__device__ __forceinline__ float silu_half(float h) { return fmaf(h, tanh_fast(h), h); }
__device__ __forceinline__ float silu_quarter(float h) { const float q = 0.5f * h; return fmaf(q, tanh_fast(h), q); }
__device__ __forceinline__ void silu_pack(const float (&acc)[32], uint32_t (&P)[16]) {
#pragma unroll
  for (int i = 0; i < 16; i++) P[i] = pack_bf16(silu_quarter(acc[2 * i]), silu_quarter(acc[2 * i + 1]));
}
__device__ __forceinline__ void ff_block(const Ctx& c, int n0, float (&own)[64]) {
  float oth[64], h[32];
  uint32_t P[16];
#pragma unroll
  for (int i = 0; i < 64; i++) oth[i] = 0.f;
  const uint32_t dA = dlo(c.sA, 16);
  {
    const uint32_t b = stage_wait(c, n0 + c.wg);
    turn_begin(c);
    wg_fence(); ff_g1(c, h, dA, b); wg_commit();
    turn_end(c);
    wg_wait<0>(); stage_release(c, n0 + c.wg);
    silu_pack(h, P);
  }
#pragma unroll 1
  for (int it = c.dry ? 7 : 1; it < 8; it++) {
    const int n = n0 + 4 * it - 2 + 2 * c.wg;
    uint32_t b = stage_wait(c, n);
    turn_begin(c);
    wg_fence(); ff_g2(own, P, b, c.wg); ff_g2(oth, P, b, c.wg ^ 1); wg_commit();
    b = stage_wait(c, n + 1);
    wg_fence(); ff_g1(c, h, dA, b); wg_commit();
    turn_end(c);
    wg_wait<1>(); stage_release(c, n);
    wg_wait<0>(); stage_release(c, n + 1);
    silu_pack(h, P);
  }
  if (c.wg == 0) bar_arrive(2, 256);
  {
    const int n = n0 + 30 + c.wg;
    const uint32_t b = stage_wait(c, n);
    turn_begin(c);
    wg_fence(); ff_g2(oth, P, b, c.wg ^ 1); wg_commit();
    ff_g2(own, P, b, c.wg); wg_commit();
    turn_end(c);
    wg_wait<1>();
    if (c.wg == 1) bar_sync(2, 256);
    const uint32_t e = (c.wg == 0 ? c.sX : c.sA) + c.tid * 16;
#pragma unroll
    for (int i = 0; i < 16; i++)
      sts128(e + i * 2048, make_uint4(__float_as_uint(oth[4 * i]), __float_as_uint(oth[4 * i + 1]), __float_as_uint(oth[4 * i + 2]), __float_as_uint(oth[4 * i + 3])));
    wg_wait<0>(); stage_release(c, n);
  }
  bar_sync(1, 256);
  const uint32_t e = (c.wg == 0 ? c.sA : c.sX) + c.tid * 16;
#pragma unroll
  for (int i = 0; i < 16; i++) {
    const uint4 u = lds128(e + i * 2048);
    own[4 * i] += __uint_as_float(u.x); own[4 * i + 1] += __uint_as_float(u.y);
    own[4 * i + 2] += __uint_as_float(u.z); own[4 * i + 3] += __uint_as_float(u.w);
  }
}
struct Maps { CUtensorMap X, W1a, W1b, Wqkv, QKVst, Q, KV, Wo, Pw1, Pw2, W2a, W2b, Out; uint16_t stage[92]; };
constexpr int NA = 44;
constexpr int NC = 45;
#define STAGE_TABLE {0x1, 0x11, 0x2, 0x21, 0x102, 0x31, 0x202, 0x41, 0x302, 0x51, 0x402, 0x61, 0x502, 0x71, 0x602, 0x81, 0x702, 0x91, 0x802, 0xa1, 0x902, 0xb1, 0xa02, 0xc1, 0xb02, 0xd1, 0xc02, 0xe1, 0xd02, 0xf1, 0xe02, 0xf02, 0x3, 0x203, 0x23, 0x223, 0x43, 0x243, 0x63, 0x263, 0x83, 0x283, 0xa3, 0x2a3, 0x7, 0x207, 0x27, 0x227, 0x8, 0x208, 0x2008, 0x2208, 0x1008, 0x1208, 0x3008, 0x3208, 0x9, 0x29, 0x209, 0x229, 0xa, 0x1a, 0xb, 0x2a, 0x10b, 0x3a, 0x20b, 0x4a, 0x30b, 0x5a, 0x40b, 0x6a, 0x50b, 0x7a, 0x60b, 0x8a, 0x70b, 0x9a, 0x80b, 0xaa, 0x90b, 0xba, 0xa0b, 0xca, 0xb0b, 0xda, 0xc0b, 0xea, 0xd0b, 0xfa, 0xe0b, 0xf0b}
__device__ __forceinline__ void load_stage(uint32_t dst, uint32_t bar, const Maps& tm, int n) {
  const uint32_t e = tm.stage[n - (n > NA)];
  mbar_expect_tx(bar, STAGE);
  tma_load_3d(dst, &tm.X + (e & 15), bar, (e >> 12) * 64, ((e >> 8) & 15) * 64, (e >> 4) & 15);
}
__device__ __forceinline__ void produce(uint32_t sW, uint32_t full, const Maps& tm, int n0, int n1) {
  uint32_t s = n0 % RING, ph = ((n0 / RING) & 1) ^ 1;
#pragma unroll 1
  for (int n = n0; n < n1; n++) {
    mbar_wait(full + 8 * RING + 8 * s, ph);
    load_stage(sW + s * STAGE, full + 8 * s, tm, n);
    if (++s == RING) { s = 0; ph ^= 1; }
  }
}
__device__ __forceinline__ Ctx make_ctx(uint32_t base, uint32_t dry) {
  Ctx c; c.dry = dry;
  c.sA = base; c.sX = base + OFF_X; c.sW = base + OFF_W;
  c.full = base + OFF_MISC; c.empty = c.full + 8 * RING; c.stats = base + OFF_MISC + 256;
  c.wg = __shfl_sync(0xffffffff, (int)(threadIdx.x >> 7), 0);
  c.tid = threadIdx.x & 127; c.lane = threadIdx.x & 31;
  const uint32_t r = (c.tid >> 5) * 16 + (c.lane & 7) + ((c.lane >> 3) & 1) * 8;
  c.frag = r * 128; c.rsw = r & 7; c.hi = c.lane >> 4;
  return c;
}

constexpr int NSTG = 4;
constexpr int KVB = 160 * 128;
constexpr int NKV = T_ / 160;
static_assert(NSTG * 2 * KVB == RING * STAGE, "the K/V ring reuses the weight ring");

struct AttCtx { uint32_t sKV, full, empty, dry, wfull; const Maps* tm; int h, b, wg; };
__device__ __forceinline__ int kv_slot(int i) { return (i + 3) & 3; }
__device__ __forceinline__ void att_load(const AttCtx& a, int i, int v) {
  const int s = i & 3;
  mbar_expect_tx(a.full + 8 * (s + v * NSTG), KVB);
  tma_load_3d(a.sKV + kv_slot(i) * 2 * KVB + v * KVB, &a.tm->KV, a.full + 8 * (s + v * NSTG), 256 + v * 256 + a.h * 64, i * 160, a.b);
}
__device__ __forceinline__ void att_load_stage(const AttCtx& a, int i) { att_load(a, i, 0); att_load(a, i, 1); }
__device__ __forceinline__ void att_init_bars(const AttCtx& a) {
  for (int i = 0; i < NSTG; i++) { mbar_init(a.full + 8 * i, 1); mbar_init(a.full + 8 * (NSTG + i), 1); mbar_init(a.empty + 8 * i, 4); }
}
__device__ __forceinline__ void att_qk(float (&S)[40], uint32_t dQ, uint32_t kd) {
  wg_ss_n80_tb0<0>(S, dQ, kd);
#pragma unroll
  for (int kk = 1; kk < 4; kk++) wg_ss_n80_tb0<1>(S, dQ + kk * 2, kd + kk * 2);
}
__device__ __forceinline__ void att_pv(float (&O)[32], const uint32_t (&P)[20], uint32_t vd) {
#pragma unroll
  for (int kk = 0; kk < 5; kk++) wg_rs_n64_tb1<1>(O, P[kk * 4], P[kk * 4 + 1], P[kk * 4 + 2], P[kk * 4 + 3], vd + kk * 128);
}
template<bool SAFE>
__device__ __forceinline__ void att_softmax(const float (&S)[40], uint32_t (&P)[20], float (&O)[32], float& m0, float& m1, float& l0, float& l1) {
  if (SAFE) {
    float x0 = fmaxf(S[0], S[1]), x1 = fmaxf(S[2], S[3]);
#pragma unroll
    for (int i = 1; i < 10; i++) { x0 = fmaxf(x0, fmaxf(S[4 * i], S[4 * i + 1])); x1 = fmaxf(x1, fmaxf(S[4 * i + 2], S[4 * i + 3])); }
    x0 = fmaxf(x0, __shfl_xor_sync(0xffffffff, x0, 1)); x1 = fmaxf(x1, __shfl_xor_sync(0xffffffff, x1, 1));
    x0 = fmaxf(x0, __shfl_xor_sync(0xffffffff, x0, 2)); x1 = fmaxf(x1, __shfl_xor_sync(0xffffffff, x1, 2));
    const float n0 = fmaxf(m0, x0), n1 = fmaxf(m1, x1);
    const float f0 = ex2(m0 - n0), f1 = ex2(m1 - n1);
    m0 = n0; m1 = n1; l0 *= f0; l1 *= f1;
#pragma unroll
    for (int i = 0; i < 8; i++) { O[4 * i] *= f0; O[4 * i + 1] *= f0; O[4 * i + 2] *= f1; O[4 * i + 3] *= f1; }
  }
#pragma unroll
  for (int i = 0; i < 10; i++) {
    float p0, p1, p2, p3;
    if (SAFE) { p0 = ex2(S[4 * i] - m0); p1 = ex2(S[4 * i + 1] - m0); p2 = ex2(S[4 * i + 2] - m1); p3 = ex2(S[4 * i + 3] - m1); }
    else { p0 = ex2(S[4 * i]); p1 = ex2(S[4 * i + 1]); p2 = ex2(S[4 * i + 2]); p3 = ex2(S[4 * i + 3]); }
    l0 += p0 + p1; l1 += p2 + p3;
    P[2 * i] = pack_bf16(p0, p1); P[2 * i + 1] = pack_bf16(p2, p3);
  }
}
template<bool SAFE>
__device__ __forceinline__ void att_refill(const AttCtx& a, int it) {
  if ((threadIdx.x & 127) == 0) {
    mbar_arrive(a.empty + 8 * (it & 3));
    if (a.wg == (it & 3) && it >= 1 && !a.dry) {
      const bool kv = it - 1 + NSTG < NKV;
      if (kv || (!SAFE && a.wfull)) {
        mbar_wait(a.empty + 8 * ((it - 1) & 3), ((it - 1) >> 2) & 1);
        if (kv) att_load_stage(a, it - 1 + NSTG);
        else load_stage(a.sKV + (it - 22) * STAGE, a.wfull + 8 * (it - 22), *a.tm, NC + it - 22);
      }
    }
  }
  __syncwarp();
}
constexpr uint32_t KV_STG = 2 * KVB / 16, KV_VOFF = KVB / 16, KV_HALF = 80 * 128 / 16;
template<bool SAFE>
__device__ __forceinline__ void att_pass(const AttCtx& a, uint32_t dQ, float (&O)[32], float& l0, float& l1) {
  float S[40];
  uint32_t P[20];
  float m0 = -INFINITY, m1 = -INFINITY;
  l0 = 0.f; l1 = 0.f;
#pragma unroll
  for (int i = 0; i < 32; i++) O[i] = 0.f;
  const uint32_t dKV = dlo(a.sKV, 16);
  if (SAFE) {
#pragma unroll 1
    for (int j = 0; j < 2 * NKV; j++) {
      const int it = j >> 1, s = it & 3;
      const uint32_t kb = dKV + kv_slot(it) * KV_STG + (j & 1) * KV_HALF;
      mbar_wait(a.full + 8 * s, (it >> 2) & 1);
      wg_fence(); att_qk(S, dQ, kb); wg_commit(); wg_wait<0>();
      att_softmax<true>(S, P, O, m0, m1, l0, l1);
      mbar_wait(a.full + 8 * (NSTG + s), (it >> 2) & 1);
      wg_fence(); att_pv(O, P, kb + KV_VOFF); wg_commit(); wg_wait<0>();
      if (j & 1) att_refill<true>(a, it);
    }
  } else {
    mbar_wait(a.full, a.dry);
    wg_fence(); att_qk(S, dQ, dKV + 3 * KV_STG); wg_commit(); wg_wait<0>();
    att_softmax<false>(S, P, O, m0, m1, l0, l1);
    mbar_wait(a.full + 8 * NSTG, a.dry);
    wg_fence(); att_pv(O, P, dKV + 3 * KV_STG + KV_VOFF); att_qk(S, dQ, dKV + 3 * KV_STG + KV_HALF); wg_commit(); wg_wait<0>();
#pragma unroll 1
    for (int it = a.dry ? NKV - 2 : 0; it < NKV - 1; it++) {
      const int sn = (it + 1) & 3;
      const uint32_t kb = dKV + kv_slot(it) * KV_STG, kn = dKV + kv_slot(it + 1) * KV_STG, par = (((it + 1) >> 2) | a.dry) & 1;
      att_softmax<false>(S, P, O, m0, m1, l0, l1);
      mbar_wait(a.full + 8 * sn, par);
      wg_fence(); att_pv(O, P, kb + KV_VOFF + KV_HALF); att_qk(S, dQ, kn); wg_commit(); wg_wait<0>();
      att_refill<false>(a, it);
      att_softmax<false>(S, P, O, m0, m1, l0, l1);
      mbar_wait(a.full + 8 * (NSTG + sn), par);
      wg_fence(); att_pv(O, P, kn + KV_VOFF); att_qk(S, dQ, kn + KV_HALF); wg_commit(); wg_wait<0>();
    }
    att_softmax<false>(S, P, O, m0, m1, l0, l1);
    wg_fence(); att_pv(O, P, dKV + 3 * KV_STG + KV_VOFF + KV_HALF); wg_commit(); wg_wait<0>();
  }
  l0 += __shfl_xor_sync(0xffffffff, l0, 1); l1 += __shfl_xor_sync(0xffffffff, l1, 1);
  l0 += __shfl_xor_sync(0xffffffff, l0, 2); l1 += __shfl_xor_sync(0xffffffff, l1, 2);
}

struct Wptrs { const void* p[8]; uint32_t bytes[8]; };

constexpr uint32_t B_FULL = 0, B_EMPTY = 8 * RING, B_X = 16 * RING, B_ADONE = B_X + 8, B_Q = B_X + 16, B_EP = B_X + 24, B_ATT = B_X + 32;

__global__ void __launch_bounds__(512, 1) conformer_kernel(const __grid_constant__ Maps tm, const __grid_constant__ Wptrs wp, const uint4* __restrict__ dw) {
  extern __shared__ uint8_t smem_raw[];
  const uint32_t base = (smem_u32(smem_raw) + 1023) & ~1023u, misc = base + OFF_MISC;
  const uint32_t dry = blockIdx.x >= 128;
  const int tile = dry ? 0 : blockIdx.x;
  const bool has_tile = dry ? blockIdx.x == 128 : tile < NTILE;
  const int wg = __shfl_sync(0xffffffff, (int)(threadIdx.x >> 7), 0);
  AttCtx a;
  a.sKV = base + OFF_W; a.full = misc + B_ATT; a.empty = a.full + 16 * NSTG; a.tm = &tm;
  a.h = (blockIdx.x >> 4) & 3; a.b = (blockIdx.x >> 6) & 1; a.wg = wg; a.dry = dry; a.wfull = has_tile ? misc + B_FULL : 0;
  const int qt = blockIdx.x & 15;

  if (threadIdx.x == 256) {
    mbar_init(misc + B_X, 1);
    for (int i = 0; i < RING; i++) { mbar_init(misc + B_FULL + 8 * i, 1); mbar_init(misc + B_EMPTY + 8 * i, 1); }
    asm volatile("fence.mbarrier_init.release.cluster;" ::: "memory");
    if (has_tile && !dry) {
      mbar_expect_tx(misc + B_X, 32768);
      tma_load_3d(base + OFF_X, &tm.X, misc + B_X, 0, tile * 64, 0);
    }
  } else if (threadIdx.x == 288) {
    mbar_init(misc + B_ADONE, 2);
    mbar_init(misc + B_Q, 1);
    mbar_init(misc + B_EP, 1);
    att_init_bars(a);
    asm volatile("fence.mbarrier_init.release.cluster;" ::: "memory");
  } else if (threadIdx.x >= 320 && threadIdx.x < 333) {
    prefetch_tmap(&tm.X + (threadIdx.x - 320));
  }
  __syncthreads();
  if ((threadIdx.x & 31) == 0 && threadIdx.x >= 256 && threadIdx.x < 256 + 32 * RING && has_tile && !dry) {
    const int i = (threadIdx.x - 256) >> 5;
    load_stage(base + OFF_W + i * STAGE, misc + B_FULL + 8 * i, tm, i);
  }
  __syncwarp();
  auto get_epoch = [&]() {
    uint32_t e;
    mbar_wait(misc + B_EP, 0);
    asm volatile("ld.shared.u32 %0, [%1];" : "=r"(e) : "r"(misc + 248) : "memory");
    return e;
  };

  if (wg < 2) {
    asm volatile("setmaxnreg.inc.sync.aligned.u32 232;");
    if (has_tile) {
      const Ctx c = make_ctx(base, dry);
      if (c.wg == 1) turn_end(c);
      float own[64];
      float a0, b0, a1, b1;
#pragma unroll 1
      for (int rep = 0; rep < 2; rep++) {
        if (rep) mbar_wait(misc + B_X, dry);
        load_half(c, c.sX, own);
        ln_stats(c, own, 0.5f, a0, b0, a1, b1);
        store_half(c, c.sA, own, a0, b0, a1, b1);
        fence_async_smem();
        bar_sync(1, 256);
      }
      ff_block(c, 0, own);
      ln_stats(c, own, 1.f, a0, b0, a1, b1);
      store_half(c, c.sA, own, a0, b0, a1, b1);
      fence_async_smem();
      bar_sync(1, 256);
#pragma unroll 1
      for (int cc = dry ? 2 : 0; cc < 3; cc++) {
        float acc[64];
        const int j = 2 * cc + c.wg;
        gemm256<1>(c, acc, 32 + 2 * j, [&]() {
          if (c.tid == 0 && !dry) {
            if (cc == 2) {
              bulk_wait_all();
              if (tile <= 62) cnt_signal(g_cnt1);
              if (tile >= 62) cnt_signal(g_cnt1 + 64);
            } else bulk_wait_read();
          }
          bar_sync(3 + c.wg, 128);
        });
        if (cc == 2 && !dry) { bar_arrive(9, 288); if (c.tid == 0) mbar_arrive(misc + B_ADONE); }
        if (cc == 0) {
#pragma unroll
          for (int i = 0; i < 64; i++) acc[i] *= 0.125f * 1.4426950408889634f;
        }
        store_half_raw(c, c.sX, acc);
        fence_async_smem();
        bar_sync(3 + c.wg, 128);
        if (c.tid == 0 && !dry) { tma_store_3d(&tm.QKVst, c.sX + c.wg * 16384, 0, tile * 64, 2 * j); bulk_commit(); }
      }
      if (c.tid == 0) bulk_wait_read();
      bar_sync(3 + c.wg, 128);
      store_half_raw(c, c.sX, own);
    }
    else bar_sync(3 + wg, 128);
    asm volatile("setmaxnreg.dec.sync.aligned.u32 128;");
    bar_arrive(7, 384); bar_arrive(8, 384);
    if (has_tile && !dry && (threadIdx.x & 127) == 0) {
      bulk_wait_all();
      if (tile <= 62) cnt_signal(g_cnt1 + 32);
      if (tile >= 62) cnt_signal(g_cnt1 + 96);
    }
    __syncwarp();
  } else {
    asm volatile("setmaxnreg.dec.sync.aligned.u32 24;");
    const uint32_t full = misc + B_FULL;
    if (threadIdx.x == 320) {
      const uint32_t e = atomicAdd(&g_start, 1) / NCTA;
      asm volatile("st.shared.u32 [%0], %1;" :: "r"(misc + 248), "r"(e + 1) : "memory");
      mbar_arrive(misc + B_EP);
    }
    if (dry) {
    } else if (threadIdx.x == 256) {
      if (has_tile) {
        produce(base + OFF_W, full, tm, RING, NA);
        mbar_wait(full + 8 * RING + 8 * 4, 1);
        mbar_arrive(full + 8 * 4); mbar_arrive(full + 8 * RING + 8 * 4);
        mbar_wait(misc + B_ADONE, 0);
      }
      cnt_wait(g_cnt1 + a.b * 64, 126 * get_epoch());
      mbar_expect_tx(misc + B_Q, 32768);
      tma_load_3d(base, &tm.Q, misc + B_Q, a.h * 64, qt * 256, a.b);
      att_load(a, 0, 0);
      mbar_wait(misc + B_Q, 0);
#pragma unroll 1
      for (int i = 1; i < NSTG; i++) att_load(a, i, 0);
    } else if ((threadIdx.x >> 5) == 12) {
      if (has_tile) bar_sync(9, 288);
      if (threadIdx.x == 384) {
        cnt_wait(g_cnt1 + a.b * 64 + 32, 126 * get_epoch());
        att_load(a, 0, 1);
        mbar_wait(a.full + 8 * NSTG, 0);
#pragma unroll 1
        for (int i = 1; i < NSTG; i++) att_load(a, i, 1);
      }
    } else if (has_tile && threadIdx.x >= 288 && threadIdx.x < 296) {
      const int w = threadIdx.x - 288;
      mbar_wait(misc + B_X, 0);
      const uint32_t bytes = wp.bytes[w], per = ((bytes / NTILE) + 127) & ~127u, off = per * tile;
      if (off < bytes) l2_prefetch((const uint8_t*)wp.p[w] + off, min(per, bytes - off));
    } else if (has_tile && threadIdx.x >= 416) {
      mbar_wait(full, 0);
      const int t = threadIdx.x - 416;
#pragma unroll 2
      for (int i = t; i < 2048; i += 96) g_att[tile * 2048 + i] = make_uint4(~0u, ~0u, ~0u, ~0u);
      g_halo[tile * 128 + t] = make_uint4(~0u, ~0u, ~0u, ~0u);
      if (t < 32) g_halo[tile * 128 + 96 + t] = make_uint4(~0u, ~0u, ~0u, ~0u);
    }
    __syncwarp();
    bar_sync(5 + wg, 384);
    asm volatile("setmaxnreg.inc.sync.aligned.u32 128;");
  }

  if (blockIdx.x == 128) return;
  if (blockIdx.x != 130) {
    const int lane = threadIdx.x & 31, wq = (threadIdx.x >> 5) & 3;
    const uint32_t dQ = dlo(base + wg * 8192, 16);
    float O[32], l0, l1;
    mbar_wait(misc + B_Q, dry);
    att_pass<false>(a, dQ, O, l0, l1);
    float z = 0.f;
#pragma unroll
    for (int i = 0; i < 32; i++) z = fmaf(O[i], 0.f, z);
    const bool ok = (l0 >= 0x1p-40f) && (l0 <= 0x1p80f) && (l1 >= 0x1p-40f) && (l1 <= 0x1p80f) && (z == 0.f);
    const bool warp_bad = !__all_sync(0xffffffff, ok) && !dry;
    auto store_out = [&]() {
      const float i0 = 1.f / l0, i1 = 1.f / l1;
      const int row = qt * 256 + wg * 64 + wq * 16;
      if (row < T_ && !dry) {
        const int slab = (a.b * T_ + row) / 16;
        uint4* op = g_att + (slab * 16 + a.h * 4) * 32 + lane;
#pragma unroll
        for (int j = 0; j < 4; j++)
          asm volatile("st.relaxed.gpu.global.v4.u32 [%0], {%1,%2,%3,%4};" :: "l"(op + j * 32),
                       "r"(pack_bf16(O[8 * j] * i0, O[8 * j + 1] * i0)), "r"(pack_bf16(O[8 * j + 2] * i1, O[8 * j + 3] * i1)),
                       "r"(pack_bf16(O[8 * j + 4] * i0, O[8 * j + 5] * i0)), "r"(pack_bf16(O[8 * j + 6] * i1, O[8 * j + 7] * i1)) : "memory");
      }
    };
    if (!warp_bad) store_out();
    if (__syncthreads_or(warp_bad)) {
      if (threadIdx.x == 0) {
        if (has_tile) { mbar_wait(misc + B_FULL, 1); mbar_wait(misc + B_FULL + 8, 1); }
        for (int i = 0; i < 3 * NSTG; i++) mbar_inval(a.full + 8 * i);
        att_init_bars(a);
        asm volatile("fence.mbarrier_init.release.cluster;" ::: "memory");
        fence_async_smem();
#pragma unroll 1
        for (int i = 0; i < NSTG; i++) att_load_stage(a, i);
      }
      __syncthreads();
      att_pass<true>(a, dQ, O, l0, l1);
      if (warp_bad) store_out();
      __syncthreads();
      if (has_tile) {
        if (threadIdx.x == 32) {
          load_stage(base + OFF_W, misc + B_X, tm, NC);
          load_stage(base + OFF_W + STAGE, misc + B_Q, tm, NC + 1);
        }
        mbar_wait(misc + B_X, 1); mbar_wait(misc + B_Q, 1);
      }
    }
  } else {
    __syncthreads();
  }
  if (dry ? blockIdx.x != 130 : !has_tile) return;

  if (wg < 2) {
    asm volatile("setmaxnreg.inc.sync.aligned.u32 232;");
    const Ctx c = make_ctx(base, dry);
    if (dry && c.wg == 1) turn_end(c);
    float own[64];
    float a0, b0, a1, b1;
    {
      uint4 af[16];
      const int slab = tile * 4 + (c.tid >> 5);
      const uint4* ap = (dry ? (const uint4*)wp.p[3] : g_att + slab * 512) + c.lane;
      if (c.wg == 1) __nanosleep(300);
#pragma unroll
      for (int i = 0; i < 16; i++)
        asm volatile("ld.global.ca.v4.u32 {%0,%1,%2,%3}, [%4];" : "=r"(af[i].x), "=r"(af[i].y), "=r"(af[i].z), "=r"(af[i].w) : "l"(ap + i * 32) : "memory");
      load_half(c, c.sX, own);
      uint32_t miss = dry ? 0 : 15;
      for (uint32_t n = 0; n < (1u << 18); n++) {
#pragma unroll
        for (int hh = 0; hh < 4; hh++)
          if ((miss >> hh) & 1) {
            uint32_t mx = 0;
#pragma unroll
            for (int i = 4 * hh; i < 4 * hh + 4; i++) mx = max(mx, max(max(af[i].x, af[i].y), max(af[i].z, af[i].w)));
            if (__any_sync(0xffffffff, mx == ~0u)) {
#pragma unroll
              for (int i = 4 * hh; i < 4 * hh + 4; i++)
                asm volatile("ld.relaxed.gpu.global.v4.u32 {%0,%1,%2,%3}, [%4];" : "=r"(af[i].x), "=r"(af[i].y), "=r"(af[i].z), "=r"(af[i].w) : "l"(ap + i * 32) : "memory");
            } else miss &= ~(1u << hh);
          }
        if (!miss) break;
      }
      const int n = NC + 2 * c.wg;
      uint32_t b = stage_wait(c, n) + ((16384 >> 4) << 16);
      turn_begin(c);
      wg_fence();
#pragma unroll
      for (int kk = 0; kk < 8; kk++) wg_rs_n128_tb1<1>(own, af[kk].x, af[kk].y, af[kk].z, af[kk].w, b + kk * 128);
      wg_commit();
      b = stage_wait(c, n + 1) + ((16384 >> 4) << 16);
      wg_fence();
#pragma unroll
      for (int kk = 0; kk < 8; kk++) wg_rs_n128_tb1<1>(own, af[8 + kk].x, af[8 + kk].y, af[8 + kk].z, af[8 + kk].w, b + kk * 128);
      wg_commit();
      turn_end(c);
      wg_wait<1>(); stage_release(c, n);
      wg_wait<0>(); stage_release(c, n + 1);
    }
    ln_stats(c, own, 0.5f, a0, b0, a1, b1);
    store_half(c, c.sA, own, a0, b0, a1, b1);
    fence_async_smem();
    bar_sync(1, 256);
    uint4 dwr[5];
#pragma unroll
    for (int i = 0; i < 5; i++) dwr[i] = __ldg(dw + i * 32 + c.wg * 16 + (c.lane & 15));
    const bool top = c.tid < 8, pub = (top || c.tid >= 120) && !dry;
    uint32_t* halo_out = (uint32_t*)g_halo + (tile * 4 + (top ? (c.tid >> 2) : ((c.tid >> 2) - 28))) * 128 + c.wg * 64 + (c.lane & 3);
#pragma unroll 1
    for (int q = dry; q < 2; q++) {
      float ab[64];
      gemm256<1>(c, ab, NC + 4 + 4 * q + 2 * c.wg);
#pragma unroll
      for (int j = 0; j < 4; j++) {
        float g[8];
#pragma unroll
        for (int i = 0; i < 8; i++) g[i] = fmaf(ab[8 * j + i], tanh_fast(ab[32 + 8 * j + i]), ab[8 * j + i]);
        const uint32_t p0 = pack_bf16(g[0], g[1]), p1 = pack_bf16(g[2], g[3]), p2 = pack_bf16(g[4], g[5]), p3 = pack_bf16(g[6], g[7]);
        if (pub) {
          uint32_t* hp = halo_out + q * 32 + j * 8;
          asm volatile("st.relaxed.gpu.global.u32 [%0], %1;" :: "l"(hp), "r"(top ? p0 : p1) : "memory");
          asm volatile("st.relaxed.gpu.global.u32 [%0], %1;" :: "l"(hp + 4), "r"(top ? p2 : p3) : "memory");
        }
        stsm_x4(c.sX + (2 * c.wg + q) * 8192 + c.frag + (((j * 2 + c.hi) ^ c.rsw) << 4), p0, p1, p2, p3);
      }
    }
    bar_sync(3 + c.wg, 128);
    {
      const int wi = c.tid >> 4;
      const uint32_t col = (2 * c.wg + ((c.lane >> 3) & 1)) * 8192, ch = c.lane & 7;
      uint4 r[12];
      const int R0 = tile * 64 + wi * 8;
      const bool first = (R0 % T_) == 0, last = ((R0 + 8) % T_) == 0;
      const bool far = ((wi == 0 && !first) || (wi == 7 && !last)) && !dry;
      const uint4* sp = g_halo + (wi == 0 ? (tile - 1) * 4 + 2 : (tile + 1) * 4) * 32 + c.wg * 16 + (c.lane & 15);
      uint4 h0 = make_uint4(0, 0, 0, 0), h1 = h0;
      auto ld_halo = [&]() {
        asm volatile("ld.relaxed.gpu.global.v4.u32 {%0,%1,%2,%3}, [%4];" : "=r"(h0.x), "=r"(h0.y), "=r"(h0.z), "=r"(h0.w) : "l"(sp) : "memory");
        asm volatile("ld.relaxed.gpu.global.v4.u32 {%0,%1,%2,%3}, [%4];" : "=r"(h1.x), "=r"(h1.y), "=r"(h1.z), "=r"(h1.w) : "l"(sp + 32) : "memory");
      };
      if (far) ld_halo();
#pragma unroll
      for (int i = 0; i < 12; i++) {
        const int row = (wi * 8 - 2 + i) & 63;
        r[i] = lds128(c.sX + col + row * 128 + ((ch ^ (row & 7)) << 4));
      }
      uint32_t w[5][4];
#pragma unroll
      for (int k = 0; k < 5; k++) {
        w[k][0] = bmul2(dwr[k].x, 0x3F003F00u); w[k][1] = bmul2(dwr[k].y, 0x3F003F00u);
        w[k][2] = bmul2(dwr[k].z, 0x3F003F00u); w[k][3] = bmul2(dwr[k].w, 0x3F003F00u);
      }
      auto conv4 = [&](int i0, int i1, int i2, int i3, bool sync) {
        const int rows[4] = {i0, i1, i2, i3};
        uint32_t acc[4][4];
#pragma unroll
        for (int k = 0; k < 5; k++)
#pragma unroll
          for (int j = 0; j < 4; j++) {
            const uint4 x = r[rows[j] + k];
            acc[j][0] = k ? bfma2(x.x, w[k][0], acc[j][0]) : bmul2(x.x, w[0][0]);
            acc[j][1] = k ? bfma2(x.y, w[k][1], acc[j][1]) : bmul2(x.y, w[0][1]);
            acc[j][2] = k ? bfma2(x.z, w[k][2], acc[j][2]) : bmul2(x.z, w[0][2]);
            acc[j][3] = k ? bfma2(x.w, w[k][3], acc[j][3]) : bmul2(x.w, w[0][3]);
          }
#pragma unroll
        for (int j = 0; j < 4; j++)
#pragma unroll
          for (int q = 0; q < 4; q++) acc[j][q] = pack_bf16(silu_half(bf_lo(acc[j][q])), silu_half(bf_hi(acc[j][q])));
        if (sync) bar_sync(3 + c.wg, 128);
#pragma unroll
        for (int j = 0; j < 4; j++)
          sts128(c.sX + col + (wi * 8 + rows[j]) * 128 + ((ch ^ rows[j]) << 4), make_uint4(acc[j][0], acc[j][1], acc[j][2], acc[j][3]));
      };
      conv4(2, 3, 4, 5, true);
      if (far) {
        for (uint32_t n = 0; n < (1u << 18); n++) {
          const uint32_t mx = max(max(max(h0.x, h0.y), max(h0.z, h0.w)), max(max(h1.x, h1.y), max(h1.z, h1.w)));
          if (mx != ~0u) break;
          ld_halo();
        }
      }
      __syncwarp();
      if (first || (far && wi == 0)) { r[0] = h0; r[1] = h1; }
      if (last || (far && wi == 7)) { r[10] = h0; r[11] = h1; }
      conv4(0, 1, 6, 7, false);
    }
    fence_async_smem();
    bar_sync(c.wg == 0 ? 3 : 1, c.wg == 0 ? 128 : 256);
    {
      uint32_t b = stage_wait(c, NC + 12 + c.wg);
      turn_begin(c);
      wg_fence(); piece_ss<0, 0>(c, own, dlo(c.sX, 16), b); wg_commit();
      if (c.wg == 0) { turn_end(c); bar_sync(1, 256); turn_begin(c); }
      b = stage_wait(c, NC + 14 + c.wg);
      wg_fence(); piece_ss<0, 1>(c, own, dlo(c.sX, 16) + 1024, b); wg_commit();
    }
    wg_wait<1>(); stage_release(c, NC + 12 + c.wg);
    wg_wait<0>(); stage_release(c, NC + 14 + c.wg);
    ln_stats(c, own, 0.5f, a0, b0, a1, b1);
    if (c.wg == 1) { turn_begin(c); turn_end(c); }
    store_half(c, c.sA, own, a0, b0, a1, b1);
    fence_async_smem();
    bar_sync(1, 256);
    ff_block(c, NC + 16, own);
    ln_stats(c, own, 1.f, a0, b0, a1, b1);
    store_half(c, c.sX, own, a0, b0, a1, b1);
    fence_async_smem();
    bar_sync(3 + c.wg, 128);
    if (c.tid == 0 && !dry) { tma_store_3d(&tm.Out, c.sX + c.wg * 16384, 0, tile * 64, 2 * c.wg); bulk_commit(); bulk_wait_read(); }
  } else {
    asm volatile("setmaxnreg.dec.sync.aligned.u32 24;");
    if (threadIdx.x == 256 && !dry) {
      __nanosleep(200);
      produce(base + OFF_W, misc + B_FULL, tm, NC + 2, NC + 48);
    }
  }
}

typedef CUresult (*EncodeFn)(CUtensorMap*, CUtensorMapDataType, cuuint32_t, void*, const cuuint64_t*, const cuuint64_t*, const cuuint32_t*,
                             const cuuint32_t*, CUtensorMapInterleave, CUtensorMapSwizzle, CUtensorMapL2promotion, CUtensorMapFloatOOBfill);

CUtensorMap make_map(EncodeFn enc, const void* p, uint64_t d0, uint64_t d1, uint64_t d2, uint64_t s1, uint64_t s2, uint32_t b1, uint32_t b2) {
  CUtensorMap tm;
  cuuint64_t dims[3] = {d0, d1, d2};
  cuuint64_t strides[2] = {s1, s2};
  cuuint32_t box[3] = {64, b1, b2};
  cuuint32_t es[3] = {1, 1, 1};
  enc(&tm, CU_TENSOR_MAP_DATA_TYPE_BFLOAT16, 3, const_cast<void*>(p), dims, strides, box, es, CU_TENSOR_MAP_INTERLEAVE_NONE,
      CU_TENSOR_MAP_SWIZZLE_128B, CU_TENSOR_MAP_L2_PROMOTION_L2_256B, CU_TENSOR_MAP_FLOAT_OOB_FILL_NONE);
  return tm;
}
CUtensorMap blk_map(EncodeFn enc, const void* p, uint64_t rows, uint64_t cols, uint32_t boxrows, uint32_t boxblks) {
  return make_map(enc, p, 64, rows, cols / 64, cols * 2, 128, boxrows, boxblks);
}
CUtensorMap seq_map(EncodeFn enc, const void* p, uint64_t cols, uint32_t boxrows) {
  return make_map(enc, p, cols, T_, 2, cols * 2, cols * 2 * T_, boxrows, 1);
}

}

extern "C" void kernel_launch(void* const* d_in, const int* in_sizes, int n_in, void* d_out, int out_size) {
  (void)in_sizes; (void)n_in; (void)out_size;
  const void *x = d_in[0], *w1a = d_in[1], *w1b = d_in[2], *wqkv = d_in[3], *wo = d_in[4], *pw1 = d_in[5], *dw = d_in[6], *pw2 = d_in[7],
             *w2a = d_in[8], *w2b = d_in[9];
  void* fn = nullptr;
  cudaDriverEntryPointQueryResult qr;
  cudaGetDriverEntryPoint("cuTensorMapEncodeTiled", &fn, cudaEnableDefault, &qr);
  EncodeFn enc = (EncodeFn)fn;
  void* qkv;
  cudaGetSymbolAddress(&qkv, g_qkv);
  cudaFuncSetAttribute(conformer_kernel, cudaFuncAttributeMaxDynamicSharedMemorySize, SMEM_BYTES);

  Wptrs wp;
  const void* ws[8] = {w1a, w1b, wqkv, wo, pw1, pw2, w2a, w2b};
  const uint32_t wb[8] = {524288, 524288, 393216, 131072, 262144, 131072, 524288, 524288};
  for (int i = 0; i < 8; i++) { wp.p[i] = ws[i]; wp.bytes[i] = wb[i]; }
  Maps tm;
  const uint16_t tab[92] = STAGE_TABLE;
  for (int i = 0; i < 92; i++) tm.stage[i] = tab[i];
  tm.X = blk_map(enc, x, ROWS, 256, 64, 4);
  tm.W1a = blk_map(enc, w1a, 256, 1024, 256, 1);
  tm.W1b = blk_map(enc, w1b, 1024, 256, 64, 4);
  tm.Wqkv = blk_map(enc, wqkv, 256, 768, 128, 2);
  tm.QKVst = blk_map(enc, qkv, ROWS, 768, 64, 2);
  tm.Q = seq_map(enc, qkv, 768, 256);
  tm.KV = seq_map(enc, qkv, 768, 160);
  tm.Wo = blk_map(enc, wo, 256, 256, 128, 2);
  tm.Pw1 = make_map(enc, pw1, 256, 256, 2, 1024, 512, 128, 2);
  tm.Pw2 = blk_map(enc, pw2, 256, 256, 128, 2);
  tm.W2a = blk_map(enc, w2a, 256, 1024, 256, 1);
  tm.W2b = blk_map(enc, w2b, 1024, 256, 64, 4);
  tm.Out = blk_map(enc, d_out, ROWS, 256, 64, 2);
  conformer_kernel<<<NCTA, 512, SMEM_BYTES, cudaStreamPerThread>>>(tm, wp, (const uint4*)dw);
}
```

```cpp
#include <cuda_runtime.h>
#include <cuda_bf16.h>
#include <cuda.h>
#include <stdint.h>

namespace {

constexpr int T_ = 4000;
constexpr int ROWS = 8000;
constexpr int NTILE = 125;
constexpr int NCTA = 131;

__device__ __nv_bfloat16 g_qkv[ROWS * 768];
__device__ uint4 g_att[(ROWS / 16) * 16 * 32];
__device__ uint4 g_halo[NTILE * 4 * 32];
__device__ uint32_t g_start;
__device__ uint32_t g_cnt1[4 * 32];


__device__ __forceinline__ uint32_t smem_u32(const void* p) { return (uint32_t)__cvta_generic_to_shared(p); }
__device__ __forceinline__ void mbar_init(uint32_t bar, uint32_t cnt) { asm volatile("mbarrier.init.shared::cta.b64 [%0], %1;" :: "r"(bar), "r"(cnt) : "memory"); }
__device__ __forceinline__ void mbar_inval(uint32_t bar) { asm volatile("mbarrier.inval.shared::cta.b64 [%0];" :: "r"(bar) : "memory"); }
__device__ __forceinline__ void mbar_expect_tx(uint32_t bar, uint32_t bytes) { asm volatile("mbarrier.arrive.expect_tx.shared::cta.b64 _, [%0], %1;" :: "r"(bar), "r"(bytes) : "memory"); }
__device__ __forceinline__ void mbar_arrive(uint32_t bar) { asm volatile("mbarrier.arrive.shared::cta.b64 _, [%0];" :: "r"(bar) : "memory"); }
__device__ __forceinline__ void mbar_wait(uint32_t bar, uint32_t parity) {
  asm volatile("{\n.reg .pred p;\n.reg .u32 n;\n"
               "mbarrier.try_wait.parity.shared::cta.b64 p, [%0], %1;\n@p bra DONE_%=;\nmov.u32 n, 0;\n"
               "LOOP_%=:\nmbarrier.try_wait.parity.shared::cta.b64 p, [%0], %1;\n@p bra DONE_%=;\n"
               "add.u32 n, n, 1;\nsetp.lt.u32 p, n, 262144;\n@p bra LOOP_%=;\ntrap;\nDONE_%=:\n}\n" :: "r"(bar), "r"(parity) : "memory");
}
__device__ __forceinline__ void cnt_wait(const uint32_t* p, uint32_t target) {
  asm volatile("{\n.reg .pred p;\n.reg .u32 n, v;\nmov.u32 n, 0;\n"
               "LOOP_%=:\nld.relaxed.gpu.global.u32 v, [%0];\nsub.u32 v, v, %1;\nsetp.ge.s32 p, v, 0;\n@p bra DONE_%=;\n"
               "nanosleep.u32 40;\nadd.u32 n, n, 1;\nsetp.lt.u32 p, n, 262144;\n@p bra LOOP_%=;\ntrap;\nDONE_%=:\n}\n" :: "l"(p), "r"(target) : "memory");
}
__device__ __forceinline__ void cnt_signal(uint32_t* p) {
  asm volatile("red.relaxed.gpu.global.add.u32 [%0], 1;" :: "l"(p) : "memory");
}
__device__ __forceinline__ void tma_load_3d(uint32_t dst, const CUtensorMap* tm, uint32_t bar, int c0, int c1, int c2) {
  asm volatile("cp.async.bulk.tensor.3d.shared::cluster.global.mbarrier::complete_tx::bytes [%0], [%1, {%3, %4, %5}], [%2];"
    :: "r"(dst), "l"(tm), "r"(bar), "r"(c0), "r"(c1), "r"(c2) : "memory");
}
__device__ __forceinline__ void tma_store_3d(const CUtensorMap* tm, uint32_t src, int c0, int c1, int c2) {
  asm volatile("cp.async.bulk.tensor.3d.global.shared::cta.bulk_group [%0, {%2, %3, %4}], [%1];" :: "l"(tm), "r"(src), "r"(c0), "r"(c1), "r"(c2) : "memory");
}
__device__ __forceinline__ void bulk_commit() { asm volatile("cp.async.bulk.commit_group;" ::: "memory"); }
__device__ __forceinline__ void bulk_wait_read() { asm volatile("cp.async.bulk.wait_group.read 0;" ::: "memory"); }
__device__ __forceinline__ void bulk_wait_all() { asm volatile("cp.async.bulk.wait_group 0;" ::: "memory"); }
__device__ __forceinline__ void l2_prefetch(const void* p, uint32_t bytes) { asm volatile("cp.async.bulk.prefetch.L2.global [%0], %1;" :: "l"(p), "r"(bytes) : "memory"); }
__device__ __forceinline__ void prefetch_tmap(const CUtensorMap* tm) { asm volatile("prefetch.tensormap [%0];" :: "l"(tm) : "memory"); }
__device__ __forceinline__ void fence_async_smem() { asm volatile("fence.proxy.async.shared::cta;" ::: "memory"); }
__device__ __forceinline__ void wg_fence() { asm volatile("wgmma.fence.sync.aligned;" ::: "memory"); }
__device__ __forceinline__ void wg_commit() { asm volatile("wgmma.commit_group.sync.aligned;" ::: "memory"); }
template<int N> __device__ __forceinline__ void wg_wait() { asm volatile("wgmma.wait_group.sync.aligned %0;" :: "n"(N) : "memory"); }
__device__ __forceinline__ void bar_sync(int id, int n) { asm volatile("bar.sync %0, %1;" :: "r"(id), "r"(n) : "memory"); }
__device__ __forceinline__ void bar_arrive(int id, int n) { asm volatile("bar.arrive %0, %1;" :: "r"(id), "r"(n) : "memory"); }
__device__ __forceinline__ float ex2(float x) { float y; asm("ex2.approx.ftz.f32 %0, %1;" : "=f"(y) : "f"(x)); return y; }
__device__ __forceinline__ float tanh_fast(float x) { float y; asm("tanh.approx.f32 %0, %1;" : "=f"(y) : "f"(x)); return y; }
__device__ __forceinline__ uint32_t pack_bf16(float lo, float hi) { uint32_t r; asm("cvt.rn.bf16x2.f32 %0, %1, %2;" : "=r"(r) : "f"(hi), "f"(lo)); return r; }
__device__ __forceinline__ uint32_t bmul2(uint32_t a, uint32_t b) { uint32_t d; asm("mul.rn.bf16x2 %0, %1, %2;" : "=r"(d) : "r"(a), "r"(b)); return d; }
__device__ __forceinline__ uint32_t bfma2(uint32_t a, uint32_t b, uint32_t c) { uint32_t d; asm("fma.rn.bf16x2 %0, %1, %2, %3;" : "=r"(d) : "r"(a), "r"(b), "r"(c)); return d; }
__device__ __forceinline__ float bf_lo(uint32_t u) { return __uint_as_float(u << 16); }
__device__ __forceinline__ float bf_hi(uint32_t u) { return __uint_as_float(u & 0xffff0000u); }
__device__ __forceinline__ void ldsm_x4(uint32_t addr, uint32_t& r0, uint32_t& r1, uint32_t& r2, uint32_t& r3) {
  asm volatile("ldmatrix.sync.aligned.m8n8.x4.shared.b16 {%0,%1,%2,%3}, [%4];" : "=r"(r0), "=r"(r1), "=r"(r2), "=r"(r3) : "r"(addr) : "memory");
}
__device__ __forceinline__ void stsm_x4(uint32_t addr, uint32_t r0, uint32_t r1, uint32_t r2, uint32_t r3) {
  asm volatile("stmatrix.sync.aligned.m8n8.x4.shared.b16 [%0], {%1,%2,%3,%4};" :: "r"(addr), "r"(r0), "r"(r1), "r"(r2), "r"(r3) : "memory");
}
__device__ __forceinline__ void sts128(uint32_t addr, uint4 v) { asm volatile("st.shared.v4.b32 [%0], {%1,%2,%3,%4};" :: "r"(addr), "r"(v.x), "r"(v.y), "r"(v.z), "r"(v.w) : "memory"); }
__device__ __forceinline__ uint4 lds128(uint32_t addr) { uint4 v; asm volatile("ld.shared.v4.b32 {%0,%1,%2,%3}, [%4];" : "=r"(v.x), "=r"(v.y), "=r"(v.z), "=r"(v.w) : "r"(addr) : "memory"); return v; }
__device__ __forceinline__ void sts64f(uint32_t addr, float a, float b) { asm volatile("st.shared.v2.f32 [%0], {%1,%2};" :: "r"(addr), "f"(a), "f"(b) : "memory"); }
__device__ __forceinline__ float2 lds64f(uint32_t addr) { float2 v; asm volatile("ld.shared.v2.f32 {%0,%1}, [%2];" : "=f"(v.x), "=f"(v.y) : "r"(addr) : "memory"); return v; }
__device__ __forceinline__ uint32_t dlo(uint32_t addr, uint32_t lbo) { return ((addr & 0x3FFFF) >> 4) | ((lbo >> 4) << 16); }

template<int SD> __device__ __forceinline__ void wg_ss_n128_tb1(float (&d)[64], uint32_t da, uint32_t db) {
  asm volatile("{\n.reg .b64 da, db;\nmov.b64 da, {%64, 0x40000040};\nmov.b64 db, {%65, 0x40000040};\n"
    "wgmma.mma_async.sync.aligned.m64n128k16.f32.bf16.bf16 {%0, %1, %2, %3, %4, %5, %6, %7, %8, %9, %10, %11, %12, %13, %14, %15, %16, %17, %18, %19, %20, %21, %22, %23, %24, %25, %26, %27, %28, %29, %30, %31, %32, %33, %34, %35, %36, %37, %38, %39, %40, %41, %42, %43, %44, %45, %46, %47, %48, %49, %50, %51, %52, %53, %54, %55, %56, %57, %58, %59, %60, %61, %62, %63}, da, db, %66, 1, 1, 0, 1;\n}\n"
    : "+f"(d[0]), "+f"(d[1]), "+f"(d[2]), "+f"(d[3]), "+f"(d[4]), "+f"(d[5]), "+f"(d[6]), "+f"(d[7]), "+f"(d[8]), "+f"(d[9]), "+f"(d[10]), "+f"(d[11]), "+f"(d[12]), "+f"(d[13]), "+f"(d[14]), "+f"(d[15]), "+f"(d[16]), "+f"(d[17]), "+f"(d[18]), "+f"(d[19]), "+f"(d[20]), "+f"(d[21]), "+f"(d[22]), "+f"(d[23]), "+f"(d[24]), "+f"(d[25]), "+f"(d[26]), "+f"(d[27]), "+f"(d[28]), "+f"(d[29]), "+f"(d[30]), "+f"(d[31]), "+f"(d[32]), "+f"(d[33]), "+f"(d[34]), "+f"(d[35]), "+f"(d[36]), "+f"(d[37]), "+f"(d[38]), "+f"(d[39]), "+f"(d[40]), "+f"(d[41]), "+f"(d[42]), "+f"(d[43]), "+f"(d[44]), "+f"(d[45]), "+f"(d[46]), "+f"(d[47]), "+f"(d[48]), "+f"(d[49]), "+f"(d[50]), "+f"(d[51]), "+f"(d[52]), "+f"(d[53]), "+f"(d[54]), "+f"(d[55]), "+f"(d[56]), "+f"(d[57]), "+f"(d[58]), "+f"(d[59]), "+f"(d[60]), "+f"(d[61]), "+f"(d[62]), "+f"(d[63])
    : "r"(da), "r"(db), "n"(SD));
}
template<int SD> __device__ __forceinline__ void wg_rs_n128_tb1(float (&d)[64], uint32_t a0, uint32_t a1, uint32_t a2, uint32_t a3, uint32_t db) {
  asm volatile("{\n.reg .b64 db;\nmov.b64 db, {%68, 0x40000040};\n"
    "wgmma.mma_async.sync.aligned.m64n128k16.f32.bf16.bf16 {%0, %1, %2, %3, %4, %5, %6, %7, %8, %9, %10, %11, %12, %13, %14, %15, %16, %17, %18, %19, %20, %21, %22, %23, %24, %25, %26, %27, %28, %29, %30, %31, %32, %33, %34, %35, %36, %37, %38, %39, %40, %41, %42, %43, %44, %45, %46, %47, %48, %49, %50, %51, %52, %53, %54, %55, %56, %57, %58, %59, %60, %61, %62, %63}, {%64, %65, %66, %67}, db, %69, 1, 1, 1;\n}\n"
    : "+f"(d[0]), "+f"(d[1]), "+f"(d[2]), "+f"(d[3]), "+f"(d[4]), "+f"(d[5]), "+f"(d[6]), "+f"(d[7]), "+f"(d[8]), "+f"(d[9]), "+f"(d[10]), "+f"(d[11]), "+f"(d[12]), "+f"(d[13]), "+f"(d[14]), "+f"(d[15]), "+f"(d[16]), "+f"(d[17]), "+f"(d[18]), "+f"(d[19]), "+f"(d[20]), "+f"(d[21]), "+f"(d[22]), "+f"(d[23]), "+f"(d[24]), "+f"(d[25]), "+f"(d[26]), "+f"(d[27]), "+f"(d[28]), "+f"(d[29]), "+f"(d[30]), "+f"(d[31]), "+f"(d[32]), "+f"(d[33]), "+f"(d[34]), "+f"(d[35]), "+f"(d[36]), "+f"(d[37]), "+f"(d[38]), "+f"(d[39]), "+f"(d[40]), "+f"(d[41]), "+f"(d[42]), "+f"(d[43]), "+f"(d[44]), "+f"(d[45]), "+f"(d[46]), "+f"(d[47]), "+f"(d[48]), "+f"(d[49]), "+f"(d[50]), "+f"(d[51]), "+f"(d[52]), "+f"(d[53]), "+f"(d[54]), "+f"(d[55]), "+f"(d[56]), "+f"(d[57]), "+f"(d[58]), "+f"(d[59]), "+f"(d[60]), "+f"(d[61]), "+f"(d[62]), "+f"(d[63])
    : "r"(a0), "r"(a1), "r"(a2), "r"(a3), "r"(db), "n"(SD));
}
template<int SD> __device__ __forceinline__ void wg_ss_n64_tb1(float (&d)[32], uint32_t da, uint32_t db) {
  asm volatile("{\n.reg .b64 da, db;\nmov.b64 da, {%32, 0x40000040};\nmov.b64 db, {%33, 0x40000040};\n"
    "wgmma.mma_async.sync.aligned.m64n64k16.f32.bf16.bf16 {%0, %1, %2, %3, %4, %5, %6, %7, %8, %9, %10, %11, %12, %13, %14, %15, %16, %17, %18, %19, %20, %21, %22, %23, %24, %25, %26, %27, %28, %29, %30, %31}, da, db, %34, 1, 1, 0, 1;\n}\n"
    : "+f"(d[0]), "+f"(d[1]), "+f"(d[2]), "+f"(d[3]), "+f"(d[4]), "+f"(d[5]), "+f"(d[6]), "+f"(d[7]), "+f"(d[8]), "+f"(d[9]), "+f"(d[10]), "+f"(d[11]), "+f"(d[12]), "+f"(d[13]), "+f"(d[14]), "+f"(d[15]), "+f"(d[16]), "+f"(d[17]), "+f"(d[18]), "+f"(d[19]), "+f"(d[20]), "+f"(d[21]), "+f"(d[22]), "+f"(d[23]), "+f"(d[24]), "+f"(d[25]), "+f"(d[26]), "+f"(d[27]), "+f"(d[28]), "+f"(d[29]), "+f"(d[30]), "+f"(d[31])
    : "r"(da), "r"(db), "n"(SD));
}
template<int SD> __device__ __forceinline__ void wg_ss_n80_tb0(float (&d)[40], uint32_t da, uint32_t db) {
  asm volatile("{\n.reg .b64 da, db;\nmov.b64 da, {%40, 0x40000040};\nmov.b64 db, {%41, 0x40000040};\n"
    "wgmma.mma_async.sync.aligned.m64n80k16.f32.bf16.bf16 {%0, %1, %2, %3, %4, %5, %6, %7, %8, %9, %10, %11, %12, %13, %14, %15, %16, %17, %18, %19, %20, %21, %22, %23, %24, %25, %26, %27, %28, %29, %30, %31, %32, %33, %34, %35, %36, %37, %38, %39}, da, db, %42, 1, 1, 0, 0;\n}\n"
    : "+f"(d[0]), "+f"(d[1]), "+f"(d[2]), "+f"(d[3]), "+f"(d[4]), "+f"(d[5]), "+f"(d[6]), "+f"(d[7]), "+f"(d[8]), "+f"(d[9]), "+f"(d[10]), "+f"(d[11]), "+f"(d[12]), "+f"(d[13]), "+f"(d[14]), "+f"(d[15]), "+f"(d[16]), "+f"(d[17]), "+f"(d[18]), "+f"(d[19]), "+f"(d[20]), "+f"(d[21]), "+f"(d[22]), "+f"(d[23]), "+f"(d[24]), "+f"(d[25]), "+f"(d[26]), "+f"(d[27]), "+f"(d[28]), "+f"(d[29]), "+f"(d[30]), "+f"(d[31]), "+f"(d[32]), "+f"(d[33]), "+f"(d[34]), "+f"(d[35]), "+f"(d[36]), "+f"(d[37]), "+f"(d[38]), "+f"(d[39])
    : "r"(da), "r"(db), "n"(SD));
}
template<int SD> __device__ __forceinline__ void wg_rs_n64_tb1(float (&d)[32], uint32_t a0, uint32_t a1, uint32_t a2, uint32_t a3, uint32_t db) {
  asm volatile("{\n.reg .b64 db;\nmov.b64 db, {%36, 0x40000040};\n"
    "wgmma.mma_async.sync.aligned.m64n64k16.f32.bf16.bf16 {%0, %1, %2, %3, %4, %5, %6, %7, %8, %9, %10, %11, %12, %13, %14, %15, %16, %17, %18, %19, %20, %21, %22, %23, %24, %25, %26, %27, %28, %29, %30, %31}, {%32, %33, %34, %35}, db, %37, 1, 1, 1;\n}\n"
    : "+f"(d[0]), "+f"(d[1]), "+f"(d[2]), "+f"(d[3]), "+f"(d[4]), "+f"(d[5]), "+f"(d[6]), "+f"(d[7]), "+f"(d[8]), "+f"(d[9]), "+f"(d[10]), "+f"(d[11]), "+f"(d[12]), "+f"(d[13]), "+f"(d[14]), "+f"(d[15]), "+f"(d[16]), "+f"(d[17]), "+f"(d[18]), "+f"(d[19]), "+f"(d[20]), "+f"(d[21]), "+f"(d[22]), "+f"(d[23]), "+f"(d[24]), "+f"(d[25]), "+f"(d[26]), "+f"(d[27]), "+f"(d[28]), "+f"(d[29]), "+f"(d[30]), "+f"(d[31])
    : "r"(a0), "r"(a1), "r"(a2), "r"(a3), "r"(db), "n"(SD));
}


constexpr int RING = 5;
constexpr uint32_t STAGE = 32768;
constexpr uint32_t OFF_X = 32768, OFF_W = 65536, OFF_MISC = OFF_W + RING * STAGE;
constexpr int SMEM_BYTES = OFF_MISC + 256 + 1024 + 1024;

struct Ctx {
  uint32_t sA, sX, sW, full, empty, stats;
  uint32_t frag;
  uint32_t rsw;
  uint32_t hi;
  int wg, tid, lane;
  uint32_t dry;
};
__device__ __forceinline__ uint32_t stage_wait(const Ctx& c, int n) {
  const int q = n / RING, s = n - q * RING;
  mbar_wait(c.full + 8 * s, (q | c.dry) & 1);
  return dlo(c.sW + s * STAGE, 0);
}
__device__ __forceinline__ void stage_release(const Ctx& c, int n) {
  const int s = n % RING;
  if (c.tid == 0) mbar_arrive(c.empty + 8 * s);
}
__device__ __forceinline__ void turn_begin(const Ctx& c) { bar_sync(5 + c.wg, 256); }
__device__ __forceinline__ void turn_end(const Ctx& c) { bar_arrive(5 + (c.wg ^ 1), 256); }
template<int FIRST, int LAST> __device__ __forceinline__ void piece_ss(const Ctx& c, float (&acc)[64], uint32_t dA, uint32_t dB) {
  dB += (16384 >> 4) << 16;
  wg_ss_n128_tb1<FIRST ? 0 : 1>(acc, dA, dB);
#pragma unroll
  for (int kk = 1; kk < 8; kk++) {
    wg_ss_n128_tb1<1>(acc, dA + (kk >> 2) * 512 + (kk & 3) * 2, dB + kk * 128);
  }
  if (LAST) turn_end(c);
}
__device__ __forceinline__ void ff_g1(const Ctx& c, float (&h)[32], uint32_t dA, uint32_t dB) {
  wg_ss_n64_tb1<0>(h, dA, dB);
#pragma unroll
  for (int kk = 1; kk < 16; kk++) {
    wg_ss_n64_tb1<1>(h, dA + (kk >> 2) * 512 + (kk & 3) * 2, dB + kk * 128);
  }
}
__device__ __forceinline__ void ff_g2(float (&acc)[64], const uint32_t (&P)[16], uint32_t dB, int half) {
  dB += ((8192 >> 4) << 16) + half * 1024;
#pragma unroll
  for (int kk = 0; kk < 4; kk++) wg_rs_n128_tb1<1>(acc, P[4 * kk], P[4 * kk + 1], P[4 * kk + 2], P[4 * kk + 3], dB + kk * 128);
}
struct NoHook { __device__ __forceinline__ void operator()() const {} };
template<int FIRST, class Hook = NoHook> __device__ __forceinline__ void gemm256(const Ctx& c, float (&acc)[64], int n, Hook hook = Hook()) {
  const uint32_t dA = dlo(c.sA, 16);
  uint32_t b = stage_wait(c, n);
  turn_begin(c);
  wg_fence(); piece_ss<FIRST, 0>(c, acc, dA, b); wg_commit();
  b = stage_wait(c, n + 1);
  wg_fence(); piece_ss<0, 1>(c, acc, dA + 1024, b); wg_commit();
  hook();
  wg_wait<1>(); stage_release(c, n);
  wg_wait<0>(); stage_release(c, n + 1);
}
__device__ __forceinline__ uint32_t frag_addr(const Ctx& c, uint32_t tile, int j) {
  return tile + (2 * c.wg + (j >> 2)) * 8192 + c.frag + ((((j & 3) * 2 + c.hi) ^ c.rsw) << 4);
}
__device__ __forceinline__ void load_half(const Ctx& c, uint32_t tile, float (&v)[64]) {
#pragma unroll
  for (int j = 0; j < 8; j++) {
    uint32_t r0, r1, r2, r3;
    ldsm_x4(frag_addr(c, tile, j), r0, r1, r2, r3);
    v[8 * j] = bf_lo(r0); v[8 * j + 1] = bf_hi(r0); v[8 * j + 2] = bf_lo(r1); v[8 * j + 3] = bf_hi(r1);
    v[8 * j + 4] = bf_lo(r2); v[8 * j + 5] = bf_hi(r2); v[8 * j + 6] = bf_lo(r3); v[8 * j + 7] = bf_hi(r3);
  }
}
__device__ __forceinline__ void store_half(const Ctx& c, uint32_t tile, const float (&v)[64], float a0, float b0, float a1, float b1) {
#pragma unroll
  for (int j = 0; j < 8; j++)
    stsm_x4(frag_addr(c, tile, j),
            pack_bf16(fmaf(v[8 * j], a0, b0), fmaf(v[8 * j + 1], a0, b0)), pack_bf16(fmaf(v[8 * j + 2], a1, b1), fmaf(v[8 * j + 3], a1, b1)),
            pack_bf16(fmaf(v[8 * j + 4], a0, b0), fmaf(v[8 * j + 5], a0, b0)), pack_bf16(fmaf(v[8 * j + 6], a1, b1), fmaf(v[8 * j + 7], a1, b1)));
}
__device__ __forceinline__ void store_half_raw(const Ctx& c, uint32_t tile, const float (&v)[64]) {
#pragma unroll
  for (int j = 0; j < 8; j++)
    stsm_x4(frag_addr(c, tile, j), pack_bf16(v[8 * j], v[8 * j + 1]), pack_bf16(v[8 * j + 2], v[8 * j + 3]),
            pack_bf16(v[8 * j + 4], v[8 * j + 5]), pack_bf16(v[8 * j + 6], v[8 * j + 7]));
}
__device__ __forceinline__ void ln_stats(const Ctx& c, const float (&v)[64], float scale, float& a0, float& b0, float& a1, float& b1) {
  float s0 = 0.f, s1 = 0.f, q0 = 0.f, q1 = 0.f, s2 = 0.f, s3 = 0.f, q2 = 0.f, q3 = 0.f;
#pragma unroll
  for (int i = 0; i < 16; i++) {
    s0 += v[4 * i]; q0 = fmaf(v[4 * i], v[4 * i], q0);
    s2 += v[4 * i + 1]; q2 = fmaf(v[4 * i + 1], v[4 * i + 1], q2);
    s1 += v[4 * i + 2]; q1 = fmaf(v[4 * i + 2], v[4 * i + 2], q1);
    s3 += v[4 * i + 3]; q3 = fmaf(v[4 * i + 3], v[4 * i + 3], q3);
  }
  s0 += s2; q0 += q2; s1 += s3; q1 += q3;
  s0 += __shfl_xor_sync(0xffffffff, s0, 1); q0 += __shfl_xor_sync(0xffffffff, q0, 1);
  s1 += __shfl_xor_sync(0xffffffff, s1, 1); q1 += __shfl_xor_sync(0xffffffff, q1, 1);
  s0 += __shfl_xor_sync(0xffffffff, s0, 2); q0 += __shfl_xor_sync(0xffffffff, q0, 2);
  s1 += __shfl_xor_sync(0xffffffff, s1, 2); q1 += __shfl_xor_sync(0xffffffff, q1, 2);
  const uint32_t row = (c.tid >> 5) * 16 + (c.lane >> 2);
  if ((c.lane & 3) == 0) {
    sts64f(c.stats + c.wg * 512 + row * 8, s0, q0);
    sts64f(c.stats + c.wg * 512 + (row + 8) * 8, s1, q1);
  }
  bar_sync(1, 256);
  const float2 o0 = lds64f(c.stats + (c.wg ^ 1) * 512 + row * 8), o1 = lds64f(c.stats + (c.wg ^ 1) * 512 + (row + 8) * 8);
  const float m0 = (s0 + o0.x) * (1.f / 256.f), m1 = (s1 + o1.x) * (1.f / 256.f);
  const float var0 = fmaxf(fmaf(-m0, m0, (q0 + o0.y) * (1.f / 256.f)), 0.f), var1 = fmaxf(fmaf(-m1, m1, (q1 + o1.y) * (1.f / 256.f)), 0.f);
  a0 = rsqrtf(var0 + 1e-5f) * scale; a1 = rsqrtf(var1 + 1e-5f) * scale;
  b0 = -m0 * a0; b1 = -m1 * a1;
}
__device__ __forceinline__ float silu_half(float h) { return fmaf(h, tanh_fast(h), h); }
__device__ __forceinline__ float silu_quarter(float h) { const float q = 0.5f * h; return fmaf(q, tanh_fast(h), q); }
__device__ __forceinline__ void silu_pack(const float (&acc)[32], uint32_t (&P)[16]) {
#pragma unroll
  for (int i = 0; i < 16; i++) P[i] = pack_bf16(silu_quarter(acc[2 * i]), silu_quarter(acc[2 * i + 1]));
}
__device__ __forceinline__ void ff_block(const Ctx& c, int n0, float (&own)[64]) {
  float oth[64], h[32];
  uint32_t P[16];
#pragma unroll
  for (int i = 0; i < 64; i++) oth[i] = 0.f;
  const uint32_t dA = dlo(c.sA, 16);
  {
    const uint32_t b = stage_wait(c, n0 + c.wg);
    turn_begin(c);
    wg_fence(); ff_g1(c, h, dA, b); wg_commit();
    turn_end(c);
    wg_wait<0>(); stage_release(c, n0 + c.wg);
    silu_pack(h, P);
  }
#pragma unroll 1
  for (int it = c.dry ? 7 : 1; it < 8; it++) {
    const int n = n0 + 4 * it - 2 + 2 * c.wg;
    uint32_t b = stage_wait(c, n);
    turn_begin(c);
    wg_fence(); ff_g2(own, P, b, c.wg); ff_g2(oth, P, b, c.wg ^ 1); wg_commit();
    b = stage_wait(c, n + 1);
    wg_fence(); ff_g1(c, h, dA, b); wg_commit();
    turn_end(c);
    wg_wait<1>(); stage_release(c, n);
    wg_wait<0>(); stage_release(c, n + 1);
    silu_pack(h, P);
  }
  if (c.wg == 0) bar_arrive(2, 256);
  {
    const int n = n0 + 30 + c.wg;
    const uint32_t b = stage_wait(c, n);
    turn_begin(c);
    wg_fence(); ff_g2(oth, P, b, c.wg ^ 1); wg_commit();
    ff_g2(own, P, b, c.wg); wg_commit();
    turn_end(c);
    wg_wait<1>();
    if (c.wg == 1) bar_sync(2, 256);
    const uint32_t e = (c.wg == 0 ? c.sX : c.sA) + c.tid * 16;
#pragma unroll
    for (int i = 0; i < 16; i++)
      sts128(e + i * 2048, make_uint4(__float_as_uint(oth[4 * i]), __float_as_uint(oth[4 * i + 1]), __float_as_uint(oth[4 * i + 2]), __float_as_uint(oth[4 * i + 3])));
    wg_wait<0>(); stage_release(c, n);
  }
  bar_sync(1, 256);
  const uint32_t e = (c.wg == 0 ? c.sA : c.sX) + c.tid * 16;
#pragma unroll
  for (int i = 0; i < 16; i++) {
    const uint4 u = lds128(e + i * 2048);
    own[4 * i] += __uint_as_float(u.x); own[4 * i + 1] += __uint_as_float(u.y);
    own[4 * i + 2] += __uint_as_float(u.z); own[4 * i + 3] += __uint_as_float(u.w);
  }
}
struct Maps { CUtensorMap X, W1a, W1b, Wqkv, QKVst, Q, KV, Wo, Pw1, Pw2, W2a, W2b, Out; uint16_t stage[92]; };
constexpr int NA = 44;
constexpr int NC = 45;
#define STAGE_TABLE {0x1, 0x11, 0x2, 0x21, 0x102, 0x31, 0x202, 0x41, 0x302, 0x51, 0x402, 0x61, 0x502, 0x71, 0x602, 0x81, 0x702, 0x91, 0x802, 0xa1, 0x902, 0xb1, 0xa02, 0xc1, 0xb02, 0xd1, 0xc02, 0xe1, 0xd02, 0xf1, 0xe02, 0xf02, 0x3, 0x203, 0x23, 0x223, 0x43, 0x243, 0x63, 0x263, 0x83, 0x283, 0xa3, 0x2a3, 0x7, 0x207, 0x27, 0x227, 0x8, 0x208, 0x2008, 0x2208, 0x1008, 0x1208, 0x3008, 0x3208, 0x9, 0x29, 0x209, 0x229, 0xa, 0x1a, 0xb, 0x2a, 0x10b, 0x3a, 0x20b, 0x4a, 0x30b, 0x5a, 0x40b, 0x6a, 0x50b, 0x7a, 0x60b, 0x8a, 0x70b, 0x9a, 0x80b, 0xaa, 0x90b, 0xba, 0xa0b, 0xca, 0xb0b, 0xda, 0xc0b, 0xea, 0xd0b, 0xfa, 0xe0b, 0xf0b}
__device__ __forceinline__ void load_stage(uint32_t dst, uint32_t bar, const Maps& tm, int n) {
  const uint32_t e = tm.stage[n - (n > NA)];
  mbar_expect_tx(bar, STAGE);
  tma_load_3d(dst, &tm.X + (e & 15), bar, (e >> 12) * 64, ((e >> 8) & 15) * 64, (e >> 4) & 15);
}
__device__ __forceinline__ void produce(uint32_t sW, uint32_t full, const Maps& tm, int n0, int n1) {
  uint32_t s = n0 % RING, ph = ((n0 / RING) & 1) ^ 1;
#pragma unroll 1
  for (int n = n0; n < n1; n++) {
    mbar_wait(full + 8 * RING + 8 * s, ph);
    load_stage(sW + s * STAGE, full + 8 * s, tm, n);
    if (++s == RING) { s = 0; ph ^= 1; }
  }
}
__device__ __forceinline__ Ctx make_ctx(uint32_t base, uint32_t dry) {
  Ctx c; c.dry = dry;
  c.sA = base; c.sX = base + OFF_X; c.sW = base + OFF_W;
  c.full = base + OFF_MISC; c.empty = c.full + 8 * RING; c.stats = base + OFF_MISC + 256;
  c.wg = __shfl_sync(0xffffffff, (int)(threadIdx.x >> 7), 0);
  c.tid = threadIdx.x & 127; c.lane = threadIdx.x & 31;
  const uint32_t r = (c.tid >> 5) * 16 + (c.lane & 7) + ((c.lane >> 3) & 1) * 8;
  c.frag = r * 128; c.rsw = r & 7; c.hi = c.lane >> 4;
  return c;
}

constexpr int NSTG = 4;
constexpr int KVB = 160 * 128;
constexpr int NKV = T_ / 160;
static_assert(NSTG * 2 * KVB == RING * STAGE, "the K/V ring reuses the weight ring");

struct AttCtx { uint32_t sKV, full, empty, dry, wfull; const Maps* tm; int h, b, wg; };
__device__ __forceinline__ int kv_slot(int i) { return (i + 3) & 3; }
__device__ __forceinline__ void att_load(const AttCtx& a, int i, int v) {
  const int s = i & 3;
  mbar_expect_tx(a.full + 8 * (s + v * NSTG), KVB);
  tma_load_3d(a.sKV + kv_slot(i) * 2 * KVB + v * KVB, &a.tm->KV, a.full + 8 * (s + v * NSTG), 256 + v * 256 + a.h * 64, i * 160, a.b);
}
__device__ __forceinline__ void att_load_stage(const AttCtx& a, int i) { att_load(a, i, 0); att_load(a, i, 1); }
__device__ __forceinline__ void att_init_bars(const AttCtx& a) {
  for (int i = 0; i < NSTG; i++) { mbar_init(a.full + 8 * i, 1); mbar_init(a.full + 8 * (NSTG + i), 1); mbar_init(a.empty + 8 * i, 4); }
}
__device__ __forceinline__ void att_qk(float (&S)[40], uint32_t dQ, uint32_t kd) {
  wg_ss_n80_tb0<0>(S, dQ, kd);
#pragma unroll
  for (int kk = 1; kk < 4; kk++) wg_ss_n80_tb0<1>(S, dQ + kk * 2, kd + kk * 2);
}
__device__ __forceinline__ void att_pv(float (&O)[32], const uint32_t (&P)[20], uint32_t vd) {
#pragma unroll
  for (int kk = 0; kk < 5; kk++) wg_rs_n64_tb1<1>(O, P[kk * 4], P[kk * 4 + 1], P[kk * 4 + 2], P[kk * 4 + 3], vd + kk * 128);
}
template<bool SAFE>
__device__ __forceinline__ void att_softmax(const float (&S)[40], uint32_t (&P)[20], float (&O)[32], float& m0, float& m1, float& l0, float& l1) {
  if (SAFE) {
    float x0 = fmaxf(S[0], S[1]), x1 = fmaxf(S[2], S[3]);
#pragma unroll
    for (int i = 1; i < 10; i++) { x0 = fmaxf(x0, fmaxf(S[4 * i], S[4 * i + 1])); x1 = fmaxf(x1, fmaxf(S[4 * i + 2], S[4 * i + 3])); }
    x0 = fmaxf(x0, __shfl_xor_sync(0xffffffff, x0, 1)); x1 = fmaxf(x1, __shfl_xor_sync(0xffffffff, x1, 1));
    x0 = fmaxf(x0, __shfl_xor_sync(0xffffffff, x0, 2)); x1 = fmaxf(x1, __shfl_xor_sync(0xffffffff, x1, 2));
    const float n0 = fmaxf(m0, x0), n1 = fmaxf(m1, x1);
    const float f0 = ex2(m0 - n0), f1 = ex2(m1 - n1);
    m0 = n0; m1 = n1; l0 *= f0; l1 *= f1;
#pragma unroll
    for (int i = 0; i < 8; i++) { O[4 * i] *= f0; O[4 * i + 1] *= f0; O[4 * i + 2] *= f1; O[4 * i + 3] *= f1; }
  }
#pragma unroll
  for (int i = 0; i < 10; i++) {
    float p0, p1, p2, p3;
    if (SAFE) { p0 = ex2(S[4 * i] - m0); p1 = ex2(S[4 * i + 1] - m0); p2 = ex2(S[4 * i + 2] - m1); p3 = ex2(S[4 * i + 3] - m1); }
    else { p0 = ex2(S[4 * i]); p1 = ex2(S[4 * i + 1]); p2 = ex2(S[4 * i + 2]); p3 = ex2(S[4 * i + 3]); }
    l0 += p0 + p1; l1 += p2 + p3;
    P[2 * i] = pack_bf16(p0, p1); P[2 * i + 1] = pack_bf16(p2, p3);
  }
}
template<bool SAFE>
__device__ __forceinline__ void att_refill(const AttCtx& a, int it) {
  if ((threadIdx.x & 127) == 0) {
    mbar_arrive(a.empty + 8 * (it & 3));
    if (a.wg == (it & 3) && it >= 1 && !a.dry) {
      const bool kv = it - 1 + NSTG < NKV;
      if (kv || (!SAFE && a.wfull)) {
        mbar_wait(a.empty + 8 * ((it - 1) & 3), ((it - 1) >> 2) & 1);
        if (kv) att_load_stage(a, it - 1 + NSTG);
        else load_stage(a.sKV + (it - 22) * STAGE, a.wfull + 8 * (it - 22), *a.tm, NC + it - 22);
      }
    }
  }
  __syncwarp();
}
constexpr uint32_t KV_STG = 2 * KVB / 16, KV_VOFF = KVB / 16, KV_HALF = 80 * 128 / 16;
template<bool SAFE>
__device__ __forceinline__ void att_pass(const AttCtx& a, bool idle, uint32_t dQ, float (&O)[32], float& l0, float& l1) {
  float S[40];
  uint32_t P[20];
  float m0 = -INFINITY, m1 = -INFINITY;
  l0 = 0.f; l1 = 0.f;
#pragma unroll
  for (int i = 0; i < 32; i++) O[i] = 0.f;
  const uint32_t dKV = dlo(a.sKV, 16);
  if (SAFE) {
#pragma unroll 1
    for (int j = 0; j < 2 * NKV; j++) {
      const int it = j >> 1, s = it & 3;
      const uint32_t kb = dKV + kv_slot(it) * KV_STG + (j & 1) * KV_HALF;
      mbar_wait(a.full + 8 * s, (it >> 2) & 1);
      wg_fence(); att_qk(S, dQ, kb); wg_commit(); wg_wait<0>();
      att_softmax<true>(S, P, O, m0, m1, l0, l1);
      mbar_wait(a.full + 8 * (NSTG + s), (it >> 2) & 1);
      wg_fence(); att_pv(O, P, kb + KV_VOFF); wg_commit(); wg_wait<0>();
      if (j & 1) att_refill<true>(a, it);
    }
  } else if (idle) {
    l0 = 1.f; l1 = 1.f;
#pragma unroll 1
    for (int it = 0; it < NKV - 1; it++) { mbar_wait(a.full + 8 * (it & 3), (it >> 2) & 1); att_refill<false>(a, it); }
  } else {
    mbar_wait(a.full, a.dry);
    wg_fence(); att_qk(S, dQ, dKV + 3 * KV_STG); wg_commit(); wg_wait<0>();
    att_softmax<false>(S, P, O, m0, m1, l0, l1);
    mbar_wait(a.full + 8 * NSTG, a.dry);
    wg_fence(); att_pv(O, P, dKV + 3 * KV_STG + KV_VOFF); att_qk(S, dQ, dKV + 3 * KV_STG + KV_HALF); wg_commit(); wg_wait<0>();
#pragma unroll 1
    for (int it = a.dry ? NKV - 2 : 0; it < NKV - 1; it++) {
      const int sn = (it + 1) & 3;
      const uint32_t kb = dKV + kv_slot(it) * KV_STG, kn = dKV + kv_slot(it + 1) * KV_STG, par = (((it + 1) >> 2) | a.dry) & 1;
      att_softmax<false>(S, P, O, m0, m1, l0, l1);
      mbar_wait(a.full + 8 * sn, par);
      wg_fence(); att_pv(O, P, kb + KV_VOFF + KV_HALF); att_qk(S, dQ, kn); wg_commit(); wg_wait<0>();
      att_refill<false>(a, it);
      att_softmax<false>(S, P, O, m0, m1, l0, l1);
      mbar_wait(a.full + 8 * (NSTG + sn), par);
      wg_fence(); att_pv(O, P, kn + KV_VOFF); att_qk(S, dQ, kn + KV_HALF); wg_commit(); wg_wait<0>();
    }
    att_softmax<false>(S, P, O, m0, m1, l0, l1);
    wg_fence(); att_pv(O, P, dKV + 3 * KV_STG + KV_VOFF + KV_HALF); wg_commit(); wg_wait<0>();
  }
  l0 += __shfl_xor_sync(0xffffffff, l0, 1); l1 += __shfl_xor_sync(0xffffffff, l1, 1);
  l0 += __shfl_xor_sync(0xffffffff, l0, 2); l1 += __shfl_xor_sync(0xffffffff, l1, 2);
}

struct Wptrs { const void* p[8]; uint32_t bytes[8]; };

constexpr uint32_t B_FULL = 0, B_EMPTY = 8 * RING, B_X = 16 * RING, B_ADONE = B_X + 8, B_Q = B_X + 16, B_EP = B_X + 24, B_ATT = B_X + 32;

__global__ void __launch_bounds__(512, 1) conformer_kernel(const __grid_constant__ Maps tm, const __grid_constant__ Wptrs wp, const uint4* __restrict__ dw) {
  extern __shared__ uint8_t smem_raw[];
  const uint32_t base = (smem_u32(smem_raw) + 1023) & ~1023u, misc = base + OFF_MISC;
  const uint32_t bq = blockIdx.x / 19, br = blockIdx.x - bq * 19;
  const uint32_t bid = br == 18 ? ((bq & 1) ? 125 : 128) + (bq >> 1) : blockIdx.x - bq;
  const uint32_t dry = bid >= 128;
  const int tile = dry ? 0 : bid;
  const bool has_tile = dry ? bid == 128 : tile < NTILE;
  const int wg = __shfl_sync(0xffffffff, (int)(threadIdx.x >> 7), 0);
  AttCtx a;
  a.sKV = base + OFF_W; a.full = misc + B_ATT; a.empty = a.full + 16 * NSTG; a.tm = &tm;
  a.h = (bid >> 4) & 3; a.b = (bid >> 6) & 1; a.wg = wg; a.dry = dry; a.wfull = has_tile ? misc + B_FULL : 0;
  const int qt = bid & 15;

  if (threadIdx.x == 256) {
    mbar_init(misc + B_X, 1);
    for (int i = 0; i < RING; i++) { mbar_init(misc + B_FULL + 8 * i, 1); mbar_init(misc + B_EMPTY + 8 * i, 1); }
    asm volatile("fence.mbarrier_init.release.cluster;" ::: "memory");
    if (has_tile && !dry) {
      mbar_expect_tx(misc + B_X, 32768);
      tma_load_3d(base + OFF_X, &tm.X, misc + B_X, 0, tile * 64, 0);
    }
  } else if (threadIdx.x == 288) {
    mbar_init(misc + B_ADONE, 2);
    mbar_init(misc + B_Q, 1);
    mbar_init(misc + B_EP, 1);
    att_init_bars(a);
    asm volatile("fence.mbarrier_init.release.cluster;" ::: "memory");
  } else if (threadIdx.x >= 320 && threadIdx.x < 333) {
    prefetch_tmap(&tm.X + (threadIdx.x - 320));
  }
  __syncthreads();
  if ((threadIdx.x & 31) == 0 && threadIdx.x >= 256 && threadIdx.x < 256 + 32 * RING && has_tile && !dry) {
    const int i = (threadIdx.x - 256) >> 5;
    load_stage(base + OFF_W + i * STAGE, misc + B_FULL + 8 * i, tm, i);
  }
  __syncwarp();
  auto get_epoch = [&]() {
    uint32_t e;
    mbar_wait(misc + B_EP, 0);
    asm volatile("ld.shared.u32 %0, [%1];" : "=r"(e) : "r"(misc + 248) : "memory");
    return e;
  };

  if (wg < 2) {
    asm volatile("setmaxnreg.inc.sync.aligned.u32 232;");
    if (has_tile) {
      const Ctx c = make_ctx(base, dry);
      if (c.wg == 1) turn_end(c);
      float own[64];
      float a0, b0, a1, b1;
#pragma unroll 1
      for (int rep = 0; rep < 2; rep++) {
        if (rep) mbar_wait(misc + B_X, dry);
        load_half(c, c.sX, own);
        ln_stats(c, own, 0.5f, a0, b0, a1, b1);
        store_half(c, c.sA, own, a0, b0, a1, b1);
        fence_async_smem();
        bar_sync(1, 256);
      }
      ff_block(c, 0, own);
      ln_stats(c, own, 1.f, a0, b0, a1, b1);
      store_half(c, c.sA, own, a0, b0, a1, b1);
      fence_async_smem();
      bar_sync(1, 256);
#pragma unroll 1
      for (int cc = dry ? 2 : 0; cc < 3; cc++) {
        float acc[64];
        const int j = 2 * cc + c.wg;
        gemm256<1>(c, acc, 32 + 2 * j, [&]() {
          if (c.tid == 0 && !dry) {
            if (cc == 2) {
              bulk_wait_all();
              if (tile <= 62) cnt_signal(g_cnt1);
              if (tile >= 62) cnt_signal(g_cnt1 + 64);
            } else bulk_wait_read();
          }
          bar_sync(3 + c.wg, 128);
        });
        if (cc == 2 && !dry) { bar_arrive(9, 288); if (c.tid == 0) mbar_arrive(misc + B_ADONE); }
        if (cc == 0) {
#pragma unroll
          for (int i = 0; i < 64; i++) acc[i] *= 0.125f * 1.4426950408889634f;
        }
        store_half_raw(c, c.sX, acc);
        fence_async_smem();
        bar_sync(3 + c.wg, 128);
        if (c.tid == 0 && !dry) { tma_store_3d(&tm.QKVst, c.sX + c.wg * 16384, 0, tile * 64, 2 * j); bulk_commit(); }
      }
      if (c.tid == 0) bulk_wait_read();
      bar_sync(3 + c.wg, 128);
      store_half_raw(c, c.sX, own);
    }
    else bar_sync(3 + wg, 128);
    asm volatile("setmaxnreg.dec.sync.aligned.u32 128;");
    bar_arrive(7, 384); bar_arrive(8, 384);
    if (has_tile && !dry && (threadIdx.x & 127) == 0) {
      bulk_wait_all();
      if (tile <= 62) cnt_signal(g_cnt1 + 32);
      if (tile >= 62) cnt_signal(g_cnt1 + 96);
    }
    __syncwarp();
  } else {
    asm volatile("setmaxnreg.dec.sync.aligned.u32 24;");
    const uint32_t full = misc + B_FULL;
    if (threadIdx.x == 320) {
      const uint32_t e = atomicAdd(&g_start, 1) / NCTA;
      asm volatile("st.shared.u32 [%0], %1;" :: "r"(misc + 248), "r"(e + 1) : "memory");
      mbar_arrive(misc + B_EP);
    }
    if (dry) {
    } else if (threadIdx.x == 256) {
      if (has_tile) {
        produce(base + OFF_W, full, tm, RING, NA);
        mbar_wait(full + 8 * RING + 8 * 4, 1);
        mbar_arrive(full + 8 * 4); mbar_arrive(full + 8 * RING + 8 * 4);
        mbar_wait(misc + B_ADONE, 0);
      }
      cnt_wait(g_cnt1 + a.b * 64, 126 * get_epoch());
      mbar_expect_tx(misc + B_Q, 32768);
      tma_load_3d(base, &tm.Q, misc + B_Q, a.h * 64, qt * 256, a.b);
      att_load(a, 0, 0);
      mbar_wait(misc + B_Q, 0);
#pragma unroll 1
      for (int i = 1; i < NSTG; i++) att_load(a, i, 0);
    } else if ((threadIdx.x >> 5) == 12) {
      if (has_tile) bar_sync(9, 288);
      if (threadIdx.x == 384) {
        cnt_wait(g_cnt1 + a.b * 64 + 32, 126 * get_epoch());
        att_load(a, 0, 1);
        mbar_wait(a.full + 8 * NSTG, 0);
#pragma unroll 1
        for (int i = 1; i < NSTG; i++) att_load(a, i, 1);
      }
    } else if (has_tile && threadIdx.x >= 288 && threadIdx.x < 296) {
      const int w = threadIdx.x - 288;
      mbar_wait(misc + B_X, 0);
      const uint32_t bytes = wp.bytes[w], per = ((bytes / NTILE) + 127) & ~127u, off = per * tile;
      if (off < bytes) l2_prefetch((const uint8_t*)wp.p[w] + off, min(per, bytes - off));
    } else if (has_tile && threadIdx.x >= 416) {
      mbar_wait(full, 0);
      const int t = threadIdx.x - 416;
#pragma unroll 2
      for (int i = t; i < 2048; i += 96) g_att[tile * 2048 + i] = make_uint4(~0u, ~0u, ~0u, ~0u);
      g_halo[tile * 128 + t] = make_uint4(~0u, ~0u, ~0u, ~0u);
      if (t < 32) g_halo[tile * 128 + 96 + t] = make_uint4(~0u, ~0u, ~0u, ~0u);
    }
    __syncwarp();
    bar_sync(5 + wg, 384);
    asm volatile("setmaxnreg.inc.sync.aligned.u32 128;");
  }

  if (bid == 128) return;
  if (bid != 130) {
    const int lane = threadIdx.x & 31, wq = (threadIdx.x >> 5) & 3;
    const uint32_t dQ = dlo(base + wg * 8192, 16);
    float O[32], l0, l1;
    mbar_wait(misc + B_Q, dry);
    att_pass<false>(a, qt * 256 + wg * 64 >= T_, dQ, O, l0, l1);
    float z = 0.f;
#pragma unroll
    for (int i = 0; i < 32; i++) z = fmaf(O[i], 0.f, z);
    const bool ok = (l0 >= 0x1p-40f) && (l0 <= 0x1p80f) && (l1 >= 0x1p-40f) && (l1 <= 0x1p80f) && (z == 0.f);
    const bool warp_bad = !__all_sync(0xffffffff, ok) && !dry;
    auto store_out = [&]() {
      const float i0 = 1.f / l0, i1 = 1.f / l1;
      const int row = qt * 256 + wg * 64 + wq * 16;
      if (row < T_ && !dry) {
        const int slab = (a.b * T_ + row) / 16;
        uint4* op = g_att + (slab * 16 + a.h * 4) * 32 + lane;
#pragma unroll
        for (int j = 0; j < 4; j++)
          asm volatile("st.relaxed.gpu.global.v4.u32 [%0], {%1,%2,%3,%4};" :: "l"(op + j * 32),
                       "r"(pack_bf16(O[8 * j] * i0, O[8 * j + 1] * i0)), "r"(pack_bf16(O[8 * j + 2] * i1, O[8 * j + 3] * i1)),
                       "r"(pack_bf16(O[8 * j + 4] * i0, O[8 * j + 5] * i0)), "r"(pack_bf16(O[8 * j + 6] * i1, O[8 * j + 7] * i1)) : "memory");
      }
    };
    if (!warp_bad) store_out();
    if (__syncthreads_or(warp_bad)) {
      if (threadIdx.x == 0) {
        if (has_tile) { mbar_wait(misc + B_FULL, 1); mbar_wait(misc + B_FULL + 8, 1); }
        for (int i = 0; i < 3 * NSTG; i++) mbar_inval(a.full + 8 * i);
        att_init_bars(a);
        asm volatile("fence.mbarrier_init.release.cluster;" ::: "memory");
        fence_async_smem();
#pragma unroll 1
        for (int i = 0; i < NSTG; i++) att_load_stage(a, i);
      }
      __syncthreads();
      att_pass<true>(a, false, dQ, O, l0, l1);
      if (warp_bad) store_out();
      __syncthreads();
      if (has_tile) {
        if (threadIdx.x == 32) {
          load_stage(base + OFF_W, misc + B_X, tm, NC);
          load_stage(base + OFF_W + STAGE, misc + B_Q, tm, NC + 1);
        }
        mbar_wait(misc + B_X, 1); mbar_wait(misc + B_Q, 1);
      }
    }
  } else {
    __syncthreads();
  }
  if (dry ? bid != 130 : !has_tile) return;

  if (wg < 2) {
    asm volatile("setmaxnreg.inc.sync.aligned.u32 232;");
    const Ctx c = make_ctx(base, dry);
    if (dry && c.wg == 1) turn_end(c);
    float own[64];
    float a0, b0, a1, b1;
    {
      uint4 af[16];
      const int slab = tile * 4 + (c.tid >> 5);
      const uint4* ap = (dry ? (const uint4*)wp.p[3] : g_att + slab * 512) + c.lane;
      if (c.wg == 1) __nanosleep(300);
#pragma unroll
      for (int i = 0; i < 16; i++)
        asm volatile("ld.global.ca.v4.u32 {%0,%1,%2,%3}, [%4];" : "=r"(af[i].x), "=r"(af[i].y), "=r"(af[i].z), "=r"(af[i].w) : "l"(ap + i * 32) : "memory");
      load_half(c, c.sX, own);
      uint32_t miss = dry ? 0 : 15;
      for (uint32_t n = 0; n < (1u << 18); n++) {
#pragma unroll
        for (int hh = 0; hh < 4; hh++)
          if ((miss >> hh) & 1) {
            uint32_t mx = 0;
#pragma unroll
            for (int i = 4 * hh; i < 4 * hh + 4; i++) mx = max(mx, max(max(af[i].x, af[i].y), max(af[i].z, af[i].w)));
            if (__any_sync(0xffffffff, mx == ~0u)) {
#pragma unroll
              for (int i = 4 * hh; i < 4 * hh + 4; i++)
                asm volatile("ld.relaxed.gpu.global.v4.u32 {%0,%1,%2,%3}, [%4];" : "=r"(af[i].x), "=r"(af[i].y), "=r"(af[i].z), "=r"(af[i].w) : "l"(ap + i * 32) : "memory");
            } else miss &= ~(1u << hh);
          }
        if (!miss) break;
      }
      const int n = NC + 2 * c.wg;
      uint32_t b = stage_wait(c, n) + ((16384 >> 4) << 16);
      turn_begin(c);
      wg_fence();
#pragma unroll
      for (int kk = 0; kk < 8; kk++) wg_rs_n128_tb1<1>(own, af[kk].x, af[kk].y, af[kk].z, af[kk].w, b + kk * 128);
      wg_commit();
      b = stage_wait(c, n + 1) + ((16384 >> 4) << 16);
      wg_fence();
#pragma unroll
      for (int kk = 0; kk < 8; kk++) wg_rs_n128_tb1<1>(own, af[8 + kk].x, af[8 + kk].y, af[8 + kk].z, af[8 + kk].w, b + kk * 128);
      wg_commit();
      turn_end(c);
      wg_wait<1>(); stage_release(c, n);
      wg_wait<0>(); stage_release(c, n + 1);
    }
    ln_stats(c, own, 0.5f, a0, b0, a1, b1);
    store_half(c, c.sA, own, a0, b0, a1, b1);
    fence_async_smem();
    bar_sync(1, 256);
    uint4 dwr[5];
#pragma unroll
    for (int i = 0; i < 5; i++) dwr[i] = __ldg(dw + i * 32 + c.wg * 16 + (c.lane & 15));
    const bool top = c.tid < 8, pub = (top || c.tid >= 120) && !dry;
    uint32_t* halo_out = (uint32_t*)g_halo + (tile * 4 + (top ? (c.tid >> 2) : ((c.tid >> 2) - 28))) * 128 + c.wg * 64 + (c.lane & 3);
#pragma unroll 1
    for (int q = dry; q < 2; q++) {
      float ab[64];
      gemm256<1>(c, ab, NC + 4 + 4 * q + 2 * c.wg);
#pragma unroll
      for (int j = 0; j < 4; j++) {
        float g[8];
#pragma unroll
        for (int i = 0; i < 8; i++) g[i] = fmaf(ab[8 * j + i], tanh_fast(ab[32 + 8 * j + i]), ab[8 * j + i]);
        const uint32_t p0 = pack_bf16(g[0], g[1]), p1 = pack_bf16(g[2], g[3]), p2 = pack_bf16(g[4], g[5]), p3 = pack_bf16(g[6], g[7]);
        if (pub) {
          uint32_t* hp = halo_out + q * 32 + j * 8;
          asm volatile("st.relaxed.gpu.global.u32 [%0], %1;" :: "l"(hp), "r"(top ? p0 : p1) : "memory");
          asm volatile("st.relaxed.gpu.global.u32 [%0], %1;" :: "l"(hp + 4), "r"(top ? p2 : p3) : "memory");
        }
        stsm_x4(c.sX + (2 * c.wg + q) * 8192 + c.frag + (((j * 2 + c.hi) ^ c.rsw) << 4), p0, p1, p2, p3);
      }
    }
    bar_sync(3 + c.wg, 128);
    {
      const int wi = c.tid >> 4;
      const uint32_t col = (2 * c.wg + ((c.lane >> 3) & 1)) * 8192, ch = c.lane & 7;
      uint4 r[12];
      const int R0 = tile * 64 + wi * 8;
      const bool first = (R0 % T_) == 0, last = ((R0 + 8) % T_) == 0;
      const bool far = ((wi == 0 && !first) || (wi == 7 && !last)) && !dry;
      const uint4* sp = g_halo + (wi == 0 ? (tile - 1) * 4 + 2 : (tile + 1) * 4) * 32 + c.wg * 16 + (c.lane & 15);
      uint4 h0 = make_uint4(0, 0, 0, 0), h1 = h0;
      auto ld_halo = [&]() {
        asm volatile("ld.relaxed.gpu.global.v4.u32 {%0,%1,%2,%3}, [%4];" : "=r"(h0.x), "=r"(h0.y), "=r"(h0.z), "=r"(h0.w) : "l"(sp) : "memory");
        asm volatile("ld.relaxed.gpu.global.v4.u32 {%0,%1,%2,%3}, [%4];" : "=r"(h1.x), "=r"(h1.y), "=r"(h1.z), "=r"(h1.w) : "l"(sp + 32) : "memory");
      };
      if (far) ld_halo();
#pragma unroll
      for (int i = 0; i < 12; i++) {
        const int row = (wi * 8 - 2 + i) & 63;
        r[i] = lds128(c.sX + col + row * 128 + ((ch ^ (row & 7)) << 4));
      }
      uint32_t w[5][4];
#pragma unroll
      for (int k = 0; k < 5; k++) {
        w[k][0] = bmul2(dwr[k].x, 0x3F003F00u); w[k][1] = bmul2(dwr[k].y, 0x3F003F00u);
        w[k][2] = bmul2(dwr[k].z, 0x3F003F00u); w[k][3] = bmul2(dwr[k].w, 0x3F003F00u);
      }
      auto conv4 = [&](int i0, int i1, int i2, int i3, bool sync) {
        const int rows[4] = {i0, i1, i2, i3};
        uint32_t acc[4][4];
#pragma unroll
        for (int k = 0; k < 5; k++)
#pragma unroll
          for (int j = 0; j < 4; j++) {
            const uint4 x = r[rows[j] + k];
            acc[j][0] = k ? bfma2(x.x, w[k][0], acc[j][0]) : bmul2(x.x, w[0][0]);
            acc[j][1] = k ? bfma2(x.y, w[k][1], acc[j][1]) : bmul2(x.y, w[0][1]);
            acc[j][2] = k ? bfma2(x.z, w[k][2], acc[j][2]) : bmul2(x.z, w[0][2]);
            acc[j][3] = k ? bfma2(x.w, w[k][3], acc[j][3]) : bmul2(x.w, w[0][3]);
          }
#pragma unroll
        for (int j = 0; j < 4; j++)
#pragma unroll
          for (int q = 0; q < 4; q++) acc[j][q] = pack_bf16(silu_half(bf_lo(acc[j][q])), silu_half(bf_hi(acc[j][q])));
        if (sync) bar_sync(3 + c.wg, 128);
#pragma unroll
        for (int j = 0; j < 4; j++)
          sts128(c.sX + col + (wi * 8 + rows[j]) * 128 + ((ch ^ rows[j]) << 4), make_uint4(acc[j][0], acc[j][1], acc[j][2], acc[j][3]));
      };
      conv4(2, 3, 4, 5, true);
      if (far) {
        for (uint32_t n = 0; n < (1u << 18); n++) {
          const uint32_t mx = max(max(max(h0.x, h0.y), max(h0.z, h0.w)), max(max(h1.x, h1.y), max(h1.z, h1.w)));
          if (mx != ~0u) break;
          ld_halo();
        }
      }
      __syncwarp();
      if (first || (far && wi == 0)) { r[0] = h0; r[1] = h1; }
      if (last || (far && wi == 7)) { r[10] = h0; r[11] = h1; }
      conv4(0, 1, 6, 7, false);
    }
    fence_async_smem();
    bar_sync(c.wg == 0 ? 3 : 1, c.wg == 0 ? 128 : 256);
    {
      uint32_t b = stage_wait(c, NC + 12 + c.wg);
      turn_begin(c);
      wg_fence(); piece_ss<0, 0>(c, own, dlo(c.sX, 16), b); wg_commit();
      if (c.wg == 0) { turn_end(c); bar_sync(1, 256); turn_begin(c); }
      b = stage_wait(c, NC + 14 + c.wg);
      wg_fence(); piece_ss<0, 1>(c, own, dlo(c.sX, 16) + 1024, b); wg_commit();
    }
    wg_wait<1>(); stage_release(c, NC + 12 + c.wg);
    wg_wait<0>(); stage_release(c, NC + 14 + c.wg);
    ln_stats(c, own, 0.5f, a0, b0, a1, b1);
    if (c.wg == 1) { turn_begin(c); turn_end(c); }
    store_half(c, c.sA, own, a0, b0, a1, b1);
    fence_async_smem();
    bar_sync(1, 256);
    ff_block(c, NC + 16, own);
    ln_stats(c, own, 1.f, a0, b0, a1, b1);
    store_half(c, c.sX, own, a0, b0, a1, b1);
    fence_async_smem();
    bar_sync(3 + c.wg, 128);
    if (c.tid == 0 && !dry) { tma_store_3d(&tm.Out, c.sX + c.wg * 16384, 0, tile * 64, 2 * c.wg); bulk_commit(); bulk_wait_read(); }
  } else {
    asm volatile("setmaxnreg.dec.sync.aligned.u32 24;");
    if (threadIdx.x == 256 && !dry) {
      __nanosleep(200);
      produce(base + OFF_W, misc + B_FULL, tm, NC + 2, NC + 48);
    }
  }
}

typedef CUresult (*EncodeFn)(CUtensorMap*, CUtensorMapDataType, cuuint32_t, void*, const cuuint64_t*, const cuuint64_t*, const cuuint32_t*,
                             const cuuint32_t*, CUtensorMapInterleave, CUtensorMapSwizzle, CUtensorMapL2promotion, CUtensorMapFloatOOBfill);

CUtensorMap make_map(EncodeFn enc, const void* p, uint64_t d0, uint64_t d1, uint64_t d2, uint64_t s1, uint64_t s2, uint32_t b1, uint32_t b2) {
  CUtensorMap tm;
  cuuint64_t dims[3] = {d0, d1, d2};
  cuuint64_t strides[2] = {s1, s2};
  cuuint32_t box[3] = {64, b1, b2};
  cuuint32_t es[3] = {1, 1, 1};
  enc(&tm, CU_TENSOR_MAP_DATA_TYPE_BFLOAT16, 3, const_cast<void*>(p), dims, strides, box, es, CU_TENSOR_MAP_INTERLEAVE_NONE,
      CU_TENSOR_MAP_SWIZZLE_128B, CU_TENSOR_MAP_L2_PROMOTION_L2_256B, CU_TENSOR_MAP_FLOAT_OOB_FILL_NONE);
  return tm;
}
CUtensorMap blk_map(EncodeFn enc, const void* p, uint64_t rows, uint64_t cols, uint32_t boxrows, uint32_t boxblks) {
  return make_map(enc, p, 64, rows, cols / 64, cols * 2, 128, boxrows, boxblks);
}
CUtensorMap seq_map(EncodeFn enc, const void* p, uint64_t cols, uint32_t boxrows) {
  return make_map(enc, p, cols, T_, 2, cols * 2, cols * 2 * T_, boxrows, 1);
}

}

extern "C" void kernel_launch(void* const* d_in, const int* in_sizes, int n_in, void* d_out, int out_size) {
  (void)in_sizes; (void)n_in; (void)out_size;
  const void *x = d_in[0], *w1a = d_in[1], *w1b = d_in[2], *wqkv = d_in[3], *wo = d_in[4], *pw1 = d_in[5], *dw = d_in[6], *pw2 = d_in[7],
             *w2a = d_in[8], *w2b = d_in[9];
  void* fn = nullptr;
  cudaDriverEntryPointQueryResult qr;
  cudaGetDriverEntryPoint("cuTensorMapEncodeTiled", &fn, cudaEnableDefault, &qr);
  EncodeFn enc = (EncodeFn)fn;
  void* qkv;
  cudaGetSymbolAddress(&qkv, g_qkv);
  cudaFuncSetAttribute(conformer_kernel, cudaFuncAttributeMaxDynamicSharedMemorySize, SMEM_BYTES);

  Wptrs wp;
  const void* ws[8] = {w1a, w1b, wqkv, wo, pw1, pw2, w2a, w2b};
  const uint32_t wb[8] = {524288, 524288, 393216, 131072, 262144, 131072, 524288, 524288};
  for (int i = 0; i < 8; i++) { wp.p[i] = ws[i]; wp.bytes[i] = wb[i]; }
  Maps tm;
  const uint16_t tab[92] = STAGE_TABLE;
  for (int i = 0; i < 92; i++) tm.stage[i] = tab[i];
  tm.X = blk_map(enc, x, ROWS, 256, 64, 4);
  tm.W1a = blk_map(enc, w1a, 256, 1024, 256, 1);
  tm.W1b = blk_map(enc, w1b, 1024, 256, 64, 4);
  tm.Wqkv = blk_map(enc, wqkv, 256, 768, 128, 2);
  tm.QKVst = blk_map(enc, qkv, ROWS, 768, 64, 2);
  tm.Q = seq_map(enc, qkv, 768, 256);
  tm.KV = seq_map(enc, qkv, 768, 160);
  tm.Wo = blk_map(enc, wo, 256, 256, 128, 2);
  tm.Pw1 = make_map(enc, pw1, 256, 256, 2, 1024, 512, 128, 2);
  tm.Pw2 = blk_map(enc, pw2, 256, 256, 128, 2);
  tm.W2a = blk_map(enc, w2a, 256, 1024, 256, 1);
  tm.W2b = blk_map(enc, w2b, 1024, 256, 64, 4);
  tm.Out = blk_map(enc, d_out, ROWS, 256, 64, 2);
  conformer_kernel<<<NCTA, 512, SMEM_BYTES, cudaStreamPerThread>>>(tm, wp, (const uint4*)dw);
}
```

```cpp
#include <cuda_runtime.h>
#include <cuda_bf16.h>
#include <cuda.h>
#include <stdint.h>

namespace {

constexpr int T_ = 4000;
constexpr int ROWS = 8000;
constexpr int NTILE = 125;
constexpr int NWORK = 128;
constexpr int NCTA = 131;

__device__ __align__(128) __nv_bfloat16 g_qkv[ROWS * 768];
__device__ uint4 g_att[(ROWS / 16) * 16 * 32];
__device__ uint4 g_halo[NTILE * 4 * 32];
__device__ uint32_t g_start;
__device__ uint32_t g_cnt1[4 * 32];


__device__ __forceinline__ uint32_t smem_u32(const void* p) { return (uint32_t)__cvta_generic_to_shared(p); }
__device__ __forceinline__ void mbar_init(uint32_t bar, uint32_t cnt) { asm volatile("mbarrier.init.shared::cta.b64 [%0], %1;" :: "r"(bar), "r"(cnt) : "memory"); }
__device__ __forceinline__ void mbar_inval(uint32_t bar) { asm volatile("mbarrier.inval.shared::cta.b64 [%0];" :: "r"(bar) : "memory"); }
__device__ __forceinline__ void mbar_expect_tx(uint32_t bar, uint32_t bytes) { asm volatile("mbarrier.arrive.expect_tx.shared::cta.b64 _, [%0], %1;" :: "r"(bar), "r"(bytes) : "memory"); }
__device__ __forceinline__ void mbar_arrive(uint32_t bar) { asm volatile("mbarrier.arrive.shared::cta.b64 _, [%0];" :: "r"(bar) : "memory"); }
__device__ __forceinline__ void mbar_wait(uint32_t bar, uint32_t parity) {
  asm volatile("{\n.reg .pred p;\n.reg .u32 n;\n"
               "mbarrier.try_wait.parity.shared::cta.b64 p, [%0], %1;\n@p bra DONE_%=;\nmov.u32 n, 0;\n"
               "LOOP_%=:\nmbarrier.try_wait.parity.shared::cta.b64 p, [%0], %1;\n@p bra DONE_%=;\n"
               "add.u32 n, n, 1;\nsetp.lt.u32 p, n, 262144;\n@p bra LOOP_%=;\ntrap;\nDONE_%=:\n}\n" :: "r"(bar), "r"(parity) : "memory");
}
__device__ __forceinline__ void cnt_wait(const uint32_t* p, uint32_t target) {
  asm volatile("{\n.reg .pred p;\n.reg .u32 n, v;\nmov.u32 n, 0;\n"
               "LOOP_%=:\nld.relaxed.gpu.global.u32 v, [%0];\nsub.u32 v, v, %1;\nsetp.ge.s32 p, v, 0;\n@p bra DONE_%=;\n"
               "nanosleep.u32 40;\nadd.u32 n, n, 1;\nsetp.lt.u32 p, n, 262144;\n@p bra LOOP_%=;\ntrap;\nDONE_%=:\n}\n" :: "l"(p), "r"(target) : "memory");
}
__device__ __forceinline__ void cnt_signal(uint32_t* p) {
  asm volatile("red.relaxed.gpu.global.add.u32 [%0], 1;" :: "l"(p) : "memory");
}
__device__ __forceinline__ void tma_load_3d(uint32_t dst, const CUtensorMap* tm, uint32_t bar, int c0, int c1, int c2) {
  asm volatile("cp.async.bulk.tensor.3d.shared::cluster.global.mbarrier::complete_tx::bytes [%0], [%1, {%3, %4, %5}], [%2];"
    :: "r"(dst), "l"(tm), "r"(bar), "r"(c0), "r"(c1), "r"(c2) : "memory");
}
__device__ __forceinline__ void tma_store_3d(const CUtensorMap* tm, uint32_t src, int c0, int c1, int c2) {
  asm volatile("cp.async.bulk.tensor.3d.global.shared::cta.bulk_group [%0, {%2, %3, %4}], [%1];" :: "l"(tm), "r"(src), "r"(c0), "r"(c1), "r"(c2) : "memory");
}
__device__ __forceinline__ void bulk_commit() { asm volatile("cp.async.bulk.commit_group;" ::: "memory"); }
__device__ __forceinline__ void bulk_wait_read() { asm volatile("cp.async.bulk.wait_group.read 0;" ::: "memory"); }
__device__ __forceinline__ void bulk_wait_all() { asm volatile("cp.async.bulk.wait_group 0;" ::: "memory"); }
__device__ __forceinline__ void l2_prefetch(const void* p, uint32_t bytes) { asm volatile("cp.async.bulk.prefetch.L2.global [%0], %1;" :: "l"(p), "r"(bytes) : "memory"); }
__device__ __forceinline__ void prefetch_tmap(const CUtensorMap* tm) { asm volatile("prefetch.tensormap [%0];" :: "l"(tm) : "memory"); }
__device__ __forceinline__ void fence_async_smem() { asm volatile("fence.proxy.async.shared::cta;" ::: "memory"); }
__device__ __forceinline__ void wg_fence() { asm volatile("wgmma.fence.sync.aligned;" ::: "memory"); }
__device__ __forceinline__ void wg_commit() { asm volatile("wgmma.commit_group.sync.aligned;" ::: "memory"); }
template<int N> __device__ __forceinline__ void wg_wait() { asm volatile("wgmma.wait_group.sync.aligned %0;" :: "n"(N) : "memory"); }
__device__ __forceinline__ void bar_sync(int id, int n) { asm volatile("bar.sync %0, %1;" :: "r"(id), "r"(n) : "memory"); }
__device__ __forceinline__ void bar_arrive(int id, int n) { asm volatile("bar.arrive %0, %1;" :: "r"(id), "r"(n) : "memory"); }
__device__ __forceinline__ float ex2(float x) { float y; asm("ex2.approx.ftz.f32 %0, %1;" : "=f"(y) : "f"(x)); return y; }
__device__ __forceinline__ float tanh_fast(float x) { float y; asm("tanh.approx.f32 %0, %1;" : "=f"(y) : "f"(x)); return y; }
__device__ __forceinline__ uint32_t pack_bf16(float lo, float hi) { uint32_t r; asm("cvt.rn.bf16x2.f32 %0, %1, %2;" : "=r"(r) : "f"(hi), "f"(lo)); return r; }
__device__ __forceinline__ uint32_t bmul2(uint32_t a, uint32_t b) { uint32_t d; asm("mul.rn.bf16x2 %0, %1, %2;" : "=r"(d) : "r"(a), "r"(b)); return d; }
__device__ __forceinline__ uint32_t bfma2(uint32_t a, uint32_t b, uint32_t c) { uint32_t d; asm("fma.rn.bf16x2 %0, %1, %2, %3;" : "=r"(d) : "r"(a), "r"(b), "r"(c)); return d; }
__device__ __forceinline__ float bf_lo(uint32_t u) { return __uint_as_float(u << 16); }
__device__ __forceinline__ float bf_hi(uint32_t u) { return __uint_as_float(u & 0xffff0000u); }
__device__ __forceinline__ void ldsm_x4(uint32_t addr, uint32_t& r0, uint32_t& r1, uint32_t& r2, uint32_t& r3) {
  asm volatile("ldmatrix.sync.aligned.m8n8.x4.shared.b16 {%0,%1,%2,%3}, [%4];" : "=r"(r0), "=r"(r1), "=r"(r2), "=r"(r3) : "r"(addr) : "memory");
}
__device__ __forceinline__ void stsm_x4(uint32_t addr, uint32_t r0, uint32_t r1, uint32_t r2, uint32_t r3) {
  asm volatile("stmatrix.sync.aligned.m8n8.x4.shared.b16 [%0], {%1,%2,%3,%4};" :: "r"(addr), "r"(r0), "r"(r1), "r"(r2), "r"(r3) : "memory");
}
__device__ __forceinline__ void sts128(uint32_t addr, uint4 v) { asm volatile("st.shared.v4.b32 [%0], {%1,%2,%3,%4};" :: "r"(addr), "r"(v.x), "r"(v.y), "r"(v.z), "r"(v.w) : "memory"); }
__device__ __forceinline__ uint4 lds128(uint32_t addr) { uint4 v; asm volatile("ld.shared.v4.b32 {%0,%1,%2,%3}, [%4];" : "=r"(v.x), "=r"(v.y), "=r"(v.z), "=r"(v.w) : "r"(addr) : "memory"); return v; }
__device__ __forceinline__ void sts64f(uint32_t addr, float a, float b) { asm volatile("st.shared.v2.f32 [%0], {%1,%2};" :: "r"(addr), "f"(a), "f"(b) : "memory"); }
__device__ __forceinline__ float2 lds64f(uint32_t addr) { float2 v; asm volatile("ld.shared.v2.f32 {%0,%1}, [%2];" : "=f"(v.x), "=f"(v.y) : "r"(addr) : "memory"); return v; }
__device__ __forceinline__ uint32_t dlo(uint32_t addr, uint32_t lbo) { return ((addr & 0x3FFFF) >> 4) | ((lbo >> 4) << 16); }

template<int SD> __device__ __forceinline__ void wg_ss_n128_tb1(float (&d)[64], uint32_t da, uint32_t db) {
  asm volatile("{\n.reg .b64 da, db;\nmov.b64 da, {%64, 0x40000040};\nmov.b64 db, {%65, 0x40000040};\n"
    "wgmma.mma_async.sync.aligned.m64n128k16.f32.bf16.bf16 {%0, %1, %2, %3, %4, %5, %6, %7, %8, %9, %10, %11, %12, %13, %14, %15, %16, %17, %18, %19, %20, %21, %22, %23, %24, %25, %26, %27, %28, %29, %30, %31, %32, %33, %34, %35, %36, %37, %38, %39, %40, %41, %42, %43, %44, %45, %46, %47, %48, %49, %50, %51, %52, %53, %54, %55, %56, %57, %58, %59, %60, %61, %62, %63}, da, db, %66, 1, 1, 0, 1;\n}\n"
    : "+f"(d[0]), "+f"(d[1]), "+f"(d[2]), "+f"(d[3]), "+f"(d[4]), "+f"(d[5]), "+f"(d[6]), "+f"(d[7]), "+f"(d[8]), "+f"(d[9]), "+f"(d[10]), "+f"(d[11]), "+f"(d[12]), "+f"(d[13]), "+f"(d[14]), "+f"(d[15]), "+f"(d[16]), "+f"(d[17]), "+f"(d[18]), "+f"(d[19]), "+f"(d[20]), "+f"(d[21]), "+f"(d[22]), "+f"(d[23]), "+f"(d[24]), "+f"(d[25]), "+f"(d[26]), "+f"(d[27]), "+f"(d[28]), "+f"(d[29]), "+f"(d[30]), "+f"(d[31]), "+f"(d[32]), "+f"(d[33]), "+f"(d[34]), "+f"(d[35]), "+f"(d[36]), "+f"(d[37]), "+f"(d[38]), "+f"(d[39]), "+f"(d[40]), "+f"(d[41]), "+f"(d[42]), "+f"(d[43]), "+f"(d[44]), "+f"(d[45]), "+f"(d[46]), "+f"(d[47]), "+f"(d[48]), "+f"(d[49]), "+f"(d[50]), "+f"(d[51]), "+f"(d[52]), "+f"(d[53]), "+f"(d[54]), "+f"(d[55]), "+f"(d[56]), "+f"(d[57]), "+f"(d[58]), "+f"(d[59]), "+f"(d[60]), "+f"(d[61]), "+f"(d[62]), "+f"(d[63])
    : "r"(da), "r"(db), "n"(SD));
}
template<int SD> __device__ __forceinline__ void wg_rs_n128_tb1(float (&d)[64], uint32_t a0, uint32_t a1, uint32_t a2, uint32_t a3, uint32_t db) {
  asm volatile("{\n.reg .b64 db;\nmov.b64 db, {%68, 0x40000040};\n"
    "wgmma.mma_async.sync.aligned.m64n128k16.f32.bf16.bf16 {%0, %1, %2, %3, %4, %5, %6, %7, %8, %9, %10, %11, %12, %13, %14, %15, %16, %17, %18, %19, %20, %21, %22, %23, %24, %25, %26, %27, %28, %29, %30, %31, %32, %33, %34, %35, %36, %37, %38, %39, %40, %41, %42, %43, %44, %45, %46, %47, %48, %49, %50, %51, %52, %53, %54, %55, %56, %57, %58, %59, %60, %61, %62, %63}, {%64, %65, %66, %67}, db, %69, 1, 1, 1;\n}\n"
    : "+f"(d[0]), "+f"(d[1]), "+f"(d[2]), "+f"(d[3]), "+f"(d[4]), "+f"(d[5]), "+f"(d[6]), "+f"(d[7]), "+f"(d[8]), "+f"(d[9]), "+f"(d[10]), "+f"(d[11]), "+f"(d[12]), "+f"(d[13]), "+f"(d[14]), "+f"(d[15]), "+f"(d[16]), "+f"(d[17]), "+f"(d[18]), "+f"(d[19]), "+f"(d[20]), "+f"(d[21]), "+f"(d[22]), "+f"(d[23]), "+f"(d[24]), "+f"(d[25]), "+f"(d[26]), "+f"(d[27]), "+f"(d[28]), "+f"(d[29]), "+f"(d[30]), "+f"(d[31]), "+f"(d[32]), "+f"(d[33]), "+f"(d[34]), "+f"(d[35]), "+f"(d[36]), "+f"(d[37]), "+f"(d[38]), "+f"(d[39]), "+f"(d[40]), "+f"(d[41]), "+f"(d[42]), "+f"(d[43]), "+f"(d[44]), "+f"(d[45]), "+f"(d[46]), "+f"(d[47]), "+f"(d[48]), "+f"(d[49]), "+f"(d[50]), "+f"(d[51]), "+f"(d[52]), "+f"(d[53]), "+f"(d[54]), "+f"(d[55]), "+f"(d[56]), "+f"(d[57]), "+f"(d[58]), "+f"(d[59]), "+f"(d[60]), "+f"(d[61]), "+f"(d[62]), "+f"(d[63])
    : "r"(a0), "r"(a1), "r"(a2), "r"(a3), "r"(db), "n"(SD));
}
template<int SD> __device__ __forceinline__ void wg_ss_n64_tb1(float (&d)[32], uint32_t da, uint32_t db) {
  asm volatile("{\n.reg .b64 da, db;\nmov.b64 da, {%32, 0x40000040};\nmov.b64 db, {%33, 0x40000040};\n"
    "wgmma.mma_async.sync.aligned.m64n64k16.f32.bf16.bf16 {%0, %1, %2, %3, %4, %5, %6, %7, %8, %9, %10, %11, %12, %13, %14, %15, %16, %17, %18, %19, %20, %21, %22, %23, %24, %25, %26, %27, %28, %29, %30, %31}, da, db, %34, 1, 1, 0, 1;\n}\n"
    : "+f"(d[0]), "+f"(d[1]), "+f"(d[2]), "+f"(d[3]), "+f"(d[4]), "+f"(d[5]), "+f"(d[6]), "+f"(d[7]), "+f"(d[8]), "+f"(d[9]), "+f"(d[10]), "+f"(d[11]), "+f"(d[12]), "+f"(d[13]), "+f"(d[14]), "+f"(d[15]), "+f"(d[16]), "+f"(d[17]), "+f"(d[18]), "+f"(d[19]), "+f"(d[20]), "+f"(d[21]), "+f"(d[22]), "+f"(d[23]), "+f"(d[24]), "+f"(d[25]), "+f"(d[26]), "+f"(d[27]), "+f"(d[28]), "+f"(d[29]), "+f"(d[30]), "+f"(d[31])
    : "r"(da), "r"(db), "n"(SD));
}
template<int SD> __device__ __forceinline__ void wg_ss_n80_tb0(float (&d)[40], uint32_t da, uint32_t db) {
  asm volatile("{\n.reg .b64 da, db;\nmov.b64 da, {%40, 0x40000040};\nmov.b64 db, {%41, 0x40000040};\n"
    "wgmma.mma_async.sync.aligned.m64n80k16.f32.bf16.bf16 {%0, %1, %2, %3, %4, %5, %6, %7, %8, %9, %10, %11, %12, %13, %14, %15, %16, %17, %18, %19, %20, %21, %22, %23, %24, %25, %26, %27, %28, %29, %30, %31, %32, %33, %34, %35, %36, %37, %38, %39}, da, db, %42, 1, 1, 0, 0;\n}\n"
    : "+f"(d[0]), "+f"(d[1]), "+f"(d[2]), "+f"(d[3]), "+f"(d[4]), "+f"(d[5]), "+f"(d[6]), "+f"(d[7]), "+f"(d[8]), "+f"(d[9]), "+f"(d[10]), "+f"(d[11]), "+f"(d[12]), "+f"(d[13]), "+f"(d[14]), "+f"(d[15]), "+f"(d[16]), "+f"(d[17]), "+f"(d[18]), "+f"(d[19]), "+f"(d[20]), "+f"(d[21]), "+f"(d[22]), "+f"(d[23]), "+f"(d[24]), "+f"(d[25]), "+f"(d[26]), "+f"(d[27]), "+f"(d[28]), "+f"(d[29]), "+f"(d[30]), "+f"(d[31]), "+f"(d[32]), "+f"(d[33]), "+f"(d[34]), "+f"(d[35]), "+f"(d[36]), "+f"(d[37]), "+f"(d[38]), "+f"(d[39])
    : "r"(da), "r"(db), "n"(SD));
}
template<int SD> __device__ __forceinline__ void wg_rs_n64_tb1(float (&d)[32], uint32_t a0, uint32_t a1, uint32_t a2, uint32_t a3, uint32_t db) {
  asm volatile("{\n.reg .b64 db;\nmov.b64 db, {%36, 0x40000040};\n"
    "wgmma.mma_async.sync.aligned.m64n64k16.f32.bf16.bf16 {%0, %1, %2, %3, %4, %5, %6, %7, %8, %9, %10, %11, %12, %13, %14, %15, %16, %17, %18, %19, %20, %21, %22, %23, %24, %25, %26, %27, %28, %29, %30, %31}, {%32, %33, %34, %35}, db, %37, 1, 1, 1;\n}\n"
    : "+f"(d[0]), "+f"(d[1]), "+f"(d[2]), "+f"(d[3]), "+f"(d[4]), "+f"(d[5]), "+f"(d[6]), "+f"(d[7]), "+f"(d[8]), "+f"(d[9]), "+f"(d[10]), "+f"(d[11]), "+f"(d[12]), "+f"(d[13]), "+f"(d[14]), "+f"(d[15]), "+f"(d[16]), "+f"(d[17]), "+f"(d[18]), "+f"(d[19]), "+f"(d[20]), "+f"(d[21]), "+f"(d[22]), "+f"(d[23]), "+f"(d[24]), "+f"(d[25]), "+f"(d[26]), "+f"(d[27]), "+f"(d[28]), "+f"(d[29]), "+f"(d[30]), "+f"(d[31])
    : "r"(a0), "r"(a1), "r"(a2), "r"(a3), "r"(db), "n"(SD));
}


constexpr int RING = 5;
constexpr uint32_t STAGE = 32768;
constexpr uint32_t OFF_X = 32768, OFF_W = 65536, OFF_MISC = OFF_W + RING * STAGE;
constexpr int SMEM_BYTES = OFF_MISC + 256 + 1024 + 1024;

struct Ctx {
  uint32_t sA, sX, sW, full, empty, stats;
  uint32_t frag;
  uint32_t rsw;
  uint32_t hi;
  int wg, tid, lane;
};
__device__ __forceinline__ uint32_t stage_wait(const Ctx& c, int n) {
  const int q = n / RING, s = n - q * RING;
  mbar_wait(c.full + 8 * s, q & 1);
  return dlo(c.sW + s * STAGE, 0);
}
__device__ __forceinline__ void stage_release(const Ctx& c, int n) {
  const int s = n % RING;
  if (c.tid == 0) mbar_arrive(c.empty + 8 * s);
}
__device__ __forceinline__ void turn_begin(const Ctx& c) { bar_sync(5 + c.wg, 256); }
__device__ __forceinline__ void turn_end(const Ctx& c) { bar_arrive(5 + (c.wg ^ 1), 256); }
template<int FIRST, int LAST> __device__ __forceinline__ void piece_ss(const Ctx& c, float (&acc)[64], uint32_t dA, uint32_t dB) {
  dB += (16384 >> 4) << 16;
  wg_ss_n128_tb1<FIRST ? 0 : 1>(acc, dA, dB);
#pragma unroll
  for (int kk = 1; kk < 8; kk++) {
    wg_ss_n128_tb1<1>(acc, dA + (kk >> 2) * 512 + (kk & 3) * 2, dB + kk * 128);
  }
  if (LAST) turn_end(c);
}
__device__ __forceinline__ void ff_g1(const Ctx& c, float (&h)[32], uint32_t dA, uint32_t dB) {
  wg_ss_n64_tb1<0>(h, dA, dB);
#pragma unroll
  for (int kk = 1; kk < 16; kk++) {
    wg_ss_n64_tb1<1>(h, dA + (kk >> 2) * 512 + (kk & 3) * 2, dB + kk * 128);
  }
}
__device__ __forceinline__ void ff_g2(float (&acc)[64], const uint32_t (&P)[16], uint32_t dB, int half) {
  dB += ((8192 >> 4) << 16) + half * 1024;
#pragma unroll
  for (int kk = 0; kk < 4; kk++) wg_rs_n128_tb1<1>(acc, P[4 * kk], P[4 * kk + 1], P[4 * kk + 2], P[4 * kk + 3], dB + kk * 128);
}
struct NoHook { __device__ __forceinline__ void operator()() const {} };
template<int FIRST, class Hook = NoHook> __device__ __forceinline__ void gemm256(const Ctx& c, float (&acc)[64], int n, Hook hook = Hook()) {
  const uint32_t dA = dlo(c.sA, 16);
  uint32_t b = stage_wait(c, n);
  turn_begin(c);
  wg_fence(); piece_ss<FIRST, 0>(c, acc, dA, b); wg_commit();
  b = stage_wait(c, n + 1);
  wg_fence(); piece_ss<0, 1>(c, acc, dA + 1024, b); wg_commit();
  hook();
  wg_wait<1>(); stage_release(c, n);
  wg_wait<0>(); stage_release(c, n + 1);
}
__device__ __forceinline__ uint32_t frag_addr(const Ctx& c, uint32_t tile, int j) {
  return tile + (2 * c.wg + (j >> 2)) * 8192 + c.frag + ((((j & 3) * 2 + c.hi) ^ c.rsw) << 4);
}
__device__ __forceinline__ void load_half(const Ctx& c, uint32_t tile, float (&v)[64]) {
#pragma unroll
  for (int j = 0; j < 8; j++) {
    uint32_t r0, r1, r2, r3;
    ldsm_x4(frag_addr(c, tile, j), r0, r1, r2, r3);
    v[8 * j] = bf_lo(r0); v[8 * j + 1] = bf_hi(r0); v[8 * j + 2] = bf_lo(r1); v[8 * j + 3] = bf_hi(r1);
    v[8 * j + 4] = bf_lo(r2); v[8 * j + 5] = bf_hi(r2); v[8 * j + 6] = bf_lo(r3); v[8 * j + 7] = bf_hi(r3);
  }
}
__device__ __forceinline__ void store_half(const Ctx& c, uint32_t tile, const float (&v)[64], float a0, float b0, float a1, float b1) {
#pragma unroll
  for (int j = 0; j < 8; j++)
    stsm_x4(frag_addr(c, tile, j),
            pack_bf16(fmaf(v[8 * j], a0, b0), fmaf(v[8 * j + 1], a0, b0)), pack_bf16(fmaf(v[8 * j + 2], a1, b1), fmaf(v[8 * j + 3], a1, b1)),
            pack_bf16(fmaf(v[8 * j + 4], a0, b0), fmaf(v[8 * j + 5], a0, b0)), pack_bf16(fmaf(v[8 * j + 6], a1, b1), fmaf(v[8 * j + 7], a1, b1)));
}
__device__ __forceinline__ void store_half_raw(const Ctx& c, uint32_t tile, const float (&v)[64]) {
#pragma unroll
  for (int j = 0; j < 8; j++)
    stsm_x4(frag_addr(c, tile, j), pack_bf16(v[8 * j], v[8 * j + 1]), pack_bf16(v[8 * j + 2], v[8 * j + 3]),
            pack_bf16(v[8 * j + 4], v[8 * j + 5]), pack_bf16(v[8 * j + 6], v[8 * j + 7]));
}
__device__ __forceinline__ void ln_stats(const Ctx& c, const float (&v)[64], float scale, float& a0, float& b0, float& a1, float& b1) {
  float s0 = 0.f, s1 = 0.f, q0 = 0.f, q1 = 0.f, s2 = 0.f, s3 = 0.f, q2 = 0.f, q3 = 0.f;
#pragma unroll
  for (int i = 0; i < 16; i++) {
    s0 += v[4 * i]; q0 = fmaf(v[4 * i], v[4 * i], q0);
    s2 += v[4 * i + 1]; q2 = fmaf(v[4 * i + 1], v[4 * i + 1], q2);
    s1 += v[4 * i + 2]; q1 = fmaf(v[4 * i + 2], v[4 * i + 2], q1);
    s3 += v[4 * i + 3]; q3 = fmaf(v[4 * i + 3], v[4 * i + 3], q3);
  }
  s0 += s2; q0 += q2; s1 += s3; q1 += q3;
  s0 += __shfl_xor_sync(0xffffffff, s0, 1); q0 += __shfl_xor_sync(0xffffffff, q0, 1);
  s1 += __shfl_xor_sync(0xffffffff, s1, 1); q1 += __shfl_xor_sync(0xffffffff, q1, 1);
  s0 += __shfl_xor_sync(0xffffffff, s0, 2); q0 += __shfl_xor_sync(0xffffffff, q0, 2);
  s1 += __shfl_xor_sync(0xffffffff, s1, 2); q1 += __shfl_xor_sync(0xffffffff, q1, 2);
  const uint32_t row = (c.tid >> 5) * 16 + (c.lane >> 2);
  if ((c.lane & 3) == 0) {
    sts64f(c.stats + c.wg * 512 + row * 8, s0, q0);
    sts64f(c.stats + c.wg * 512 + (row + 8) * 8, s1, q1);
  }
  bar_sync(1, 256);
  const float2 o0 = lds64f(c.stats + (c.wg ^ 1) * 512 + row * 8), o1 = lds64f(c.stats + (c.wg ^ 1) * 512 + (row + 8) * 8);
  const float m0 = (s0 + o0.x) * (1.f / 256.f), m1 = (s1 + o1.x) * (1.f / 256.f);
  const float var0 = fmaxf(fmaf(-m0, m0, (q0 + o0.y) * (1.f / 256.f)), 0.f), var1 = fmaxf(fmaf(-m1, m1, (q1 + o1.y) * (1.f / 256.f)), 0.f);
  a0 = rsqrtf(var0 + 1e-5f) * scale; a1 = rsqrtf(var1 + 1e-5f) * scale;
  b0 = -m0 * a0; b1 = -m1 * a1;
}
__device__ __forceinline__ float silu_half(float h) { return fmaf(h, tanh_fast(h), h); }
__device__ __forceinline__ float silu_quarter(float h) { const float q = 0.5f * h; return fmaf(q, tanh_fast(h), q); }
__device__ __forceinline__ void silu_pack(const float (&acc)[32], uint32_t (&P)[16]) {
#pragma unroll
  for (int i = 0; i < 16; i++) P[i] = pack_bf16(silu_quarter(acc[2 * i]), silu_quarter(acc[2 * i + 1]));
}
__device__ __forceinline__ void ff_block(const Ctx& c, int n0, float (&own)[64]) {
  float oth[64], h[32];
  uint32_t P[16];
#pragma unroll
  for (int i = 0; i < 64; i++) oth[i] = 0.f;
  const uint32_t dA = dlo(c.sA, 16);
  {
    const uint32_t b = stage_wait(c, n0 + c.wg);
    turn_begin(c);
    wg_fence(); ff_g1(c, h, dA, b); wg_commit();
    turn_end(c);
    wg_wait<0>(); stage_release(c, n0 + c.wg);
    silu_pack(h, P);
  }
#pragma unroll 1
  for (int it = 1; it < 8; it++) {
    const int n = n0 + 4 * it - 2 + 2 * c.wg;
    uint32_t b = stage_wait(c, n);
    turn_begin(c);
    wg_fence(); ff_g2(own, P, b, c.wg); ff_g2(oth, P, b, c.wg ^ 1); wg_commit();
    b = stage_wait(c, n + 1);
    wg_fence(); ff_g1(c, h, dA, b); wg_commit();
    turn_end(c);
    wg_wait<1>(); stage_release(c, n);
    wg_wait<0>(); stage_release(c, n + 1);
    silu_pack(h, P);
  }
  if (c.wg == 0) bar_arrive(2, 256);
  {
    const int n = n0 + 30 + c.wg;
    const uint32_t b = stage_wait(c, n);
    turn_begin(c);
    wg_fence(); ff_g2(oth, P, b, c.wg ^ 1); wg_commit();
    ff_g2(own, P, b, c.wg); wg_commit();
    turn_end(c);
    wg_wait<1>();
    if (c.wg == 1) bar_sync(2, 256);
    const uint32_t e = (c.wg == 0 ? c.sX : c.sA) + c.tid * 16;
#pragma unroll
    for (int i = 0; i < 16; i++)
      sts128(e + i * 2048, make_uint4(__float_as_uint(oth[4 * i]), __float_as_uint(oth[4 * i + 1]), __float_as_uint(oth[4 * i + 2]), __float_as_uint(oth[4 * i + 3])));
    wg_wait<0>(); stage_release(c, n);
  }
  bar_sync(1, 256);
  const uint32_t e = (c.wg == 0 ? c.sA : c.sX) + c.tid * 16;
#pragma unroll
  for (int i = 0; i < 16; i++) {
    const uint4 u = lds128(e + i * 2048);
    own[4 * i] += __uint_as_float(u.x); own[4 * i + 1] += __uint_as_float(u.y);
    own[4 * i + 2] += __uint_as_float(u.z); own[4 * i + 3] += __uint_as_float(u.w);
  }
}
struct Maps { CUtensorMap X, W1a, W1b, Wqkv, QKVst, Q, KV, Wo, Pw1, Pw2, W2a, W2b, Out; uint16_t stage[92]; };
constexpr int NA = 44;
constexpr int NC = 45;
#define STAGE_TABLE {0x1, 0x11, 0x2, 0x21, 0x102, 0x31, 0x202, 0x41, 0x302, 0x51, 0x402, 0x61, 0x502, 0x71, 0x602, 0x81, 0x702, 0x91, 0x802, 0xa1, 0x902, 0xb1, 0xa02, 0xc1, 0xb02, 0xd1, 0xc02, 0xe1, 0xd02, 0xf1, 0xe02, 0xf02, 0x3, 0x203, 0x23, 0x223, 0x43, 0x243, 0x63, 0x263, 0x83, 0x283, 0xa3, 0x2a3, 0x7, 0x207, 0x27, 0x227, 0x8, 0x208, 0x2008, 0x2208, 0x1008, 0x1208, 0x3008, 0x3208, 0x9, 0x29, 0x209, 0x229, 0xa, 0x1a, 0xb, 0x2a, 0x10b, 0x3a, 0x20b, 0x4a, 0x30b, 0x5a, 0x40b, 0x6a, 0x50b, 0x7a, 0x60b, 0x8a, 0x70b, 0x9a, 0x80b, 0xaa, 0x90b, 0xba, 0xa0b, 0xca, 0xb0b, 0xda, 0xc0b, 0xea, 0xd0b, 0xfa, 0xe0b, 0xf0b}
__device__ __forceinline__ void load_stage(uint32_t dst, uint32_t bar, const Maps& tm, int n) {
  const uint32_t e = tm.stage[n - (n > NA)];
  mbar_expect_tx(bar, STAGE);
  tma_load_3d(dst, &tm.X + (e & 15), bar, (e >> 12) * 64, ((e >> 8) & 15) * 64, (e >> 4) & 15);
}
__device__ __forceinline__ void produce(uint32_t sW, uint32_t full, const Maps& tm, int n0, int n1) {
  uint32_t s = n0 % RING, ph = ((n0 / RING) & 1) ^ 1;
#pragma unroll 1
  for (int n = n0; n < n1; n++) {
    mbar_wait(full + 8 * RING + 8 * s, ph);
    load_stage(sW + s * STAGE, full + 8 * s, tm, n);
    if (++s == RING) { s = 0; ph ^= 1; }
  }
}
__device__ __forceinline__ Ctx make_ctx(uint32_t base) {
  Ctx c;
  c.sA = base; c.sX = base + OFF_X; c.sW = base + OFF_W;
  c.full = base + OFF_MISC; c.empty = c.full + 8 * RING; c.stats = base + OFF_MISC + 256;
  c.wg = __shfl_sync(0xffffffff, (int)(threadIdx.x >> 7), 0);
  c.tid = threadIdx.x & 127; c.lane = threadIdx.x & 31;
  const uint32_t r = (c.tid >> 5) * 16 + (c.lane & 7) + ((c.lane >> 3) & 1) * 8;
  c.frag = r * 128; c.rsw = r & 7; c.hi = c.lane >> 4;
  return c;
}

constexpr int NSTG = 4;
constexpr int KVB = 160 * 128;
constexpr int NKV = T_ / 160;
static_assert(NSTG * 2 * KVB == RING * STAGE, "the K/V ring reuses the weight ring");

struct AttCtx { uint32_t sKV, full, empty, wfull; const Maps* tm; int h, b, wg; };
__device__ __forceinline__ int kv_slot(int i) { return (i + 3) & 3; }
__device__ __forceinline__ void att_load(const AttCtx& a, int i, int v) {
  const int s = i & 3;
  mbar_expect_tx(a.full + 8 * (s + v * NSTG), KVB);
  tma_load_3d(a.sKV + kv_slot(i) * 2 * KVB + v * KVB, &a.tm->KV, a.full + 8 * (s + v * NSTG), 256 + v * 256 + a.h * 64, i * 160, a.b);
}
__device__ __forceinline__ void att_load_stage(const AttCtx& a, int i) { att_load(a, i, 0); att_load(a, i, 1); }
__device__ __forceinline__ void att_init_bars(const AttCtx& a) {
  for (int i = 0; i < NSTG; i++) { mbar_init(a.full + 8 * i, 1); mbar_init(a.full + 8 * (NSTG + i), 1); mbar_init(a.empty + 8 * i, 4); }
}
__device__ __forceinline__ void att_qk(float (&S)[40], uint32_t dQ, uint32_t kd) {
  wg_ss_n80_tb0<0>(S, dQ, kd);
#pragma unroll
  for (int kk = 1; kk < 4; kk++) wg_ss_n80_tb0<1>(S, dQ + kk * 2, kd + kk * 2);
}
__device__ __forceinline__ void att_pv(float (&O)[32], const uint32_t (&P)[20], uint32_t vd) {
#pragma unroll
  for (int kk = 0; kk < 5; kk++) wg_rs_n64_tb1<1>(O, P[kk * 4], P[kk * 4 + 1], P[kk * 4 + 2], P[kk * 4 + 3], vd + kk * 128);
}
template<bool SAFE>
__device__ __forceinline__ void att_softmax(const float (&S)[40], uint32_t (&P)[20], float (&O)[32], float& m0, float& m1, float& l0, float& l1) {
  if (SAFE) {
    float x0 = fmaxf(S[0], S[1]), x1 = fmaxf(S[2], S[3]);
#pragma unroll
    for (int i = 1; i < 10; i++) { x0 = fmaxf(x0, fmaxf(S[4 * i], S[4 * i + 1])); x1 = fmaxf(x1, fmaxf(S[4 * i + 2], S[4 * i + 3])); }
    x0 = fmaxf(x0, __shfl_xor_sync(0xffffffff, x0, 1)); x1 = fmaxf(x1, __shfl_xor_sync(0xffffffff, x1, 1));
    x0 = fmaxf(x0, __shfl_xor_sync(0xffffffff, x0, 2)); x1 = fmaxf(x1, __shfl_xor_sync(0xffffffff, x1, 2));
    const float n0 = fmaxf(m0, x0), n1 = fmaxf(m1, x1);
    const float f0 = ex2(m0 - n0), f1 = ex2(m1 - n1);
    m0 = n0; m1 = n1; l0 *= f0; l1 *= f1;
#pragma unroll
    for (int i = 0; i < 8; i++) { O[4 * i] *= f0; O[4 * i + 1] *= f0; O[4 * i + 2] *= f1; O[4 * i + 3] *= f1; }
  }
#pragma unroll
  for (int i = 0; i < 10; i++) {
    float p0, p1, p2, p3;
    if (SAFE) { p0 = ex2(S[4 * i] - m0); p1 = ex2(S[4 * i + 1] - m0); p2 = ex2(S[4 * i + 2] - m1); p3 = ex2(S[4 * i + 3] - m1); }
    else { p0 = ex2(S[4 * i]); p1 = ex2(S[4 * i + 1]); p2 = ex2(S[4 * i + 2]); p3 = ex2(S[4 * i + 3]); }
    l0 += p0 + p1; l1 += p2 + p3;
    P[2 * i] = pack_bf16(p0, p1); P[2 * i + 1] = pack_bf16(p2, p3);
  }
}
template<bool SAFE>
__device__ __forceinline__ void att_refill(const AttCtx& a, int it) {
  if ((threadIdx.x & 127) == 0) {
    mbar_arrive(a.empty + 8 * (it & 3));
    if (a.wg == (it & 3) && it >= 1) {
      const bool kv = it - 1 + NSTG < NKV;
      if (kv || (!SAFE && a.wfull)) {
        mbar_wait(a.empty + 8 * ((it - 1) & 3), ((it - 1) >> 2) & 1);
        if (kv) att_load_stage(a, it - 1 + NSTG);
        else load_stage(a.sKV + (it - 22) * STAGE, a.wfull + 8 * (it - 22), *a.tm, NC + it - 22);
      }
    }
  }
  __syncwarp();
}
constexpr uint32_t KV_STG = 2 * KVB / 16, KV_VOFF = KVB / 16, KV_HALF = 80 * 128 / 16;
template<bool SAFE>
__device__ __forceinline__ void att_pass(const AttCtx& a, bool idle, uint32_t dQ, float (&O)[32], float& l0, float& l1) {
  float S[40];
  uint32_t P[20];
  float m0 = -INFINITY, m1 = -INFINITY;
  l0 = 0.f; l1 = 0.f;
#pragma unroll
  for (int i = 0; i < 32; i++) O[i] = 0.f;
  const uint32_t dKV = dlo(a.sKV, 16);
  if (SAFE) {
#pragma unroll 1
    for (int j = 0; j < 2 * NKV; j++) {
      const int it = j >> 1, s = it & 3;
      const uint32_t kb = dKV + kv_slot(it) * KV_STG + (j & 1) * KV_HALF;
      mbar_wait(a.full + 8 * s, (it >> 2) & 1);
      wg_fence(); att_qk(S, dQ, kb); wg_commit(); wg_wait<0>();
      att_softmax<true>(S, P, O, m0, m1, l0, l1);
      mbar_wait(a.full + 8 * (NSTG + s), (it >> 2) & 1);
      wg_fence(); att_pv(O, P, kb + KV_VOFF); wg_commit(); wg_wait<0>();
      if (j & 1) att_refill<true>(a, it);
    }
  } else if (idle) {
    l0 = 1.f; l1 = 1.f;
#pragma unroll 1
    for (int it = 0; it < NKV - 1; it++) { mbar_wait(a.full + 8 * (it & 3), (it >> 2) & 1); att_refill<false>(a, it); }
  } else {
    mbar_wait(a.full, 0);
    wg_fence(); att_qk(S, dQ, dKV + 3 * KV_STG); wg_commit(); wg_wait<0>();
    att_softmax<false>(S, P, O, m0, m1, l0, l1);
    mbar_wait(a.full + 8 * NSTG, 0);
    wg_fence(); att_pv(O, P, dKV + 3 * KV_STG + KV_VOFF); att_qk(S, dQ, dKV + 3 * KV_STG + KV_HALF); wg_commit(); wg_wait<0>();
#pragma unroll 1
    for (int it = 0; it < NKV - 1; it++) {
      const int sn = (it + 1) & 3;
      const uint32_t kb = dKV + kv_slot(it) * KV_STG, kn = dKV + kv_slot(it + 1) * KV_STG, par = ((it + 1) >> 2) & 1;
      att_softmax<false>(S, P, O, m0, m1, l0, l1);
      mbar_wait(a.full + 8 * sn, par);
      wg_fence(); att_pv(O, P, kb + KV_VOFF + KV_HALF); att_qk(S, dQ, kn); wg_commit(); wg_wait<0>();
      att_refill<false>(a, it);
      att_softmax<false>(S, P, O, m0, m1, l0, l1);
      mbar_wait(a.full + 8 * (NSTG + sn), par);
      wg_fence(); att_pv(O, P, kn + KV_VOFF); att_qk(S, dQ, kn + KV_HALF); wg_commit(); wg_wait<0>();
    }
    att_softmax<false>(S, P, O, m0, m1, l0, l1);
    wg_fence(); att_pv(O, P, dKV + 3 * KV_STG + KV_VOFF + KV_HALF); wg_commit(); wg_wait<0>();
  }
  l0 += __shfl_xor_sync(0xffffffff, l0, 1); l1 += __shfl_xor_sync(0xffffffff, l1, 1);
  l0 += __shfl_xor_sync(0xffffffff, l0, 2); l1 += __shfl_xor_sync(0xffffffff, l1, 2);
}

struct Wptrs { const void* p[8]; uint32_t bytes[8]; };

constexpr uint32_t B_FULL = 0, B_EMPTY = 8 * RING, B_X = 16 * RING, B_ADONE = B_X + 8, B_Q = B_X + 16, B_EP = B_X + 24, B_ATT = B_X + 32;

__global__ void __launch_bounds__(512, 1) conformer_kernel(const __grid_constant__ Maps tm, const __grid_constant__ Wptrs wp, const uint4* __restrict__ dw) {
  extern __shared__ uint8_t smem_raw[];
  const uint32_t base = (smem_u32(smem_raw) + 1023) & ~1023u, misc = base + OFF_MISC;
  const uint32_t bq = blockIdx.x / 19, br = blockIdx.x - bq * 19;
  const uint32_t bid = br == 18 ? ((bq & 1) ? 125 : 128) + (bq >> 1) : blockIdx.x - bq;
  if (bid >= NWORK) return;
  const int tile = bid;
  const bool has_tile = tile < NTILE;
  const int wg = __shfl_sync(0xffffffff, (int)(threadIdx.x >> 7), 0);
  AttCtx a;
  a.sKV = base + OFF_W; a.full = misc + B_ATT; a.empty = a.full + 16 * NSTG; a.tm = &tm;
  a.h = (bid >> 4) & 3; a.b = (bid >> 6) & 1; a.wg = wg; a.wfull = has_tile ? misc + B_FULL : 0;
  const int qt = bid & 15;

  if (threadIdx.x == 256) {
    mbar_init(misc + B_X, 1);
    for (int i = 0; i < RING; i++) { mbar_init(misc + B_FULL + 8 * i, 1); mbar_init(misc + B_EMPTY + 8 * i, 1); }
    asm volatile("fence.mbarrier_init.release.cluster;" ::: "memory");
    if (has_tile) {
      mbar_expect_tx(misc + B_X, 32768);
      tma_load_3d(base + OFF_X, &tm.X, misc + B_X, 0, tile * 64, 0);
    }
  } else if (threadIdx.x == 288) {
    mbar_init(misc + B_ADONE, 2);
    mbar_init(misc + B_Q, 1);
    mbar_init(misc + B_EP, 1);
    att_init_bars(a);
    asm volatile("fence.mbarrier_init.release.cluster;" ::: "memory");
  } else if (threadIdx.x >= 320 && threadIdx.x < 333) {
    prefetch_tmap(&tm.X + (threadIdx.x - 320));
  }
  __syncthreads();
  if ((threadIdx.x & 31) == 0 && threadIdx.x >= 256 && threadIdx.x < 256 + 32 * RING && has_tile) {
    const int i = (threadIdx.x - 256) >> 5;
    load_stage(base + OFF_W + i * STAGE, misc + B_FULL + 8 * i, tm, i);
  }
  __syncwarp();
  auto get_epoch = [&]() {
    uint32_t e;
    mbar_wait(misc + B_EP, 0);
    asm volatile("ld.shared.u32 %0, [%1];" : "=r"(e) : "r"(misc + 248) : "memory");
    return e;
  };

  if (wg < 2) {
    asm volatile("setmaxnreg.inc.sync.aligned.u32 232;");
    if (has_tile) {
      const Ctx c = make_ctx(base);
      if (c.wg == 1) turn_end(c);
      float own[64];
      float a0, b0, a1, b1;
      mbar_wait(misc + B_X, 0);
      load_half(c, c.sX, own);
      ln_stats(c, own, 0.5f, a0, b0, a1, b1);
      store_half(c, c.sA, own, a0, b0, a1, b1);
      fence_async_smem();
      bar_sync(1, 256);
      ff_block(c, 0, own);
      ln_stats(c, own, 1.f, a0, b0, a1, b1);
      store_half(c, c.sA, own, a0, b0, a1, b1);
      fence_async_smem();
      bar_sync(1, 256);
#pragma unroll 1
      for (int cc = 0; cc < 3; cc++) {
        float acc[64];
        const int j = 2 * cc + c.wg;
        gemm256<1>(c, acc, 32 + 2 * j, [&]() {
          if (c.tid == 0) {
            if (cc == 2) {
              bulk_wait_all();
              if (tile <= 62) cnt_signal(g_cnt1);
              if (tile >= 62) cnt_signal(g_cnt1 + 64);
            } else bulk_wait_read();
          }
          bar_sync(3 + c.wg, 128);
        });
        if (cc == 2) { bar_arrive(9, 288); if (c.tid == 0) mbar_arrive(misc + B_ADONE); }
        if (cc == 0) {
#pragma unroll
          for (int i = 0; i < 64; i++) acc[i] *= 0.125f * 1.4426950408889634f;
        }
        store_half_raw(c, c.sX, acc);
        fence_async_smem();
        bar_sync(3 + c.wg, 128);
        if (c.tid == 0) { tma_store_3d(&tm.QKVst, c.sX + c.wg * 16384, 0, tile * 64, 2 * j); bulk_commit(); }
      }
      if (c.tid == 0) bulk_wait_read();
      bar_sync(3 + c.wg, 128);
      store_half_raw(c, c.sX, own);
    }
    else bar_sync(3 + wg, 128);
    asm volatile("setmaxnreg.dec.sync.aligned.u32 128;");
    bar_arrive(7, 384); bar_arrive(8, 384);
    if (has_tile && (threadIdx.x & 127) == 0) {
      bulk_wait_all();
      if (tile <= 62) cnt_signal(g_cnt1 + 32);
      if (tile >= 62) cnt_signal(g_cnt1 + 96);
    }
    __syncwarp();
  } else {
    asm volatile("setmaxnreg.dec.sync.aligned.u32 24;");
    const uint32_t full = misc + B_FULL;
    if (threadIdx.x == 320) {
      const uint32_t e = atomicAdd(&g_start, 1) / NWORK;
      asm volatile("st.shared.u32 [%0], %1;" :: "r"(misc + 248), "r"(e + 1) : "memory");
      mbar_arrive(misc + B_EP);
    }
    if (threadIdx.x == 256) {
      if (has_tile) {
        produce(base + OFF_W, full, tm, RING, NA);
        mbar_wait(full + 8 * RING + 8 * 4, 1);
        mbar_arrive(full + 8 * 4); mbar_arrive(full + 8 * RING + 8 * 4);
        mbar_wait(misc + B_ADONE, 0);
      }
      cnt_wait(g_cnt1 + a.b * 64, 126 * get_epoch());
      mbar_expect_tx(misc + B_Q, 32768);
      tma_load_3d(base, &tm.Q, misc + B_Q, a.h * 64, qt * 256, a.b);
      att_load(a, 0, 0);
      mbar_wait(misc + B_Q, 0);
#pragma unroll 1
      for (int i = 1; i < NSTG; i++) att_load(a, i, 0);
    } else if ((threadIdx.x >> 5) == 12) {
      if (has_tile) bar_sync(9, 288);
      if (threadIdx.x == 384) {
        cnt_wait(g_cnt1 + a.b * 64 + 32, 126 * get_epoch());
        att_load(a, 0, 1);
        mbar_wait(a.full + 8 * NSTG, 0);
#pragma unroll 1
        for (int i = 1; i < NSTG; i++) att_load(a, i, 1);
      }
    } else if (has_tile && threadIdx.x >= 288 && threadIdx.x < 296) {
      const int w = threadIdx.x - 288;
      mbar_wait(misc + B_X, 0);
      const uint32_t bytes = wp.bytes[w], per = ((bytes / NTILE) + 127) & ~127u, off = per * tile;
      if (off < bytes) l2_prefetch((const uint8_t*)wp.p[w] + off, min(per, bytes - off));
    } else if (has_tile && threadIdx.x >= 416) {
      mbar_wait(full, 0);
      const int t = threadIdx.x - 416;
#pragma unroll 2
      for (int i = t; i < 2048; i += 96) g_att[tile * 2048 + i] = make_uint4(~0u, ~0u, ~0u, ~0u);
      g_halo[tile * 128 + t] = make_uint4(~0u, ~0u, ~0u, ~0u);
      if (t < 32) g_halo[tile * 128 + 96 + t] = make_uint4(~0u, ~0u, ~0u, ~0u);
    }
    __syncwarp();
    bar_sync(5 + wg, 384);
    asm volatile("setmaxnreg.inc.sync.aligned.u32 128;");
  }

  {
    const int lane = threadIdx.x & 31, wq = (threadIdx.x >> 5) & 3;
    const uint32_t dQ = dlo(base + wg * 8192, 16);
    float O[32], l0, l1;
    mbar_wait(misc + B_Q, 0);
    att_pass<false>(a, qt * 256 + wg * 64 >= T_, dQ, O, l0, l1);
    float z = 0.f;
#pragma unroll
    for (int i = 0; i < 32; i++) z = fmaf(O[i], 0.f, z);
    const bool ok = (l0 >= 0x1p-40f) && (l0 <= 0x1p80f) && (l1 >= 0x1p-40f) && (l1 <= 0x1p80f) && (z == 0.f);
    const bool warp_bad = !__all_sync(0xffffffff, ok);
    auto store_out = [&]() {
      const float i0 = 1.f / l0, i1 = 1.f / l1;
      const int row = qt * 256 + wg * 64 + wq * 16;
      if (row < T_) {
        const int slab = (a.b * T_ + row) / 16;
        uint4* op = g_att + (slab * 16 + a.h * 4) * 32 + lane;
#pragma unroll
        for (int j = 0; j < 4; j++)
          asm volatile("st.relaxed.gpu.global.v4.u32 [%0], {%1,%2,%3,%4};" :: "l"(op + j * 32),
                       "r"(pack_bf16(O[8 * j] * i0, O[8 * j + 1] * i0)), "r"(pack_bf16(O[8 * j + 2] * i1, O[8 * j + 3] * i1)),
                       "r"(pack_bf16(O[8 * j + 4] * i0, O[8 * j + 5] * i0)), "r"(pack_bf16(O[8 * j + 6] * i1, O[8 * j + 7] * i1)) : "memory");
      }
    };
    if (!warp_bad) store_out();
    if (__syncthreads_or(warp_bad)) {
      if (threadIdx.x == 0) {
        if (has_tile) { mbar_wait(misc + B_FULL, 1); mbar_wait(misc + B_FULL + 8, 1); }
        for (int i = 0; i < 3 * NSTG; i++) mbar_inval(a.full + 8 * i);
        att_init_bars(a);
        asm volatile("fence.mbarrier_init.release.cluster;" ::: "memory");
        fence_async_smem();
#pragma unroll 1
        for (int i = 0; i < NSTG; i++) att_load_stage(a, i);
      }
      __syncthreads();
      att_pass<true>(a, false, dQ, O, l0, l1);
      if (warp_bad) store_out();
      __syncthreads();
      if (has_tile) {
        if (threadIdx.x == 32) {
          load_stage(base + OFF_W, misc + B_X, tm, NC);
          load_stage(base + OFF_W + STAGE, misc + B_Q, tm, NC + 1);
        }
        mbar_wait(misc + B_X, 1); mbar_wait(misc + B_Q, 1);
      }
    }
  }
  if (!has_tile) return;

  if (wg < 2) {
    asm volatile("setmaxnreg.inc.sync.aligned.u32 232;");
    const Ctx c = make_ctx(base);
    float own[64];
    float a0, b0, a1, b1;
    {
      uint4 af[16];
      const int slab = tile * 4 + (c.tid >> 5);
      const uint4* ap = g_att + slab * 512 + c.lane;
#pragma unroll
      for (int i = 0; i < 16; i++)
        asm volatile("ld.global.ca.v4.u32 {%0,%1,%2,%3}, [%4];" : "=r"(af[i].x), "=r"(af[i].y), "=r"(af[i].z), "=r"(af[i].w) : "l"(ap + i * 32) : "memory");
      load_half(c, c.sX, own);
      uint32_t miss = 15;
      for (uint32_t n = 0; n < (1u << 18); n++) {
#pragma unroll
        for (int hh = 0; hh < 4; hh++)
          if ((miss >> hh) & 1) {
            uint32_t mx = 0;
#pragma unroll
            for (int i = 4 * hh; i < 4 * hh + 4; i++) mx = max(mx, max(max(af[i].x, af[i].y), max(af[i].z, af[i].w)));
            if (__any_sync(0xffffffff, mx == ~0u)) {
#pragma unroll
              for (int i = 4 * hh; i < 4 * hh + 4; i++)
                asm volatile("ld.relaxed.gpu.global.v4.u32 {%0,%1,%2,%3}, [%4];" : "=r"(af[i].x), "=r"(af[i].y), "=r"(af[i].z), "=r"(af[i].w) : "l"(ap + i * 32) : "memory");
            } else miss &= ~(1u << hh);
          }
        if (!miss) break;
      }
      const int n = NC + 2 * c.wg;
      uint32_t b = stage_wait(c, n) + ((16384 >> 4) << 16);
      turn_begin(c);
      wg_fence();
#pragma unroll
      for (int kk = 0; kk < 8; kk++) wg_rs_n128_tb1<1>(own, af[kk].x, af[kk].y, af[kk].z, af[kk].w, b + kk * 128);
      wg_commit();
      b = stage_wait(c, n + 1) + ((16384 >> 4) << 16);
      wg_fence();
#pragma unroll
      for (int kk = 0; kk < 8; kk++) wg_rs_n128_tb1<1>(own, af[8 + kk].x, af[8 + kk].y, af[8 + kk].z, af[8 + kk].w, b + kk * 128);
      wg_commit();
      turn_end(c);
      wg_wait<1>(); stage_release(c, n);
      wg_wait<0>(); stage_release(c, n + 1);
    }
    ln_stats(c, own, 0.5f, a0, b0, a1, b1);
    store_half(c, c.sA, own, a0, b0, a1, b1);
    fence_async_smem();
    bar_sync(1, 256);
    uint4 dwr[5];
#pragma unroll
    for (int i = 0; i < 5; i++) dwr[i] = __ldg(dw + i * 32 + c.wg * 16 + (c.lane & 15));
    const bool top = c.tid < 8, pub = (top || c.tid >= 120);
    uint32_t* halo_out = (uint32_t*)g_halo + (tile * 4 + (top ? (c.tid >> 2) : ((c.tid >> 2) - 28))) * 128 + c.wg * 64 + (c.lane & 3);
#pragma unroll 1
    for (int q = 0; q < 2; q++) {
      float ab[64];
      gemm256<1>(c, ab, NC + 4 + 4 * q + 2 * c.wg);
#pragma unroll
      for (int j = 0; j < 4; j++) {
        float g[8];
#pragma unroll
        for (int i = 0; i < 8; i++) g[i] = fmaf(ab[8 * j + i], tanh_fast(ab[32 + 8 * j + i]), ab[8 * j + i]);
        const uint32_t p0 = pack_bf16(g[0], g[1]), p1 = pack_bf16(g[2], g[3]), p2 = pack_bf16(g[4], g[5]), p3 = pack_bf16(g[6], g[7]);
        if (pub) {
          uint32_t* hp = halo_out + q * 32 + j * 8;
          asm volatile("st.relaxed.gpu.global.u32 [%0], %1;" :: "l"(hp), "r"(top ? p0 : p1) : "memory");
          asm volatile("st.relaxed.gpu.global.u32 [%0], %1;" :: "l"(hp + 4), "r"(top ? p2 : p3) : "memory");
        }
        stsm_x4(c.sX + (2 * c.wg + q) * 8192 + c.frag + (((j * 2 + c.hi) ^ c.rsw) << 4), p0, p1, p2, p3);
      }
    }
    bar_sync(3 + c.wg, 128);
    {
      const int wi = c.tid >> 4;
      const uint32_t col = (2 * c.wg + ((c.lane >> 3) & 1)) * 8192, ch = c.lane & 7;
      uint4 r[12];
      const int R0 = tile * 64 + wi * 8;
      const bool first = (R0 % T_) == 0, last = ((R0 + 8) % T_) == 0;
      const bool far = ((wi == 0 && !first) || (wi == 7 && !last));
      const uint4* sp = g_halo + (wi == 0 ? (tile - 1) * 4 + 2 : (tile + 1) * 4) * 32 + c.wg * 16 + (c.lane & 15);
      uint4 h0 = make_uint4(0, 0, 0, 0), h1 = h0;
      auto ld_halo = [&]() {
        asm volatile("ld.relaxed.gpu.global.v4.u32 {%0,%1,%2,%3}, [%4];" : "=r"(h0.x), "=r"(h0.y), "=r"(h0.z), "=r"(h0.w) : "l"(sp) : "memory");
        asm volatile("ld.relaxed.gpu.global.v4.u32 {%0,%1,%2,%3}, [%4];" : "=r"(h1.x), "=r"(h1.y), "=r"(h1.z), "=r"(h1.w) : "l"(sp + 32) : "memory");
      };
      if (far) ld_halo();
#pragma unroll
      for (int i = 0; i < 12; i++) {
        const int row = (wi * 8 - 2 + i) & 63;
        r[i] = lds128(c.sX + col + row * 128 + ((ch ^ (row & 7)) << 4));
      }
      uint32_t w[5][4];
#pragma unroll
      for (int k = 0; k < 5; k++) {
        w[k][0] = bmul2(dwr[k].x, 0x3F003F00u); w[k][1] = bmul2(dwr[k].y, 0x3F003F00u);
        w[k][2] = bmul2(dwr[k].z, 0x3F003F00u); w[k][3] = bmul2(dwr[k].w, 0x3F003F00u);
      }
      auto conv4 = [&](int i0, int i1, int i2, int i3, bool sync) {
        const int rows[4] = {i0, i1, i2, i3};
        uint32_t acc[4][4];
#pragma unroll
        for (int k = 0; k < 5; k++)
#pragma unroll
          for (int j = 0; j < 4; j++) {
            const uint4 x = r[rows[j] + k];
            acc[j][0] = k ? bfma2(x.x, w[k][0], acc[j][0]) : bmul2(x.x, w[0][0]);
            acc[j][1] = k ? bfma2(x.y, w[k][1], acc[j][1]) : bmul2(x.y, w[0][1]);
            acc[j][2] = k ? bfma2(x.z, w[k][2], acc[j][2]) : bmul2(x.z, w[0][2]);
            acc[j][3] = k ? bfma2(x.w, w[k][3], acc[j][3]) : bmul2(x.w, w[0][3]);
          }
#pragma unroll
        for (int j = 0; j < 4; j++)
#pragma unroll
          for (int q = 0; q < 4; q++) acc[j][q] = pack_bf16(silu_half(bf_lo(acc[j][q])), silu_half(bf_hi(acc[j][q])));
        if (sync) bar_sync(3 + c.wg, 128);
#pragma unroll
        for (int j = 0; j < 4; j++)
          sts128(c.sX + col + (wi * 8 + rows[j]) * 128 + ((ch ^ rows[j]) << 4), make_uint4(acc[j][0], acc[j][1], acc[j][2], acc[j][3]));
      };
      conv4(2, 3, 4, 5, true);
      if (far) {
        for (uint32_t n = 0; n < (1u << 18); n++) {
          const uint32_t mx = max(max(max(h0.x, h0.y), max(h0.z, h0.w)), max(max(h1.x, h1.y), max(h1.z, h1.w)));
          if (mx != ~0u) break;
          ld_halo();
        }
      }
      __syncwarp();
      if (first || (far && wi == 0)) { r[0] = h0; r[1] = h1; }
      if (last || (far && wi == 7)) { r[10] = h0; r[11] = h1; }
      conv4(0, 1, 6, 7, false);
    }
    fence_async_smem();
    bar_sync(c.wg == 0 ? 3 : 1, c.wg == 0 ? 128 : 256);
    {
      uint32_t b = stage_wait(c, NC + 12 + c.wg);
      turn_begin(c);
      wg_fence(); piece_ss<0, 0>(c, own, dlo(c.sX, 16), b); wg_commit();
      if (c.wg == 0) { turn_end(c); bar_sync(1, 256); turn_begin(c); }
      b = stage_wait(c, NC + 14 + c.wg);
      wg_fence(); piece_ss<0, 1>(c, own, dlo(c.sX, 16) + 1024, b); wg_commit();
    }
    wg_wait<1>(); stage_release(c, NC + 12 + c.wg);
    wg_wait<0>(); stage_release(c, NC + 14 + c.wg);
    ln_stats(c, own, 0.5f, a0, b0, a1, b1);
    if (c.wg == 1) { turn_begin(c); turn_end(c); }
    store_half(c, c.sA, own, a0, b0, a1, b1);
    fence_async_smem();
    bar_sync(1, 256);
    ff_block(c, NC + 16, own);
    ln_stats(c, own, 1.f, a0, b0, a1, b1);
    store_half(c, c.sX, own, a0, b0, a1, b1);
    fence_async_smem();
    bar_sync(3 + c.wg, 128);
    if (c.tid == 0) { tma_store_3d(&tm.Out, c.sX + c.wg * 16384, 0, tile * 64, 2 * c.wg); bulk_commit(); bulk_wait_read(); }
  } else {
    asm volatile("setmaxnreg.dec.sync.aligned.u32 24;");
    if (threadIdx.x == 256) {
      __nanosleep(200);
      produce(base + OFF_W, misc + B_FULL, tm, NC + 2, NC + 48);
    }
  }
}

typedef CUresult (*EncodeFn)(CUtensorMap*, CUtensorMapDataType, cuuint32_t, void*, const cuuint64_t*, const cuuint64_t*, const cuuint32_t*,
                             const cuuint32_t*, CUtensorMapInterleave, CUtensorMapSwizzle, CUtensorMapL2promotion, CUtensorMapFloatOOBfill);

CUtensorMap make_map(EncodeFn enc, const void* p, uint64_t d0, uint64_t d1, uint64_t d2, uint64_t s1, uint64_t s2, uint32_t b1, uint32_t b2) {
  CUtensorMap tm;
  cuuint64_t dims[3] = {d0, d1, d2};
  cuuint64_t strides[2] = {s1, s2};
  cuuint32_t box[3] = {64, b1, b2};
  cuuint32_t es[3] = {1, 1, 1};
  enc(&tm, CU_TENSOR_MAP_DATA_TYPE_BFLOAT16, 3, const_cast<void*>(p), dims, strides, box, es, CU_TENSOR_MAP_INTERLEAVE_NONE,
      CU_TENSOR_MAP_SWIZZLE_128B, CU_TENSOR_MAP_L2_PROMOTION_L2_256B, CU_TENSOR_MAP_FLOAT_OOB_FILL_NONE);
  return tm;
}
CUtensorMap blk_map(EncodeFn enc, const void* p, uint64_t rows, uint64_t cols, uint32_t boxrows, uint32_t boxblks) {
  return make_map(enc, p, 64, rows, cols / 64, cols * 2, 128, boxrows, boxblks);
}
CUtensorMap seq_map(EncodeFn enc, const void* p, uint64_t cols, uint32_t boxrows) {
  return make_map(enc, p, cols, T_, 2, cols * 2, cols * 2 * T_, boxrows, 1);
}

}

extern "C" void kernel_launch(void* const* d_in, const int* in_sizes, int n_in, void* d_out, int out_size) {
  (void)in_sizes; (void)n_in; (void)out_size;
  const void *x = d_in[0], *w1a = d_in[1], *w1b = d_in[2], *wqkv = d_in[3], *wo = d_in[4], *pw1 = d_in[5], *dw = d_in[6], *pw2 = d_in[7],
             *w2a = d_in[8], *w2b = d_in[9];
  void* fn = nullptr;
  cudaDriverEntryPointQueryResult qr;
  cudaGetDriverEntryPoint("cuTensorMapEncodeTiled", &fn, cudaEnableDefault, &qr);
  EncodeFn enc = (EncodeFn)fn;
  void* qkv;
  cudaGetSymbolAddress(&qkv, g_qkv);
  cudaFuncSetAttribute(conformer_kernel, cudaFuncAttributeMaxDynamicSharedMemorySize, SMEM_BYTES);

  Wptrs wp;
  const void* ws[8] = {w1a, w1b, wqkv, wo, pw1, pw2, w2a, w2b};
  const uint32_t wb[8] = {524288, 524288, 393216, 131072, 262144, 131072, 524288, 524288};
  for (int i = 0; i < 8; i++) { wp.p[i] = ws[i]; wp.bytes[i] = wb[i]; }
  Maps tm;
  const uint16_t tab[92] = STAGE_TABLE;
  for (int i = 0; i < 92; i++) tm.stage[i] = tab[i];
  tm.X = blk_map(enc, x, ROWS, 256, 64, 4);
  tm.W1a = blk_map(enc, w1a, 256, 1024, 256, 1);
  tm.W1b = blk_map(enc, w1b, 1024, 256, 64, 4);
  tm.Wqkv = blk_map(enc, wqkv, 256, 768, 128, 2);
  tm.QKVst = blk_map(enc, qkv, ROWS, 768, 64, 2);
  tm.Q = seq_map(enc, qkv, 768, 256);
  tm.KV = seq_map(enc, qkv, 768, 160);
  tm.Wo = blk_map(enc, wo, 256, 256, 128, 2);
  tm.Pw1 = make_map(enc, pw1, 256, 256, 2, 1024, 512, 128, 2);
  tm.Pw2 = blk_map(enc, pw2, 256, 256, 128, 2);
  tm.W2a = blk_map(enc, w2a, 256, 1024, 256, 1);
  tm.W2b = blk_map(enc, w2b, 1024, 256, 64, 4);
  tm.Out = blk_map(enc, d_out, ROWS, 256, 64, 2);
  conformer_kernel<<<NCTA, 512, SMEM_BYTES, cudaStreamPerThread>>>(tm, wp, (const uint4*)dw);
}
```

```cpp
#include <cuda_runtime.h>
#include <cuda_bf16.h>
#include <cuda.h>
#include <stdint.h>

namespace {

constexpr int T_ = 4000;
constexpr int ROWS = 8000;
constexpr int NTILE = 125;
constexpr int NWORK = 128;
constexpr int NCTA = 131;

__device__ __align__(128) __nv_bfloat16 g_qkv[ROWS * 768];
__device__ uint4 g_att[(ROWS / 16) * 16 * 32];
__device__ uint4 g_halo[NTILE * 4 * 32];
__device__ uint32_t g_start;
__device__ uint32_t g_cnt1[4 * 32];


__device__ __forceinline__ uint32_t smem_u32(const void* p) { return (uint32_t)__cvta_generic_to_shared(p); }
__device__ __forceinline__ void mbar_init(uint32_t bar, uint32_t cnt) { asm volatile("mbarrier.init.shared::cta.b64 [%0], %1;" :: "r"(bar), "r"(cnt) : "memory"); }
__device__ __forceinline__ void mbar_inval(uint32_t bar) { asm volatile("mbarrier.inval.shared::cta.b64 [%0];" :: "r"(bar) : "memory"); }
__device__ __forceinline__ void mbar_expect_tx(uint32_t bar, uint32_t bytes) { asm volatile("mbarrier.arrive.expect_tx.shared::cta.b64 _, [%0], %1;" :: "r"(bar), "r"(bytes) : "memory"); }
__device__ __forceinline__ void mbar_arrive(uint32_t bar) { asm volatile("mbarrier.arrive.shared::cta.b64 _, [%0];" :: "r"(bar) : "memory"); }
__device__ __forceinline__ void mbar_wait(uint32_t bar, uint32_t parity) {
  asm volatile("{\n.reg .pred p;\n.reg .u32 n;\n"
               "mbarrier.try_wait.parity.shared::cta.b64 p, [%0], %1;\n@p bra DONE_%=;\nmov.u32 n, 0;\n"
               "LOOP_%=:\nmbarrier.try_wait.parity.shared::cta.b64 p, [%0], %1;\n@p bra DONE_%=;\n"
               "add.u32 n, n, 1;\nsetp.lt.u32 p, n, 262144;\n@p bra LOOP_%=;\ntrap;\nDONE_%=:\n}\n" :: "r"(bar), "r"(parity) : "memory");
}
__device__ __forceinline__ void cnt_wait(const uint32_t* p, uint32_t target) {
  asm volatile("{\n.reg .pred p;\n.reg .u32 n, v;\nmov.u32 n, 0;\n"
               "LOOP_%=:\nld.relaxed.gpu.global.u32 v, [%0];\nsub.u32 v, v, %1;\nsetp.ge.s32 p, v, 0;\n@p bra DONE_%=;\n"
               "nanosleep.u32 40;\nadd.u32 n, n, 1;\nsetp.lt.u32 p, n, 262144;\n@p bra LOOP_%=;\ntrap;\nDONE_%=:\n}\n" :: "l"(p), "r"(target) : "memory");
}
__device__ __forceinline__ void cnt_signal(uint32_t* p) {
  asm volatile("red.relaxed.gpu.global.add.u32 [%0], 1;" :: "l"(p) : "memory");
}
__device__ __forceinline__ void tma_load_3d(uint32_t dst, const CUtensorMap* tm, uint32_t bar, int c0, int c1, int c2) {
  asm volatile("cp.async.bulk.tensor.3d.shared::cluster.global.mbarrier::complete_tx::bytes [%0], [%1, {%3, %4, %5}], [%2];"
    :: "r"(dst), "l"(tm), "r"(bar), "r"(c0), "r"(c1), "r"(c2) : "memory");
}
__device__ __forceinline__ void tma_store_3d(const CUtensorMap* tm, uint32_t src, int c0, int c1, int c2) {
  asm volatile("cp.async.bulk.tensor.3d.global.shared::cta.bulk_group [%0, {%2, %3, %4}], [%1];" :: "l"(tm), "r"(src), "r"(c0), "r"(c1), "r"(c2) : "memory");
}
__device__ __forceinline__ void bulk_commit() { asm volatile("cp.async.bulk.commit_group;" ::: "memory"); }
__device__ __forceinline__ void bulk_wait_read() { asm volatile("cp.async.bulk.wait_group.read 0;" ::: "memory"); }
__device__ __forceinline__ void bulk_wait_all() { asm volatile("cp.async.bulk.wait_group 0;" ::: "memory"); }
__device__ __forceinline__ void l2_prefetch(const void* p, uint32_t bytes) { asm volatile("cp.async.bulk.prefetch.L2.global [%0], %1;" :: "l"(p), "r"(bytes) : "memory"); }
__device__ __forceinline__ void prefetch_tmap(const CUtensorMap* tm) { asm volatile("prefetch.tensormap [%0];" :: "l"(tm) : "memory"); }
__device__ __forceinline__ void fence_async_smem() { asm volatile("fence.proxy.async.shared::cta;" ::: "memory"); }
__device__ __forceinline__ void wg_fence() { asm volatile("wgmma.fence.sync.aligned;" ::: "memory"); }
__device__ __forceinline__ void wg_commit() { asm volatile("wgmma.commit_group.sync.aligned;" ::: "memory"); }
template<int N> __device__ __forceinline__ void wg_wait() { asm volatile("wgmma.wait_group.sync.aligned %0;" :: "n"(N) : "memory"); }
__device__ __forceinline__ void bar_sync(int id, int n) { asm volatile("bar.sync %0, %1;" :: "r"(id), "r"(n) : "memory"); }
__device__ __forceinline__ void bar_arrive(int id, int n) { asm volatile("bar.arrive %0, %1;" :: "r"(id), "r"(n) : "memory"); }
__device__ __forceinline__ float ex2(float x) { float y; asm("ex2.approx.ftz.f32 %0, %1;" : "=f"(y) : "f"(x)); return y; }
__device__ __forceinline__ float rcp_fast(float x) { float y; asm("rcp.approx.ftz.f32 %0, %1;" : "=f"(y) : "f"(x)); return y; }
__device__ __forceinline__ float rsqrt_fast(float x) { float y; asm("rsqrt.approx.ftz.f32 %0, %1;" : "=f"(y) : "f"(x)); return y; }
__device__ __forceinline__ float tanh_fast(float x) { float y; asm("tanh.approx.f32 %0, %1;" : "=f"(y) : "f"(x)); return y; }
__device__ __forceinline__ uint32_t pack_bf16(float lo, float hi) { uint32_t r; asm("cvt.rn.bf16x2.f32 %0, %1, %2;" : "=r"(r) : "f"(hi), "f"(lo)); return r; }
__device__ __forceinline__ uint32_t bmul2(uint32_t a, uint32_t b) { uint32_t d; asm("mul.rn.bf16x2 %0, %1, %2;" : "=r"(d) : "r"(a), "r"(b)); return d; }
__device__ __forceinline__ uint32_t bfma2(uint32_t a, uint32_t b, uint32_t c) { uint32_t d; asm("fma.rn.bf16x2 %0, %1, %2, %3;" : "=r"(d) : "r"(a), "r"(b), "r"(c)); return d; }
__device__ __forceinline__ float bf_lo(uint32_t u) { return __uint_as_float(u << 16); }
__device__ __forceinline__ float bf_hi(uint32_t u) { return __uint_as_float(u & 0xffff0000u); }
__device__ __forceinline__ void ldsm_x4(uint32_t addr, uint32_t& r0, uint32_t& r1, uint32_t& r2, uint32_t& r3) {
  asm volatile("ldmatrix.sync.aligned.m8n8.x4.shared.b16 {%0,%1,%2,%3}, [%4];" : "=r"(r0), "=r"(r1), "=r"(r2), "=r"(r3) : "r"(addr) : "memory");
}
__device__ __forceinline__ void stsm_x4(uint32_t addr, uint32_t r0, uint32_t r1, uint32_t r2, uint32_t r3) {
  asm volatile("stmatrix.sync.aligned.m8n8.x4.shared.b16 [%0], {%1,%2,%3,%4};" :: "r"(addr), "r"(r0), "r"(r1), "r"(r2), "r"(r3) : "memory");
}
__device__ __forceinline__ void sts128(uint32_t addr, uint4 v) { asm volatile("st.shared.v4.b32 [%0], {%1,%2,%3,%4};" :: "r"(addr), "r"(v.x), "r"(v.y), "r"(v.z), "r"(v.w) : "memory"); }
__device__ __forceinline__ uint4 lds128(uint32_t addr) { uint4 v; asm volatile("ld.shared.v4.b32 {%0,%1,%2,%3}, [%4];" : "=r"(v.x), "=r"(v.y), "=r"(v.z), "=r"(v.w) : "r"(addr) : "memory"); return v; }
__device__ __forceinline__ void sts64f(uint32_t addr, float a, float b) { asm volatile("st.shared.v2.f32 [%0], {%1,%2};" :: "r"(addr), "f"(a), "f"(b) : "memory"); }
__device__ __forceinline__ float2 lds64f(uint32_t addr) { float2 v; asm volatile("ld.shared.v2.f32 {%0,%1}, [%2];" : "=f"(v.x), "=f"(v.y) : "r"(addr) : "memory"); return v; }
__device__ __forceinline__ uint32_t dlo(uint32_t addr, uint32_t lbo) { return ((addr & 0x3FFFF) >> 4) | ((lbo >> 4) << 16); }

template<int SD> __device__ __forceinline__ void wg_ss_n128_tb1(float (&d)[64], uint32_t da, uint32_t db) {
  asm volatile("{\n.reg .b64 da, db;\nmov.b64 da, {%64, 0x40000040};\nmov.b64 db, {%65, 0x40000040};\n"
    "wgmma.mma_async.sync.aligned.m64n128k16.f32.bf16.bf16 {%0, %1, %2, %3, %4, %5, %6, %7, %8, %9, %10, %11, %12, %13, %14, %15, %16, %17, %18, %19, %20, %21, %22, %23, %24, %25, %26, %27, %28, %29, %30, %31, %32, %33, %34, %35, %36, %37, %38, %39, %40, %41, %42, %43, %44, %45, %46, %47, %48, %49, %50, %51, %52, %53, %54, %55, %56, %57, %58, %59, %60, %61, %62, %63}, da, db, %66, 1, 1, 0, 1;\n}\n"
    : "+f"(d[0]), "+f"(d[1]), "+f"(d[2]), "+f"(d[3]), "+f"(d[4]), "+f"(d[5]), "+f"(d[6]), "+f"(d[7]), "+f"(d[8]), "+f"(d[9]), "+f"(d[10]), "+f"(d[11]), "+f"(d[12]), "+f"(d[13]), "+f"(d[14]), "+f"(d[15]), "+f"(d[16]), "+f"(d[17]), "+f"(d[18]), "+f"(d[19]), "+f"(d[20]), "+f"(d[21]), "+f"(d[22]), "+f"(d[23]), "+f"(d[24]), "+f"(d[25]), "+f"(d[26]), "+f"(d[27]), "+f"(d[28]), "+f"(d[29]), "+f"(d[30]), "+f"(d[31]), "+f"(d[32]), "+f"(d[33]), "+f"(d[34]), "+f"(d[35]), "+f"(d[36]), "+f"(d[37]), "+f"(d[38]), "+f"(d[39]), "+f"(d[40]), "+f"(d[41]), "+f"(d[42]), "+f"(d[43]), "+f"(d[44]), "+f"(d[45]), "+f"(d[46]), "+f"(d[47]), "+f"(d[48]), "+f"(d[49]), "+f"(d[50]), "+f"(d[51]), "+f"(d[52]), "+f"(d[53]), "+f"(d[54]), "+f"(d[55]), "+f"(d[56]), "+f"(d[57]), "+f"(d[58]), "+f"(d[59]), "+f"(d[60]), "+f"(d[61]), "+f"(d[62]), "+f"(d[63])
    : "r"(da), "r"(db), "n"(SD));
}
template<int SD> __device__ __forceinline__ void wg_rs_n128_tb1(float (&d)[64], uint32_t a0, uint32_t a1, uint32_t a2, uint32_t a3, uint32_t db) {
  asm volatile("{\n.reg .b64 db;\nmov.b64 db, {%68, 0x40000040};\n"
    "wgmma.mma_async.sync.aligned.m64n128k16.f32.bf16.bf16 {%0, %1, %2, %3, %4, %5, %6, %7, %8, %9, %10, %11, %12, %13, %14, %15, %16, %17, %18, %19, %20, %21, %22, %23, %24, %25, %26, %27, %28, %29, %30, %31, %32, %33, %34, %35, %36, %37, %38, %39, %40, %41, %42, %43, %44, %45, %46, %47, %48, %49, %50, %51, %52, %53, %54, %55, %56, %57, %58, %59, %60, %61, %62, %63}, {%64, %65, %66, %67}, db, %69, 1, 1, 1;\n}\n"
    : "+f"(d[0]), "+f"(d[1]), "+f"(d[2]), "+f"(d[3]), "+f"(d[4]), "+f"(d[5]), "+f"(d[6]), "+f"(d[7]), "+f"(d[8]), "+f"(d[9]), "+f"(d[10]), "+f"(d[11]), "+f"(d[12]), "+f"(d[13]), "+f"(d[14]), "+f"(d[15]), "+f"(d[16]), "+f"(d[17]), "+f"(d[18]), "+f"(d[19]), "+f"(d[20]), "+f"(d[21]), "+f"(d[22]), "+f"(d[23]), "+f"(d[24]), "+f"(d[25]), "+f"(d[26]), "+f"(d[27]), "+f"(d[28]), "+f"(d[29]), "+f"(d[30]), "+f"(d[31]), "+f"(d[32]), "+f"(d[33]), "+f"(d[34]), "+f"(d[35]), "+f"(d[36]), "+f"(d[37]), "+f"(d[38]), "+f"(d[39]), "+f"(d[40]), "+f"(d[41]), "+f"(d[42]), "+f"(d[43]), "+f"(d[44]), "+f"(d[45]), "+f"(d[46]), "+f"(d[47]), "+f"(d[48]), "+f"(d[49]), "+f"(d[50]), "+f"(d[51]), "+f"(d[52]), "+f"(d[53]), "+f"(d[54]), "+f"(d[55]), "+f"(d[56]), "+f"(d[57]), "+f"(d[58]), "+f"(d[59]), "+f"(d[60]), "+f"(d[61]), "+f"(d[62]), "+f"(d[63])
    : "r"(a0), "r"(a1), "r"(a2), "r"(a3), "r"(db), "n"(SD));
}
template<int SD> __device__ __forceinline__ void wg_ss_n64_tb1(float (&d)[32], uint32_t da, uint32_t db) {
  asm volatile("{\n.reg .b64 da, db;\nmov.b64 da, {%32, 0x40000040};\nmov.b64 db, {%33, 0x40000040};\n"
    "wgmma.mma_async.sync.aligned.m64n64k16.f32.bf16.bf16 {%0, %1, %2, %3, %4, %5, %6, %7, %8, %9, %10, %11, %12, %13, %14, %15, %16, %17, %18, %19, %20, %21, %22, %23, %24, %25, %26, %27, %28, %29, %30, %31}, da, db, %34, 1, 1, 0, 1;\n}\n"
    : "+f"(d[0]), "+f"(d[1]), "+f"(d[2]), "+f"(d[3]), "+f"(d[4]), "+f"(d[5]), "+f"(d[6]), "+f"(d[7]), "+f"(d[8]), "+f"(d[9]), "+f"(d[10]), "+f"(d[11]), "+f"(d[12]), "+f"(d[13]), "+f"(d[14]), "+f"(d[15]), "+f"(d[16]), "+f"(d[17]), "+f"(d[18]), "+f"(d[19]), "+f"(d[20]), "+f"(d[21]), "+f"(d[22]), "+f"(d[23]), "+f"(d[24]), "+f"(d[25]), "+f"(d[26]), "+f"(d[27]), "+f"(d[28]), "+f"(d[29]), "+f"(d[30]), "+f"(d[31])
    : "r"(da), "r"(db), "n"(SD));
}
template<int SD> __device__ __forceinline__ void wg_ss_n80_tb0(float (&d)[40], uint32_t da, uint32_t db) {
  asm volatile("{\n.reg .b64 da, db;\nmov.b64 da, {%40, 0x40000040};\nmov.b64 db, {%41, 0x40000040};\n"
    "wgmma.mma_async.sync.aligned.m64n80k16.f32.bf16.bf16 {%0, %1, %2, %3, %4, %5, %6, %7, %8, %9, %10, %11, %12, %13, %14, %15, %16, %17, %18, %19, %20, %21, %22, %23, %24, %25, %26, %27, %28, %29, %30, %31, %32, %33, %34, %35, %36, %37, %38, %39}, da, db, %42, 1, 1, 0, 0;\n}\n"
    : "+f"(d[0]), "+f"(d[1]), "+f"(d[2]), "+f"(d[3]), "+f"(d[4]), "+f"(d[5]), "+f"(d[6]), "+f"(d[7]), "+f"(d[8]), "+f"(d[9]), "+f"(d[10]), "+f"(d[11]), "+f"(d[12]), "+f"(d[13]), "+f"(d[14]), "+f"(d[15]), "+f"(d[16]), "+f"(d[17]), "+f"(d[18]), "+f"(d[19]), "+f"(d[20]), "+f"(d[21]), "+f"(d[22]), "+f"(d[23]), "+f"(d[24]), "+f"(d[25]), "+f"(d[26]), "+f"(d[27]), "+f"(d[28]), "+f"(d[29]), "+f"(d[30]), "+f"(d[31]), "+f"(d[32]), "+f"(d[33]), "+f"(d[34]), "+f"(d[35]), "+f"(d[36]), "+f"(d[37]), "+f"(d[38]), "+f"(d[39])
    : "r"(da), "r"(db), "n"(SD));
}
template<int SD> __device__ __forceinline__ void wg_rs_n64_tb1(float (&d)[32], uint32_t a0, uint32_t a1, uint32_t a2, uint32_t a3, uint32_t db) {
  asm volatile("{\n.reg .b64 db;\nmov.b64 db, {%36, 0x40000040};\n"
    "wgmma.mma_async.sync.aligned.m64n64k16.f32.bf16.bf16 {%0, %1, %2, %3, %4, %5, %6, %7, %8, %9, %10, %11, %12, %13, %14, %15, %16, %17, %18, %19, %20, %21, %22, %23, %24, %25, %26, %27, %28, %29, %30, %31}, {%32, %33, %34, %35}, db, %37, 1, 1, 1;\n}\n"
    : "+f"(d[0]), "+f"(d[1]), "+f"(d[2]), "+f"(d[3]), "+f"(d[4]), "+f"(d[5]), "+f"(d[6]), "+f"(d[7]), "+f"(d[8]), "+f"(d[9]), "+f"(d[10]), "+f"(d[11]), "+f"(d[12]), "+f"(d[13]), "+f"(d[14]), "+f"(d[15]), "+f"(d[16]), "+f"(d[17]), "+f"(d[18]), "+f"(d[19]), "+f"(d[20]), "+f"(d[21]), "+f"(d[22]), "+f"(d[23]), "+f"(d[24]), "+f"(d[25]), "+f"(d[26]), "+f"(d[27]), "+f"(d[28]), "+f"(d[29]), "+f"(d[30]), "+f"(d[31])
    : "r"(a0), "r"(a1), "r"(a2), "r"(a3), "r"(db), "n"(SD));
}


constexpr int RING = 5;
constexpr uint32_t STAGE = 32768;
constexpr uint32_t OFF_X = 32768, OFF_W = 65536, OFF_MISC = OFF_W + RING * STAGE;
constexpr int SMEM_BYTES = OFF_MISC + 256 + 1024 + 1024;

struct Ctx {
  uint32_t sA, sX, sW, full, empty, stats;
  uint32_t frag;
  uint32_t rsw;
  uint32_t hi;
  int wg, tid, lane;
};
__device__ __forceinline__ uint32_t stage_wait(const Ctx& c, int n) {
  const int q = n / RING, s = n - q * RING;
  mbar_wait(c.full + 8 * s, q & 1);
  return dlo(c.sW + s * STAGE, 0);
}
__device__ __forceinline__ void stage_release(const Ctx& c, int n) {
  const int s = n % RING;
  if (c.tid == 0) mbar_arrive(c.empty + 8 * s);
}
__device__ __forceinline__ void turn_begin(const Ctx& c) { bar_sync(5 + c.wg, 256); }
__device__ __forceinline__ void turn_end(const Ctx& c) { bar_arrive(5 + (c.wg ^ 1), 256); }
template<int FIRST, int LAST> __device__ __forceinline__ void piece_ss(const Ctx& c, float (&acc)[64], uint32_t dA, uint32_t dB) {
  dB += (16384 >> 4) << 16;
  wg_ss_n128_tb1<FIRST ? 0 : 1>(acc, dA, dB);
#pragma unroll
  for (int kk = 1; kk < 8; kk++) {
    wg_ss_n128_tb1<1>(acc, dA + (kk >> 2) * 512 + (kk & 3) * 2, dB + kk * 128);
  }
  if (LAST) turn_end(c);
}
__device__ __forceinline__ void ff_g1(const Ctx& c, float (&h)[32], uint32_t dA, uint32_t dB) {
  wg_ss_n64_tb1<0>(h, dA, dB);
#pragma unroll
  for (int kk = 1; kk < 16; kk++) {
    wg_ss_n64_tb1<1>(h, dA + (kk >> 2) * 512 + (kk & 3) * 2, dB + kk * 128);
  }
}
__device__ __forceinline__ void ff_g2(float (&acc)[64], const uint32_t (&P)[16], uint32_t dB, int half) {
  dB += ((8192 >> 4) << 16) + half * 1024;
#pragma unroll
  for (int kk = 0; kk < 4; kk++) wg_rs_n128_tb1<1>(acc, P[4 * kk], P[4 * kk + 1], P[4 * kk + 2], P[4 * kk + 3], dB + kk * 128);
}
struct NoHook { __device__ __forceinline__ void operator()() const {} };
template<int FIRST, class Hook = NoHook> __device__ __forceinline__ void gemm256(const Ctx& c, float (&acc)[64], int n, Hook hook = Hook()) {
  const uint32_t dA = dlo(c.sA, 16);
  uint32_t b = stage_wait(c, n);
  turn_begin(c);
  wg_fence(); piece_ss<FIRST, 0>(c, acc, dA, b); wg_commit();
  b = stage_wait(c, n + 1);
  wg_fence(); piece_ss<0, 1>(c, acc, dA + 1024, b); wg_commit();
  hook();
  wg_wait<1>(); stage_release(c, n);
  wg_wait<0>(); stage_release(c, n + 1);
}
__device__ __forceinline__ uint32_t frag_addr(const Ctx& c, uint32_t tile, int j) {
  return tile + (2 * c.wg + (j >> 2)) * 8192 + c.frag + ((((j & 3) * 2 + c.hi) ^ c.rsw) << 4);
}
__device__ __forceinline__ void load_half(const Ctx& c, uint32_t tile, float (&v)[64]) {
#pragma unroll
  for (int j = 0; j < 8; j++) {
    uint32_t r0, r1, r2, r3;
    ldsm_x4(frag_addr(c, tile, j), r0, r1, r2, r3);
    v[8 * j] = bf_lo(r0); v[8 * j + 1] = bf_hi(r0); v[8 * j + 2] = bf_lo(r1); v[8 * j + 3] = bf_hi(r1);
    v[8 * j + 4] = bf_lo(r2); v[8 * j + 5] = bf_hi(r2); v[8 * j + 6] = bf_lo(r3); v[8 * j + 7] = bf_hi(r3);
  }
}
__device__ __forceinline__ void store_half(const Ctx& c, uint32_t tile, const float (&v)[64], float a0, float b0, float a1, float b1) {
#pragma unroll
  for (int j = 0; j < 8; j++)
    stsm_x4(frag_addr(c, tile, j),
            pack_bf16(fmaf(v[8 * j], a0, b0), fmaf(v[8 * j + 1], a0, b0)), pack_bf16(fmaf(v[8 * j + 2], a1, b1), fmaf(v[8 * j + 3], a1, b1)),
            pack_bf16(fmaf(v[8 * j + 4], a0, b0), fmaf(v[8 * j + 5], a0, b0)), pack_bf16(fmaf(v[8 * j + 6], a1, b1), fmaf(v[8 * j + 7], a1, b1)));
}
__device__ __forceinline__ void store_half_raw(const Ctx& c, uint32_t tile, const float (&v)[64]) {
#pragma unroll
  for (int j = 0; j < 8; j++)
    stsm_x4(frag_addr(c, tile, j), pack_bf16(v[8 * j], v[8 * j + 1]), pack_bf16(v[8 * j + 2], v[8 * j + 3]),
            pack_bf16(v[8 * j + 4], v[8 * j + 5]), pack_bf16(v[8 * j + 6], v[8 * j + 7]));
}
__device__ __forceinline__ void ln_stats(const Ctx& c, const float (&v)[64], float scale, float& a0, float& b0, float& a1, float& b1) {
  float s0 = 0.f, s1 = 0.f, q0 = 0.f, q1 = 0.f, s2 = 0.f, s3 = 0.f, q2 = 0.f, q3 = 0.f;
#pragma unroll
  for (int i = 0; i < 16; i++) {
    s0 += v[4 * i]; q0 = fmaf(v[4 * i], v[4 * i], q0);
    s2 += v[4 * i + 1]; q2 = fmaf(v[4 * i + 1], v[4 * i + 1], q2);
    s1 += v[4 * i + 2]; q1 = fmaf(v[4 * i + 2], v[4 * i + 2], q1);
    s3 += v[4 * i + 3]; q3 = fmaf(v[4 * i + 3], v[4 * i + 3], q3);
  }
  s0 += s2; q0 += q2; s1 += s3; q1 += q3;
  s0 += __shfl_xor_sync(0xffffffff, s0, 1); q0 += __shfl_xor_sync(0xffffffff, q0, 1);
  s1 += __shfl_xor_sync(0xffffffff, s1, 1); q1 += __shfl_xor_sync(0xffffffff, q1, 1);
  s0 += __shfl_xor_sync(0xffffffff, s0, 2); q0 += __shfl_xor_sync(0xffffffff, q0, 2);
  s1 += __shfl_xor_sync(0xffffffff, s1, 2); q1 += __shfl_xor_sync(0xffffffff, q1, 2);
  const uint32_t row = (c.tid >> 5) * 16 + (c.lane >> 2);
  if ((c.lane & 3) == 0) {
    sts64f(c.stats + c.wg * 512 + row * 8, s0, q0);
    sts64f(c.stats + c.wg * 512 + (row + 8) * 8, s1, q1);
  }
  bar_sync(1, 256);
  const float2 o0 = lds64f(c.stats + (c.wg ^ 1) * 512 + row * 8), o1 = lds64f(c.stats + (c.wg ^ 1) * 512 + (row + 8) * 8);
  const float m0 = (s0 + o0.x) * (1.f / 256.f), m1 = (s1 + o1.x) * (1.f / 256.f);
  const float var0 = fmaxf(fmaf(-m0, m0, (q0 + o0.y) * (1.f / 256.f)), 0.f), var1 = fmaxf(fmaf(-m1, m1, (q1 + o1.y) * (1.f / 256.f)), 0.f);
  a0 = rsqrt_fast(var0 + 1e-5f) * scale; a1 = rsqrt_fast(var1 + 1e-5f) * scale;
  b0 = -m0 * a0; b1 = -m1 * a1;
}
__device__ __forceinline__ float silu_half(float h) { return fmaf(h, tanh_fast(h), h); }
__device__ __forceinline__ float silu_quarter(float h) { const float q = 0.5f * h; return fmaf(q, tanh_fast(h), q); }
__device__ __forceinline__ void silu_pack(const float (&acc)[32], uint32_t (&P)[16]) {
#pragma unroll
  for (int i = 0; i < 16; i++) P[i] = pack_bf16(silu_quarter(acc[2 * i]), silu_quarter(acc[2 * i + 1]));
}
__device__ __forceinline__ void ff_block(const Ctx& c, int n0, float (&own)[64]) {
  float oth[64], h[32];
  uint32_t P[16];
#pragma unroll
  for (int i = 0; i < 64; i++) oth[i] = 0.f;
  const uint32_t dA = dlo(c.sA, 16);
  {
    const uint32_t b = stage_wait(c, n0 + c.wg);
    turn_begin(c);
    wg_fence(); ff_g1(c, h, dA, b); wg_commit();
    turn_end(c);
    wg_wait<0>(); stage_release(c, n0 + c.wg);
    silu_pack(h, P);
  }
#pragma unroll 1
  for (int it = 1; it < 8; it++) {
    const int n = n0 + 4 * it - 2 + 2 * c.wg;
    uint32_t b = stage_wait(c, n);
    turn_begin(c);
    wg_fence(); ff_g1(c, h, dA, b); wg_commit();
    b = stage_wait(c, n + 1);
    wg_fence(); ff_g2(own, P, b, c.wg); ff_g2(oth, P, b, c.wg ^ 1); wg_commit();
    turn_end(c);
    wg_wait<1>(); stage_release(c, n);
    wg_wait<0>(); stage_release(c, n + 1);
    silu_pack(h, P);
  }
  if (c.wg == 0) bar_arrive(2, 256);
  {
    const int n = n0 + 30 + c.wg;
    const uint32_t b = stage_wait(c, n);
    turn_begin(c);
    wg_fence(); ff_g2(oth, P, b, c.wg ^ 1); wg_commit();
    ff_g2(own, P, b, c.wg); wg_commit();
    turn_end(c);
    wg_wait<1>();
    if (c.wg == 1) bar_sync(2, 256);
    const uint32_t e = (c.wg == 0 ? c.sX : c.sA) + c.tid * 16;
#pragma unroll
    for (int i = 0; i < 16; i++)
      sts128(e + i * 2048, make_uint4(__float_as_uint(oth[4 * i]), __float_as_uint(oth[4 * i + 1]), __float_as_uint(oth[4 * i + 2]), __float_as_uint(oth[4 * i + 3])));
    wg_wait<0>(); stage_release(c, n);
  }
  bar_sync(1, 256);
  const uint32_t e = (c.wg == 0 ? c.sA : c.sX) + c.tid * 16;
#pragma unroll
  for (int i = 0; i < 16; i++) {
    const uint4 u = lds128(e + i * 2048);
    own[4 * i] += __uint_as_float(u.x); own[4 * i + 1] += __uint_as_float(u.y);
    own[4 * i + 2] += __uint_as_float(u.z); own[4 * i + 3] += __uint_as_float(u.w);
  }
}
struct Maps { CUtensorMap X, W1a, W1b, Wqkv, QKVst, Q, KV, Wo, Pw1, Pw2, W2a, W2b, Out; uint16_t stage[92]; };
constexpr int NA = 44;
constexpr int NC = 45;
#define STAGE_TABLE {0x1, 0x11, 0x21, 0x2, 0x31, 0x102, 0x41, 0x202, 0x51, 0x302, 0x61, 0x402, 0x71, 0x502, 0x81, 0x602, 0x91, 0x702, 0xa1, 0x802, 0xb1, 0x902, 0xc1, 0xa02, 0xd1, 0xb02, 0xe1, 0xc02, 0xf1, 0xd02, 0xe02, 0xf02, 0x3, 0x203, 0x23, 0x223, 0x43, 0x243, 0x63, 0x263, 0x83, 0x283, 0xa3, 0x2a3, 0x7, 0x207, 0x27, 0x227, 0x8, 0x208, 0x2008, 0x2208, 0x1008, 0x1208, 0x3008, 0x3208, 0x9, 0x29, 0x209, 0x229, 0xa, 0x1a, 0x2a, 0xb, 0x3a, 0x10b, 0x4a, 0x20b, 0x5a, 0x30b, 0x6a, 0x40b, 0x7a, 0x50b, 0x8a, 0x60b, 0x9a, 0x70b, 0xaa, 0x80b, 0xba, 0x90b, 0xca, 0xa0b, 0xda, 0xb0b, 0xea, 0xc0b, 0xfa, 0xd0b, 0xe0b, 0xf0b}
__device__ __forceinline__ void load_stage(uint32_t dst, uint32_t bar, const Maps& tm, int n) {
  const uint32_t e = tm.stage[n - (n > NA)];
  mbar_expect_tx(bar, STAGE);
  tma_load_3d(dst, &tm.X + (e & 15), bar, (e >> 12) * 64, ((e >> 8) & 15) * 64, (e >> 4) & 15);
}
__device__ __forceinline__ void produce(uint32_t sW, uint32_t full, const Maps& tm, int n0, int n1) {
  uint32_t s = n0 % RING, ph = ((n0 / RING) & 1) ^ 1;
#pragma unroll 1
  for (int n = n0; n < n1; n++) {
    mbar_wait(full + 8 * RING + 8 * s, ph);
    load_stage(sW + s * STAGE, full + 8 * s, tm, n);
    if (++s == RING) { s = 0; ph ^= 1; }
  }
}
__device__ __forceinline__ Ctx make_ctx(uint32_t base) {
  Ctx c;
  c.sA = base; c.sX = base + OFF_X; c.sW = base + OFF_W;
  c.full = base + OFF_MISC; c.empty = c.full + 8 * RING; c.stats = base + OFF_MISC + 256;
  c.wg = __shfl_sync(0xffffffff, (int)(threadIdx.x >> 7), 0);
  c.tid = threadIdx.x & 127; c.lane = threadIdx.x & 31;
  const uint32_t r = (c.tid >> 5) * 16 + (c.lane & 7) + ((c.lane >> 3) & 1) * 8;
  c.frag = r * 128; c.rsw = r & 7; c.hi = c.lane >> 4;
  return c;
}

constexpr int NSTG = 4;
constexpr int KVB = 160 * 128;
constexpr int NKV = T_ / 160;
static_assert(NSTG * 2 * KVB == RING * STAGE, "the K/V ring reuses the weight ring");

struct AttCtx { uint32_t sKV, full, empty, wfull; const Maps* tm; int h, b, wg; };
__device__ __forceinline__ int kv_slot(int i) { return (i + 3) & 3; }
__device__ __forceinline__ void att_load(const AttCtx& a, int i, int v) {
  const int s = i & 3;
  mbar_expect_tx(a.full + 8 * (s + v * NSTG), KVB);
  tma_load_3d(a.sKV + kv_slot(i) * 2 * KVB + v * KVB, &a.tm->KV, a.full + 8 * (s + v * NSTG), 256 + v * 256 + a.h * 64, i * 160, a.b);
}
__device__ __forceinline__ void att_load_stage(const AttCtx& a, int i) { att_load(a, i, 0); att_load(a, i, 1); }
__device__ __forceinline__ void att_init_bars(const AttCtx& a) {
  for (int i = 0; i < NSTG; i++) { mbar_init(a.full + 8 * i, 1); mbar_init(a.full + 8 * (NSTG + i), 1); mbar_init(a.empty + 8 * i, 4); }
}
__device__ __forceinline__ void att_qk(float (&S)[40], uint32_t dQ, uint32_t kd) {
  wg_ss_n80_tb0<0>(S, dQ, kd);
#pragma unroll
  for (int kk = 1; kk < 4; kk++) wg_ss_n80_tb0<1>(S, dQ + kk * 2, kd + kk * 2);
}
__device__ __forceinline__ void att_pv(float (&O)[32], const uint32_t (&P)[20], uint32_t vd) {
#pragma unroll
  for (int kk = 0; kk < 5; kk++) wg_rs_n64_tb1<1>(O, P[kk * 4], P[kk * 4 + 1], P[kk * 4 + 2], P[kk * 4 + 3], vd + kk * 128);
}
template<bool SAFE>
__device__ __forceinline__ void att_softmax(const float (&S)[40], uint32_t (&P)[20], float (&O)[32], float& m0, float& m1, float& l0, float& l1) {
  if (SAFE) {
    float x0 = fmaxf(S[0], S[1]), x1 = fmaxf(S[2], S[3]);
#pragma unroll
    for (int i = 1; i < 10; i++) { x0 = fmaxf(x0, fmaxf(S[4 * i], S[4 * i + 1])); x1 = fmaxf(x1, fmaxf(S[4 * i + 2], S[4 * i + 3])); }
    x0 = fmaxf(x0, __shfl_xor_sync(0xffffffff, x0, 1)); x1 = fmaxf(x1, __shfl_xor_sync(0xffffffff, x1, 1));
    x0 = fmaxf(x0, __shfl_xor_sync(0xffffffff, x0, 2)); x1 = fmaxf(x1, __shfl_xor_sync(0xffffffff, x1, 2));
    const float n0 = fmaxf(m0, x0), n1 = fmaxf(m1, x1);
    const float f0 = ex2(m0 - n0), f1 = ex2(m1 - n1);
    m0 = n0; m1 = n1; l0 *= f0; l1 *= f1;
#pragma unroll
    for (int i = 0; i < 8; i++) { O[4 * i] *= f0; O[4 * i + 1] *= f0; O[4 * i + 2] *= f1; O[4 * i + 3] *= f1; }
  }
#pragma unroll
  for (int i = 0; i < 10; i++) {
    float p0, p1, p2, p3;
    if (SAFE) { p0 = ex2(S[4 * i] - m0); p1 = ex2(S[4 * i + 1] - m0); p2 = ex2(S[4 * i + 2] - m1); p3 = ex2(S[4 * i + 3] - m1); }
    else { p0 = ex2(S[4 * i]); p1 = ex2(S[4 * i + 1]); p2 = ex2(S[4 * i + 2]); p3 = ex2(S[4 * i + 3]); }
    l0 += p0 + p1; l1 += p2 + p3;
    P[2 * i] = pack_bf16(p0, p1); P[2 * i + 1] = pack_bf16(p2, p3);
  }
}
template<bool SAFE>
__device__ __forceinline__ void att_refill(const AttCtx& a, int it) {
  if ((threadIdx.x & 127) == 0) {
    mbar_arrive(a.empty + 8 * (it & 3));
    if (a.wg == (it & 3) && it >= 1) {
      const bool kv = it - 1 + NSTG < NKV;
      if (kv || (!SAFE && a.wfull)) {
        mbar_wait(a.empty + 8 * ((it - 1) & 3), ((it - 1) >> 2) & 1);
        if (kv) att_load_stage(a, it - 1 + NSTG);
        else load_stage(a.sKV + (it - 22) * STAGE, a.wfull + 8 * (it - 22), *a.tm, NC + it - 22);
      }
    }
  }
  __syncwarp();
}
constexpr uint32_t KV_STG = 2 * KVB / 16, KV_VOFF = KVB / 16, KV_HALF = 80 * 128 / 16;
template<bool SAFE>
__device__ __forceinline__ void att_pass(const AttCtx& a, bool idle, uint32_t dQ, float (&O)[32], float& l0, float& l1) {
  float S[40];
  uint32_t P[20];
  float m0 = -INFINITY, m1 = -INFINITY;
  l0 = 0.f; l1 = 0.f;
#pragma unroll
  for (int i = 0; i < 32; i++) O[i] = 0.f;
  const uint32_t dKV = dlo(a.sKV, 16);
  if (SAFE) {
#pragma unroll 1
    for (int j = 0; j < 2 * NKV; j++) {
      const int it = j >> 1, s = it & 3;
      const uint32_t kb = dKV + kv_slot(it) * KV_STG + (j & 1) * KV_HALF;
      mbar_wait(a.full + 8 * s, (it >> 2) & 1);
      wg_fence(); att_qk(S, dQ, kb); wg_commit(); wg_wait<0>();
      att_softmax<true>(S, P, O, m0, m1, l0, l1);
      mbar_wait(a.full + 8 * (NSTG + s), (it >> 2) & 1);
      wg_fence(); att_pv(O, P, kb + KV_VOFF); wg_commit(); wg_wait<0>();
      if (j & 1) att_refill<true>(a, it);
    }
  } else if (idle) {
    l0 = 1.f; l1 = 1.f;
#pragma unroll 1
    for (int it = 0; it < NKV - 1; it++) { mbar_wait(a.full + 8 * (it & 3), (it >> 2) & 1); att_refill<false>(a, it); }
  } else {
    mbar_wait(a.full, 0);
    wg_fence(); att_qk(S, dQ, dKV + 3 * KV_STG); wg_commit(); wg_wait<0>();
    att_softmax<false>(S, P, O, m0, m1, l0, l1);
    mbar_wait(a.full + 8 * NSTG, 0);
    wg_fence(); att_pv(O, P, dKV + 3 * KV_STG + KV_VOFF); att_qk(S, dQ, dKV + 3 * KV_STG + KV_HALF); wg_commit(); wg_wait<0>();
#pragma unroll 1
    for (int it = 0; it < NKV - 1; it++) {
      const int sn = (it + 1) & 3;
      const uint32_t kb = dKV + kv_slot(it) * KV_STG, kn = dKV + kv_slot(it + 1) * KV_STG, par = ((it + 1) >> 2) & 1;
      att_softmax<false>(S, P, O, m0, m1, l0, l1);
      mbar_wait(a.full + 8 * sn, par);
      wg_fence(); att_pv(O, P, kb + KV_VOFF + KV_HALF); att_qk(S, dQ, kn); wg_commit(); wg_wait<0>();
      att_refill<false>(a, it);
      att_softmax<false>(S, P, O, m0, m1, l0, l1);
      mbar_wait(a.full + 8 * (NSTG + sn), par);
      wg_fence(); att_pv(O, P, kn + KV_VOFF); att_qk(S, dQ, kn + KV_HALF); wg_commit(); wg_wait<0>();
    }
    att_softmax<false>(S, P, O, m0, m1, l0, l1);
    wg_fence(); att_pv(O, P, dKV + 3 * KV_STG + KV_VOFF + KV_HALF); wg_commit(); wg_wait<0>();
  }
  l0 += __shfl_xor_sync(0xffffffff, l0, 1); l1 += __shfl_xor_sync(0xffffffff, l1, 1);
  l0 += __shfl_xor_sync(0xffffffff, l0, 2); l1 += __shfl_xor_sync(0xffffffff, l1, 2);
}

struct Wptrs { const void* p[8]; uint32_t bytes[8]; };

constexpr uint32_t B_FULL = 0, B_EMPTY = 8 * RING, B_X = 16 * RING, B_ADONE = B_X + 8, B_Q = B_X + 16, B_EP = B_X + 24, B_ATT = B_X + 32;

__global__ void __launch_bounds__(512, 1) conformer_kernel(const __grid_constant__ Maps tm, const __grid_constant__ Wptrs wp, const uint4* __restrict__ dw) {
  extern __shared__ uint8_t smem_raw[];
  const uint32_t base = (smem_u32(smem_raw) + 1023) & ~1023u, misc = base + OFF_MISC;
  const uint32_t bq = blockIdx.x / 19, br = blockIdx.x - bq * 19;
  const uint32_t bid = br == 18 ? ((bq & 1) ? 125 : 128) + (bq >> 1) : blockIdx.x - bq;
  if (bid >= NWORK) return;
  const int tile = bid;
  const bool has_tile = tile < NTILE;
  const int wg = __shfl_sync(0xffffffff, (int)(threadIdx.x >> 7), 0);
  AttCtx a;
  a.sKV = base + OFF_W; a.full = misc + B_ATT; a.empty = a.full + 16 * NSTG; a.tm = &tm;
  a.h = (bid >> 4) & 3; a.b = (bid >> 6) & 1; a.wg = wg; a.wfull = has_tile ? misc + B_FULL : 0;
  const int qt = bid & 15;

  if (threadIdx.x == 256) {
    mbar_init(misc + B_X, 1);
    for (int i = 0; i < RING; i++) { mbar_init(misc + B_FULL + 8 * i, 1); mbar_init(misc + B_EMPTY + 8 * i, 1); }
    asm volatile("fence.mbarrier_init.release.cluster;" ::: "memory");
    if (has_tile) {
      mbar_expect_tx(misc + B_X, 32768);
      tma_load_3d(base + OFF_X, &tm.X, misc + B_X, 0, tile * 64, 0);
    }
  } else if (threadIdx.x >= 288 && threadIdx.x < 303) {
    const int i = threadIdx.x - 288;
    mbar_init(misc + B_ADONE + 8 * i, i == 0 ? 2 : i >= 11 ? 4 : 1);
    asm volatile("fence.mbarrier_init.release.cluster;" ::: "memory");
  } else if (threadIdx.x >= 320 && threadIdx.x < 333) {
    prefetch_tmap(&tm.X + (threadIdx.x - 320));
  }
  __syncthreads();
  if ((threadIdx.x & 31) == 0 && threadIdx.x >= 256 && threadIdx.x < 256 + 32 * RING && has_tile) {
    const int i = (threadIdx.x - 256) >> 5;
    load_stage(base + OFF_W + i * STAGE, misc + B_FULL + 8 * i, tm, i);
  }
  __syncwarp();
  auto get_epoch = [&]() {
    uint32_t e;
    mbar_wait(misc + B_EP, 0);
    asm volatile("ld.shared.u32 %0, [%1];" : "=r"(e) : "r"(misc + 248) : "memory");
    return e;
  };

  if (wg < 2) {
    asm volatile("setmaxnreg.inc.sync.aligned.u32 232;");
    if (has_tile) {
      const Ctx c = make_ctx(base);
      if (c.wg == 1) turn_end(c);
      float own[64];
      float a0, b0, a1, b1;
      mbar_wait(misc + B_X, 0);
      load_half(c, c.sX, own);
      ln_stats(c, own, 0.5f, a0, b0, a1, b1);
      store_half(c, c.sA, own, a0, b0, a1, b1);
      fence_async_smem();
      bar_sync(1, 256);
      ff_block(c, 0, own);
      ln_stats(c, own, 1.f, a0, b0, a1, b1);
      store_half(c, c.sA, own, a0, b0, a1, b1);
      fence_async_smem();
      bar_sync(1, 256);
#pragma unroll 1
      for (int cc = 0; cc < 3; cc++) {
        float acc[64];
        const int j = 2 * cc + c.wg;
        gemm256<1>(c, acc, 32 + 2 * j, [&]() {
          if (c.tid == 0) {
            if (cc == 2) {
              bulk_wait_all();
              if (tile <= 62) cnt_signal(g_cnt1);
              if (tile >= 62) cnt_signal(g_cnt1 + 64);
            } else bulk_wait_read();
          }
          bar_sync(3 + c.wg, 128);
        });
        if (cc == 2) { bar_arrive(9, 288); if (c.tid == 0) mbar_arrive(misc + B_ADONE); }
        if (cc == 0) {
#pragma unroll
          for (int i = 0; i < 64; i++) acc[i] *= 0.125f * 1.4426950408889634f;
        }
        store_half_raw(c, c.sX, acc);
        fence_async_smem();
        bar_sync(3 + c.wg, 128);
        if (c.tid == 0) { tma_store_3d(&tm.QKVst, c.sX + c.wg * 16384, 0, tile * 64, 2 * j); bulk_commit(); }
      }
      if (c.tid == 0) bulk_wait_read();
      bar_sync(3 + c.wg, 128);
      store_half_raw(c, c.sX, own);
    }
    else bar_sync(3 + wg, 128);
    asm volatile("setmaxnreg.dec.sync.aligned.u32 128;");
    bar_arrive(7, 384); bar_arrive(8, 384);
    if (has_tile && (threadIdx.x & 127) == 0) {
      bulk_wait_all();
      if (tile <= 62) cnt_signal(g_cnt1 + 32);
      if (tile >= 62) cnt_signal(g_cnt1 + 96);
    }
    __syncwarp();
  } else {
    asm volatile("setmaxnreg.dec.sync.aligned.u32 24;");
    const uint32_t full = misc + B_FULL;
    if (threadIdx.x == 320) {
      const uint32_t e = atomicAdd(&g_start, 1) / NWORK;
      asm volatile("st.shared.u32 [%0], %1;" :: "r"(misc + 248), "r"(e + 1) : "memory");
      mbar_arrive(misc + B_EP);
    }
    if (threadIdx.x == 256) {
      if (has_tile) {
        produce(base + OFF_W, full, tm, RING, NA);
        mbar_wait(full + 8 * RING + 8 * 4, 1);
        mbar_arrive(full + 8 * 4); mbar_arrive(full + 8 * RING + 8 * 4);
        mbar_wait(misc + B_ADONE, 0);
      }
      cnt_wait(g_cnt1 + a.b * 64, 126 * get_epoch());
      mbar_expect_tx(misc + B_Q, 32768);
      tma_load_3d(base, &tm.Q, misc + B_Q, a.h * 64, qt * 256, a.b);
      att_load(a, 0, 0);
      mbar_wait(misc + B_Q, 0);
#pragma unroll 1
      for (int i = 1; i < NSTG; i++) att_load(a, i, 0);
    } else if ((threadIdx.x >> 5) == 12) {
      if (has_tile) bar_sync(9, 288);
      if (threadIdx.x == 384) {
        cnt_wait(g_cnt1 + a.b * 64 + 32, 126 * get_epoch());
        att_load(a, 0, 1);
        mbar_wait(a.full + 8 * NSTG, 0);
#pragma unroll 1
        for (int i = 1; i < NSTG; i++) att_load(a, i, 1);
      }
    } else if (has_tile && threadIdx.x >= 288 && threadIdx.x < 296) {
      const int w = threadIdx.x - 288;
      mbar_wait(misc + B_X, 0);
      if (w >= 2) __nanosleep(4000);
      const uint32_t bytes = wp.bytes[w], per = ((bytes / NTILE) + 127) & ~127u, off = per * tile;
      if (off < bytes) l2_prefetch((const uint8_t*)wp.p[w] + off, min(per, bytes - off));
    } else if (has_tile && threadIdx.x >= 416) {
      mbar_wait(full, 0);
      const int t = threadIdx.x - 416;
#pragma unroll 1
      for (int i = t; i < 2048; i += 96) g_att[tile * 2048 + i] = make_uint4(~0u, ~0u, ~0u, ~0u);
      g_halo[tile * 128 + t] = make_uint4(~0u, ~0u, ~0u, ~0u);
      if (t < 32) g_halo[tile * 128 + 96 + t] = make_uint4(~0u, ~0u, ~0u, ~0u);
    }
    __syncwarp();
    bar_sync(5 + wg, 384);
    asm volatile("setmaxnreg.inc.sync.aligned.u32 128;");
  }

  {
    const int lane = threadIdx.x & 31, wq = (threadIdx.x >> 5) & 3;
    const uint32_t dQ = dlo(base + wg * 8192, 16);
    float O[32], l0, l1;
    mbar_wait(misc + B_Q, 0);
    att_pass<false>(a, qt * 256 + wg * 64 >= T_, dQ, O, l0, l1);
    float z0 = 0.f, z1 = 0.f, z2 = 0.f, z3 = 0.f;
#pragma unroll
    for (int i = 0; i < 8; i++) { z0 = fmaf(O[4 * i], 0.f, z0); z1 = fmaf(O[4 * i + 1], 0.f, z1); z2 = fmaf(O[4 * i + 2], 0.f, z2); z3 = fmaf(O[4 * i + 3], 0.f, z3); }
    const float z = (z0 + z1) + (z2 + z3);
    const bool ok = (l0 >= 0x1p-40f) && (l0 <= 0x1p80f) && (l1 >= 0x1p-40f) && (l1 <= 0x1p80f) && (z == 0.f);
    const bool warp_bad = !__all_sync(0xffffffff, ok);
    auto store_out = [&]() {
      const float i0 = rcp_fast(l0), i1 = rcp_fast(l1);
      const int row = qt * 256 + wg * 64 + wq * 16;
      if (row < T_) {
        const int slab = (a.b * T_ + row) / 16;
        uint4* op = g_att + (slab * 16 + a.h * 4) * 32 + lane;
#pragma unroll
        for (int j = 0; j < 4; j++)
          asm volatile("st.relaxed.gpu.global.v4.u32 [%0], {%1,%2,%3,%4};" :: "l"(op + j * 32),
                       "r"(pack_bf16(O[8 * j] * i0, O[8 * j + 1] * i0)), "r"(pack_bf16(O[8 * j + 2] * i1, O[8 * j + 3] * i1)),
                       "r"(pack_bf16(O[8 * j + 4] * i0, O[8 * j + 5] * i0)), "r"(pack_bf16(O[8 * j + 6] * i1, O[8 * j + 7] * i1)) : "memory");
      }
    };
    if (!warp_bad) store_out();
    if (__syncthreads_or(warp_bad)) {
      if (threadIdx.x == 0) {
        if (has_tile) { mbar_wait(misc + B_FULL, 1); mbar_wait(misc + B_FULL + 8, 1); }
        for (int i = 0; i < 3 * NSTG; i++) mbar_inval(a.full + 8 * i);
        att_init_bars(a);
        asm volatile("fence.mbarrier_init.release.cluster;" ::: "memory");
        fence_async_smem();
#pragma unroll 1
        for (int i = 0; i < NSTG; i++) att_load_stage(a, i);
      }
      __syncthreads();
      att_pass<true>(a, false, dQ, O, l0, l1);
      if (warp_bad) store_out();
      __syncthreads();
      if (has_tile) {
        if (threadIdx.x == 32) {
          load_stage(base + OFF_W, misc + B_X, tm, NC);
          load_stage(base + OFF_W + STAGE, misc + B_Q, tm, NC + 1);
        }
        mbar_wait(misc + B_X, 1); mbar_wait(misc + B_Q, 1);
      }
    }
  }
  if (!has_tile) return;

  if (wg < 2) {
    asm volatile("setmaxnreg.inc.sync.aligned.u32 232;");
    const Ctx c = make_ctx(base);
    float own[64];
    float a0, b0, a1, b1;
    {
      uint4 af[16];
      const int slab = tile * 4 + (c.tid >> 5);
      const uint4* ap = g_att + slab * 512 + c.lane;
#pragma unroll
      for (int i = 0; i < 16; i++)
        asm volatile("ld.global.ca.v4.u32 {%0,%1,%2,%3}, [%4];" : "=r"(af[i].x), "=r"(af[i].y), "=r"(af[i].z), "=r"(af[i].w) : "l"(ap + i * 32) : "memory");
      load_half(c, c.sX, own);
      uint32_t miss = 15;
      for (uint32_t n = 0; n < (1u << 18); n++) {
#pragma unroll
        for (int hh = 0; hh < 4; hh++)
          if ((miss >> hh) & 1) {
            uint32_t mx = 0;
#pragma unroll
            for (int i = 4 * hh; i < 4 * hh + 4; i++) mx = max(mx, max(max(af[i].x, af[i].y), max(af[i].z, af[i].w)));
            if (__any_sync(0xffffffff, mx == ~0u)) {
#pragma unroll
              for (int i = 4 * hh; i < 4 * hh + 4; i++)
                asm volatile("ld.relaxed.gpu.global.v4.u32 {%0,%1,%2,%3}, [%4];" : "=r"(af[i].x), "=r"(af[i].y), "=r"(af[i].z), "=r"(af[i].w) : "l"(ap + i * 32) : "memory");
            } else miss &= ~(1u << hh);
          }
        if (!miss) break;
      }
      const int n = NC + 2 * c.wg;
      uint32_t b = stage_wait(c, n) + ((16384 >> 4) << 16);
      turn_begin(c);
      wg_fence();
#pragma unroll
      for (int kk = 0; kk < 8; kk++) wg_rs_n128_tb1<1>(own, af[kk].x, af[kk].y, af[kk].z, af[kk].w, b + kk * 128);
      wg_commit();
      b = stage_wait(c, n + 1) + ((16384 >> 4) << 16);
      wg_fence();
#pragma unroll
      for (int kk = 0; kk < 8; kk++) wg_rs_n128_tb1<1>(own, af[8 + kk].x, af[8 + kk].y, af[8 + kk].z, af[8 + kk].w, b + kk * 128);
      wg_commit();
      turn_end(c);
      wg_wait<1>(); stage_release(c, n);
      wg_wait<0>(); stage_release(c, n + 1);
    }
    ln_stats(c, own, 0.5f, a0, b0, a1, b1);
    store_half(c, c.sA, own, a0, b0, a1, b1);
    fence_async_smem();
    bar_sync(1, 256);
    uint4 dwr[5];
#pragma unroll
    for (int i = 0; i < 5; i++) dwr[i] = __ldg(dw + i * 32 + c.wg * 16 + (c.lane & 15));
    const bool top = c.tid < 8, pub = (top || c.tid >= 120);
    uint32_t* halo_out = (uint32_t*)g_halo + (tile * 4 + (top ? (c.tid >> 2) : ((c.tid >> 2) - 28))) * 128 + c.wg * 64 + (c.lane & 3);
#pragma unroll 1
    for (int q = 0; q < 2; q++) {
      float ab[64];
      gemm256<1>(c, ab, NC + 4 + 4 * q + 2 * c.wg);
#pragma unroll
      for (int j = 0; j < 4; j++) {
        float g[8];
#pragma unroll
        for (int i = 0; i < 8; i++) g[i] = fmaf(ab[8 * j + i], tanh_fast(ab[32 + 8 * j + i]), ab[8 * j + i]);
        const uint32_t p0 = pack_bf16(g[0], g[1]), p1 = pack_bf16(g[2], g[3]), p2 = pack_bf16(g[4], g[5]), p3 = pack_bf16(g[6], g[7]);
        if (pub) {
          uint32_t* hp = halo_out + q * 32 + j * 8;
          asm volatile("st.relaxed.gpu.global.u32 [%0], %1;" :: "l"(hp), "r"(top ? p0 : p1) : "memory");
          asm volatile("st.relaxed.gpu.global.u32 [%0], %1;" :: "l"(hp + 4), "r"(top ? p2 : p3) : "memory");
        }
        stsm_x4(c.sX + (2 * c.wg + q) * 8192 + c.frag + (((j * 2 + c.hi) ^ c.rsw) << 4), p0, p1, p2, p3);
      }
    }
    bar_sync(3 + c.wg, 128);
    {
      const int wi = c.tid >> 4;
      const uint32_t col = (2 * c.wg + ((c.lane >> 3) & 1)) * 8192, ch = c.lane & 7;
      uint4 r[12];
      const int R0 = tile * 64 + wi * 8;
      const bool first = (R0 % T_) == 0, last = ((R0 + 8) % T_) == 0;
      const bool far = ((wi == 0 && !first) || (wi == 7 && !last));
      const uint4* sp = g_halo + (wi == 0 ? (tile - 1) * 4 + 2 : (tile + 1) * 4) * 32 + c.wg * 16 + (c.lane & 15);
      uint4 h0 = make_uint4(0, 0, 0, 0), h1 = h0;
      auto ld_halo = [&]() {
        asm volatile("ld.relaxed.gpu.global.v4.u32 {%0,%1,%2,%3}, [%4];" : "=r"(h0.x), "=r"(h0.y), "=r"(h0.z), "=r"(h0.w) : "l"(sp) : "memory");
        asm volatile("ld.relaxed.gpu.global.v4.u32 {%0,%1,%2,%3}, [%4];" : "=r"(h1.x), "=r"(h1.y), "=r"(h1.z), "=r"(h1.w) : "l"(sp + 32) : "memory");
      };
      if (far) ld_halo();
#pragma unroll
      for (int i = 0; i < 12; i++) {
        const int row = (wi * 8 - 2 + i) & 63;
        r[i] = lds128(c.sX + col + row * 128 + ((ch ^ (row & 7)) << 4));
      }
      uint32_t w[5][4];
#pragma unroll
      for (int k = 0; k < 5; k++) {
        w[k][0] = bmul2(dwr[k].x, 0x3F003F00u); w[k][1] = bmul2(dwr[k].y, 0x3F003F00u);
        w[k][2] = bmul2(dwr[k].z, 0x3F003F00u); w[k][3] = bmul2(dwr[k].w, 0x3F003F00u);
      }
      auto conv4 = [&](int i0, int i1, int i2, int i3, bool sync) {
        const int rows[4] = {i0, i1, i2, i3};
        uint32_t acc[4][4];
#pragma unroll
        for (int k = 0; k < 5; k++)
#pragma unroll
          for (int j = 0; j < 4; j++) {
            const uint4 x = r[rows[j] + k];
            acc[j][0] = k ? bfma2(x.x, w[k][0], acc[j][0]) : bmul2(x.x, w[0][0]);
            acc[j][1] = k ? bfma2(x.y, w[k][1], acc[j][1]) : bmul2(x.y, w[0][1]);
            acc[j][2] = k ? bfma2(x.z, w[k][2], acc[j][2]) : bmul2(x.z, w[0][2]);
            acc[j][3] = k ? bfma2(x.w, w[k][3], acc[j][3]) : bmul2(x.w, w[0][3]);
          }
#pragma unroll
        for (int j = 0; j < 4; j++)
#pragma unroll
          for (int q = 0; q < 4; q++) acc[j][q] = pack_bf16(silu_half(bf_lo(acc[j][q])), silu_half(bf_hi(acc[j][q])));
        if (sync) bar_sync(3 + c.wg, 128);
#pragma unroll
        for (int j = 0; j < 4; j++)
          sts128(c.sX + col + (wi * 8 + rows[j]) * 128 + ((ch ^ rows[j]) << 4), make_uint4(acc[j][0], acc[j][1], acc[j][2], acc[j][3]));
      };
      conv4(2, 3, 4, 5, true);
      if (far) {
        for (uint32_t n = 0; n < (1u << 18); n++) {
          const uint32_t mx = max(max(max(h0.x, h0.y), max(h0.z, h0.w)), max(max(h1.x, h1.y), max(h1.z, h1.w)));
          if (mx != ~0u) break;
          ld_halo();
        }
      }
      __syncwarp();
      if (first || (far && wi == 0)) { r[0] = h0; r[1] = h1; }
      if (last || (far && wi == 7)) { r[10] = h0; r[11] = h1; }
      conv4(0, 1, 6, 7, false);
    }
    fence_async_smem();
    bar_sync(c.wg == 0 ? 3 : 1, c.wg == 0 ? 128 : 256);
    {
      uint32_t b = stage_wait(c, NC + 12 + c.wg);
      turn_begin(c);
      wg_fence(); piece_ss<0, 0>(c, own, dlo(c.sX, 16), b); wg_commit();
      if (c.wg == 0) { turn_end(c); bar_sync(1, 256); turn_begin(c); }
      b = stage_wait(c, NC + 14 + c.wg);
      wg_fence(); piece_ss<0, 1>(c, own, dlo(c.sX, 16) + 1024, b); wg_commit();
    }
    wg_wait<1>(); stage_release(c, NC + 12 + c.wg);
    wg_wait<0>(); stage_release(c, NC + 14 + c.wg);
    ln_stats(c, own, 0.5f, a0, b0, a1, b1);
    if (c.wg == 1) { turn_begin(c); turn_end(c); }
    store_half(c, c.sA, own, a0, b0, a1, b1);
    fence_async_smem();
    bar_sync(1, 256);
    ff_block(c, NC + 16, own);
    ln_stats(c, own, 1.f, a0, b0, a1, b1);
    store_half(c, c.sX, own, a0, b0, a1, b1);
    fence_async_smem();
    bar_sync(3 + c.wg, 128);
    if (c.tid == 0) { tma_store_3d(&tm.Out, c.sX + c.wg * 16384, 0, tile * 64, 2 * c.wg); bulk_commit(); bulk_wait_read(); }
  } else {
    asm volatile("setmaxnreg.dec.sync.aligned.u32 24;");
    if (threadIdx.x == 256) {
      __nanosleep(200);
      produce(base + OFF_W, misc + B_FULL, tm, NC + 2, NC + 48);
    }
  }
}

typedef CUresult (*EncodeFn)(CUtensorMap*, CUtensorMapDataType, cuuint32_t, void*, const cuuint64_t*, const cuuint64_t*, const cuuint32_t*,
                             const cuuint32_t*, CUtensorMapInterleave, CUtensorMapSwizzle, CUtensorMapL2promotion, CUtensorMapFloatOOBfill);

CUtensorMap make_map(EncodeFn enc, const void* p, uint64_t d0, uint64_t d1, uint64_t d2, uint64_t s1, uint64_t s2, uint32_t b1, uint32_t b2) {
  CUtensorMap tm;
  cuuint64_t dims[3] = {d0, d1, d2};
  cuuint64_t strides[2] = {s1, s2};
  cuuint32_t box[3] = {64, b1, b2};
  cuuint32_t es[3] = {1, 1, 1};
  enc(&tm, CU_TENSOR_MAP_DATA_TYPE_BFLOAT16, 3, const_cast<void*>(p), dims, strides, box, es, CU_TENSOR_MAP_INTERLEAVE_NONE,
      CU_TENSOR_MAP_SWIZZLE_128B, CU_TENSOR_MAP_L2_PROMOTION_L2_256B, CU_TENSOR_MAP_FLOAT_OOB_FILL_NONE);
  return tm;
}
CUtensorMap blk_map(EncodeFn enc, const void* p, uint64_t rows, uint64_t cols, uint32_t boxrows, uint32_t boxblks) {
  return make_map(enc, p, 64, rows, cols / 64, cols * 2, 128, boxrows, boxblks);
}
CUtensorMap seq_map(EncodeFn enc, const void* p, uint64_t cols, uint32_t boxrows) {
  return make_map(enc, p, cols, T_, 2, cols * 2, cols * 2 * T_, boxrows, 1);
}

}

extern "C" void kernel_launch(void* const* d_in, const int* in_sizes, int n_in, void* d_out, int out_size) {
  (void)in_sizes; (void)n_in; (void)out_size;
  const void *x = d_in[0], *w1a = d_in[1], *w1b = d_in[2], *wqkv = d_in[3], *wo = d_in[4], *pw1 = d_in[5], *dw = d_in[6], *pw2 = d_in[7],
             *w2a = d_in[8], *w2b = d_in[9];
  void* fn = nullptr;
  cudaDriverEntryPointQueryResult qr;
  cudaGetDriverEntryPoint("cuTensorMapEncodeTiled", &fn, cudaEnableDefault, &qr);
  EncodeFn enc = (EncodeFn)fn;
  void* qkv;
  cudaGetSymbolAddress(&qkv, g_qkv);
  cudaFuncSetAttribute(conformer_kernel, cudaFuncAttributeMaxDynamicSharedMemorySize, SMEM_BYTES);

  Wptrs wp;
  const void* ws[8] = {w1a, w1b, wqkv, wo, pw1, pw2, w2a, w2b};
  const uint32_t wb[8] = {524288, 524288, 393216, 131072, 262144, 131072, 524288, 524288};
  for (int i = 0; i < 8; i++) { wp.p[i] = ws[i]; wp.bytes[i] = wb[i]; }
  Maps tm;
  const uint16_t tab[92] = STAGE_TABLE;
  for (int i = 0; i < 92; i++) tm.stage[i] = tab[i];
  tm.X = blk_map(enc, x, ROWS, 256, 64, 4);
  tm.W1a = blk_map(enc, w1a, 256, 1024, 256, 1);
  tm.W1b = blk_map(enc, w1b, 1024, 256, 64, 4);
  tm.Wqkv = blk_map(enc, wqkv, 256, 768, 128, 2);
  tm.QKVst = blk_map(enc, qkv, ROWS, 768, 64, 2);
  tm.Q = seq_map(enc, qkv, 768, 256);
  tm.KV = seq_map(enc, qkv, 768, 160);
  tm.Wo = blk_map(enc, wo, 256, 256, 128, 2);
  tm.Pw1 = make_map(enc, pw1, 256, 256, 2, 1024, 512, 128, 2);
  tm.Pw2 = blk_map(enc, pw2, 256, 256, 128, 2);
  tm.W2a = blk_map(enc, w2a, 256, 1024, 256, 1);
  tm.W2b = blk_map(enc, w2b, 1024, 256, 64, 4);
  tm.Out = blk_map(enc, d_out, ROWS, 256, 64, 2);
  conformer_kernel<<<NCTA, 512, SMEM_BYTES, cudaStreamPerThread>>>(tm, wp, (const uint4*)dw);
}
```

```cpp
#include <cuda_runtime.h>
#include <cuda_bf16.h>
#include <cuda.h>
#include <stdint.h>

namespace {

constexpr int T_ = 4000;
constexpr int ROWS = 8000;
constexpr int NTILE = 125;
constexpr int NWORK = 128;
constexpr int NCTA = 131;

__device__ __align__(128) __nv_bfloat16 g_qkv[ROWS * 768];
__device__ uint4 g_att[(ROWS / 16) * 16 * 32];
__device__ uint4 g_halo[NTILE * 4 * 32];
__device__ uint32_t g_start;
__device__ uint32_t g_cnt1[4 * 32];


__device__ __forceinline__ uint32_t smem_u32(const void* p) { return (uint32_t)__cvta_generic_to_shared(p); }
__device__ __forceinline__ void mbar_init(uint32_t bar, uint32_t cnt) { asm volatile("mbarrier.init.shared::cta.b64 [%0], %1;" :: "r"(bar), "r"(cnt) : "memory"); }
__device__ __forceinline__ void mbar_inval(uint32_t bar) { asm volatile("mbarrier.inval.shared::cta.b64 [%0];" :: "r"(bar) : "memory"); }
__device__ __forceinline__ void mbar_expect_tx(uint32_t bar, uint32_t bytes) { asm volatile("mbarrier.arrive.expect_tx.shared::cta.b64 _, [%0], %1;" :: "r"(bar), "r"(bytes) : "memory"); }
__device__ __forceinline__ void mbar_arrive(uint32_t bar) { asm volatile("mbarrier.arrive.shared::cta.b64 _, [%0];" :: "r"(bar) : "memory"); }
__device__ __forceinline__ void mbar_wait(uint32_t bar, uint32_t parity) {
  asm volatile("{\n.reg .pred p;\n.reg .u32 n;\n"
               "mbarrier.try_wait.parity.shared::cta.b64 p, [%0], %1;\n@p bra DONE_%=;\nmov.u32 n, 0;\n"
               "LOOP_%=:\nmbarrier.try_wait.parity.shared::cta.b64 p, [%0], %1;\n@p bra DONE_%=;\n"
               "add.u32 n, n, 1;\nsetp.lt.u32 p, n, 262144;\n@p bra LOOP_%=;\ntrap;\nDONE_%=:\n}\n" :: "r"(bar), "r"(parity) : "memory");
}
__device__ __forceinline__ void cnt_wait(const uint32_t* p, uint32_t target) {
  asm volatile("{\n.reg .pred p;\n.reg .u32 n, v;\nmov.u32 n, 0;\n"
               "LOOP_%=:\nld.relaxed.gpu.global.u32 v, [%0];\nsub.u32 v, v, %1;\nsetp.ge.s32 p, v, 0;\n@p bra DONE_%=;\n"
               "nanosleep.u32 40;\nadd.u32 n, n, 1;\nsetp.lt.u32 p, n, 262144;\n@p bra LOOP_%=;\ntrap;\nDONE_%=:\n}\n" :: "l"(p), "r"(target) : "memory");
}
__device__ __forceinline__ void cnt_signal(uint32_t* p) {
  asm volatile("red.relaxed.gpu.global.add.u32 [%0], 1;" :: "l"(p) : "memory");
}
__device__ __forceinline__ void tma_load_3d(uint32_t dst, const CUtensorMap* tm, uint32_t bar, int c0, int c1, int c2) {
  asm volatile("cp.async.bulk.tensor.3d.shared::cluster.global.mbarrier::complete_tx::bytes [%0], [%1, {%3, %4, %5}], [%2];"
    :: "r"(dst), "l"(tm), "r"(bar), "r"(c0), "r"(c1), "r"(c2) : "memory");
}
__device__ __forceinline__ void tma_store_3d(const CUtensorMap* tm, uint32_t src, int c0, int c1, int c2) {
  asm volatile("cp.async.bulk.tensor.3d.global.shared::cta.bulk_group [%0, {%2, %3, %4}], [%1];" :: "l"(tm), "r"(src), "r"(c0), "r"(c1), "r"(c2) : "memory");
}
__device__ __forceinline__ void bulk_commit() { asm volatile("cp.async.bulk.commit_group;" ::: "memory"); }
__device__ __forceinline__ void bulk_wait_read() { asm volatile("cp.async.bulk.wait_group.read 0;" ::: "memory"); }
__device__ __forceinline__ void bulk_wait_all() { asm volatile("cp.async.bulk.wait_group 0;" ::: "memory"); }
__device__ __forceinline__ void l2_prefetch(const void* p, uint32_t bytes) { asm volatile("cp.async.bulk.prefetch.L2.global [%0], %1;" :: "l"(p), "r"(bytes) : "memory"); }
__device__ __forceinline__ void prefetch_tmap(const CUtensorMap* tm) { asm volatile("prefetch.tensormap [%0];" :: "l"(tm) : "memory"); }
__device__ __forceinline__ void fence_async_smem() { asm volatile("fence.proxy.async.shared::cta;" ::: "memory"); }
__device__ __forceinline__ void wg_fence() { asm volatile("wgmma.fence.sync.aligned;" ::: "memory"); }
__device__ __forceinline__ void wg_commit() { asm volatile("wgmma.commit_group.sync.aligned;" ::: "memory"); }
template<int N> __device__ __forceinline__ void wg_wait() { asm volatile("wgmma.wait_group.sync.aligned %0;" :: "n"(N) : "memory"); }
__device__ __forceinline__ void bar_sync(int id, int n) { asm volatile("bar.sync %0, %1;" :: "r"(id), "r"(n) : "memory"); }
__device__ __forceinline__ void bar_arrive(int id, int n) { asm volatile("bar.arrive %0, %1;" :: "r"(id), "r"(n) : "memory"); }
__device__ __forceinline__ float ex2(float x) { float y; asm("ex2.approx.ftz.f32 %0, %1;" : "=f"(y) : "f"(x)); return y; }
__device__ __forceinline__ float rcp_fast(float x) { float y; asm("rcp.approx.ftz.f32 %0, %1;" : "=f"(y) : "f"(x)); return y; }
__device__ __forceinline__ float rsqrt_fast(float x) { float y; asm("rsqrt.approx.ftz.f32 %0, %1;" : "=f"(y) : "f"(x)); return y; }
__device__ __forceinline__ float tanh_fast(float x) { float y; asm("tanh.approx.f32 %0, %1;" : "=f"(y) : "f"(x)); return y; }
__device__ __forceinline__ uint32_t pack_bf16(float lo, float hi) { uint32_t r; asm("cvt.rn.bf16x2.f32 %0, %1, %2;" : "=r"(r) : "f"(hi), "f"(lo)); return r; }
__device__ __forceinline__ uint32_t bmul2(uint32_t a, uint32_t b) { uint32_t d; asm("mul.rn.bf16x2 %0, %1, %2;" : "=r"(d) : "r"(a), "r"(b)); return d; }
__device__ __forceinline__ uint32_t bfma2(uint32_t a, uint32_t b, uint32_t c) { uint32_t d; asm("fma.rn.bf16x2 %0, %1, %2, %3;" : "=r"(d) : "r"(a), "r"(b), "r"(c)); return d; }
__device__ __forceinline__ float bf_lo(uint32_t u) { return __uint_as_float(u << 16); }
__device__ __forceinline__ float bf_hi(uint32_t u) { return __uint_as_float(u & 0xffff0000u); }
__device__ __forceinline__ void ldsm_x4(uint32_t addr, uint32_t& r0, uint32_t& r1, uint32_t& r2, uint32_t& r3) {
  asm volatile("ldmatrix.sync.aligned.m8n8.x4.shared.b16 {%0,%1,%2,%3}, [%4];" : "=r"(r0), "=r"(r1), "=r"(r2), "=r"(r3) : "r"(addr) : "memory");
}
__device__ __forceinline__ void stsm_x4(uint32_t addr, uint32_t r0, uint32_t r1, uint32_t r2, uint32_t r3) {
  asm volatile("stmatrix.sync.aligned.m8n8.x4.shared.b16 [%0], {%1,%2,%3,%4};" :: "r"(addr), "r"(r0), "r"(r1), "r"(r2), "r"(r3) : "memory");
}
__device__ __forceinline__ void sts128(uint32_t addr, uint4 v) { asm volatile("st.shared.v4.b32 [%0], {%1,%2,%3,%4};" :: "r"(addr), "r"(v.x), "r"(v.y), "r"(v.z), "r"(v.w) : "memory"); }
__device__ __forceinline__ uint4 lds128(uint32_t addr) { uint4 v; asm volatile("ld.shared.v4.b32 {%0,%1,%2,%3}, [%4];" : "=r"(v.x), "=r"(v.y), "=r"(v.z), "=r"(v.w) : "r"(addr) : "memory"); return v; }
__device__ __forceinline__ void sts64f(uint32_t addr, float a, float b) { asm volatile("st.shared.v2.f32 [%0], {%1,%2};" :: "r"(addr), "f"(a), "f"(b) : "memory"); }
__device__ __forceinline__ float2 lds64f(uint32_t addr) { float2 v; asm volatile("ld.shared.v2.f32 {%0,%1}, [%2];" : "=f"(v.x), "=f"(v.y) : "r"(addr) : "memory"); return v; }
__device__ __forceinline__ uint32_t dlo(uint32_t addr, uint32_t lbo) { return ((addr & 0x3FFFF) >> 4) | ((lbo >> 4) << 16); }

template<int SD> __device__ __forceinline__ void wg_ss_n128_tb1(float (&d)[64], uint32_t da, uint32_t db) {
  asm volatile("{\n.reg .b64 da, db;\nmov.b64 da, {%64, 0x40000040};\nmov.b64 db, {%65, 0x40000040};\n"
    "wgmma.mma_async.sync.aligned.m64n128k16.f32.bf16.bf16 {%0, %1, %2, %3, %4, %5, %6, %7, %8, %9, %10, %11, %12, %13, %14, %15, %16, %17, %18, %19, %20, %21, %22, %23, %24, %25, %26, %27, %28, %29, %30, %31, %32, %33, %34, %35, %36, %37, %38, %39, %40, %41, %42, %43, %44, %45, %46, %47, %48, %49, %50, %51, %52, %53, %54, %55, %56, %57, %58, %59, %60, %61, %62, %63}, da, db, %66, 1, 1, 0, 1;\n}\n"
    : "+f"(d[0]), "+f"(d[1]), "+f"(d[2]), "+f"(d[3]), "+f"(d[4]), "+f"(d[5]), "+f"(d[6]), "+f"(d[7]), "+f"(d[8]), "+f"(d[9]), "+f"(d[10]), "+f"(d[11]), "+f"(d[12]), "+f"(d[13]), "+f"(d[14]), "+f"(d[15]), "+f"(d[16]), "+f"(d[17]), "+f"(d[18]), "+f"(d[19]), "+f"(d[20]), "+f"(d[21]), "+f"(d[22]), "+f"(d[23]), "+f"(d[24]), "+f"(d[25]), "+f"(d[26]), "+f"(d[27]), "+f"(d[28]), "+f"(d[29]), "+f"(d[30]), "+f"(d[31]), "+f"(d[32]), "+f"(d[33]), "+f"(d[34]), "+f"(d[35]), "+f"(d[36]), "+f"(d[37]), "+f"(d[38]), "+f"(d[39]), "+f"(d[40]), "+f"(d[41]), "+f"(d[42]), "+f"(d[43]), "+f"(d[44]), "+f"(d[45]), "+f"(d[46]), "+f"(d[47]), "+f"(d[48]), "+f"(d[49]), "+f"(d[50]), "+f"(d[51]), "+f"(d[52]), "+f"(d[53]), "+f"(d[54]), "+f"(d[55]), "+f"(d[56]), "+f"(d[57]), "+f"(d[58]), "+f"(d[59]), "+f"(d[60]), "+f"(d[61]), "+f"(d[62]), "+f"(d[63])
    : "r"(da), "r"(db), "n"(SD));
}
template<int SD> __device__ __forceinline__ void wg_rs_n128_tb1(float (&d)[64], uint32_t a0, uint32_t a1, uint32_t a2, uint32_t a3, uint32_t db) {
  asm volatile("{\n.reg .b64 db;\nmov.b64 db, {%68, 0x40000040};\n"
    "wgmma.mma_async.sync.aligned.m64n128k16.f32.bf16.bf16 {%0, %1, %2, %3, %4, %5, %6, %7, %8, %9, %10, %11, %12, %13, %14, %15, %16, %17, %18, %19, %20, %21, %22, %23, %24, %25, %26, %27, %28, %29, %30, %31, %32, %33, %34, %35, %36, %37, %38, %39, %40, %41, %42, %43, %44, %45, %46, %47, %48, %49, %50, %51, %52, %53, %54, %55, %56, %57, %58, %59, %60, %61, %62, %63}, {%64, %65, %66, %67}, db, %69, 1, 1, 1;\n}\n"
    : "+f"(d[0]), "+f"(d[1]), "+f"(d[2]), "+f"(d[3]), "+f"(d[4]), "+f"(d[5]), "+f"(d[6]), "+f"(d[7]), "+f"(d[8]), "+f"(d[9]), "+f"(d[10]), "+f"(d[11]), "+f"(d[12]), "+f"(d[13]), "+f"(d[14]), "+f"(d[15]), "+f"(d[16]), "+f"(d[17]), "+f"(d[18]), "+f"(d[19]), "+f"(d[20]), "+f"(d[21]), "+f"(d[22]), "+f"(d[23]), "+f"(d[24]), "+f"(d[25]), "+f"(d[26]), "+f"(d[27]), "+f"(d[28]), "+f"(d[29]), "+f"(d[30]), "+f"(d[31]), "+f"(d[32]), "+f"(d[33]), "+f"(d[34]), "+f"(d[35]), "+f"(d[36]), "+f"(d[37]), "+f"(d[38]), "+f"(d[39]), "+f"(d[40]), "+f"(d[41]), "+f"(d[42]), "+f"(d[43]), "+f"(d[44]), "+f"(d[45]), "+f"(d[46]), "+f"(d[47]), "+f"(d[48]), "+f"(d[49]), "+f"(d[50]), "+f"(d[51]), "+f"(d[52]), "+f"(d[53]), "+f"(d[54]), "+f"(d[55]), "+f"(d[56]), "+f"(d[57]), "+f"(d[58]), "+f"(d[59]), "+f"(d[60]), "+f"(d[61]), "+f"(d[62]), "+f"(d[63])
    : "r"(a0), "r"(a1), "r"(a2), "r"(a3), "r"(db), "n"(SD));
}
template<int SD> __device__ __forceinline__ void wg_ss_n64_tb1(float (&d)[32], uint32_t da, uint32_t db) {
  asm volatile("{\n.reg .b64 da, db;\nmov.b64 da, {%32, 0x40000040};\nmov.b64 db, {%33, 0x40000040};\n"
    "wgmma.mma_async.sync.aligned.m64n64k16.f32.bf16.bf16 {%0, %1, %2, %3, %4, %5, %6, %7, %8, %9, %10, %11, %12, %13, %14, %15, %16, %17, %18, %19, %20, %21, %22, %23, %24, %25, %26, %27, %28, %29, %30, %31}, da, db, %34, 1, 1, 0, 1;\n}\n"
    : "+f"(d[0]), "+f"(d[1]), "+f"(d[2]), "+f"(d[3]), "+f"(d[4]), "+f"(d[5]), "+f"(d[6]), "+f"(d[7]), "+f"(d[8]), "+f"(d[9]), "+f"(d[10]), "+f"(d[11]), "+f"(d[12]), "+f"(d[13]), "+f"(d[14]), "+f"(d[15]), "+f"(d[16]), "+f"(d[17]), "+f"(d[18]), "+f"(d[19]), "+f"(d[20]), "+f"(d[21]), "+f"(d[22]), "+f"(d[23]), "+f"(d[24]), "+f"(d[25]), "+f"(d[26]), "+f"(d[27]), "+f"(d[28]), "+f"(d[29]), "+f"(d[30]), "+f"(d[31])
    : "r"(da), "r"(db), "n"(SD));
}
template<int SD> __device__ __forceinline__ void wg_ss_n80_tb0(float (&d)[40], uint32_t da, uint32_t db) {
  asm volatile("{\n.reg .b64 da, db;\nmov.b64 da, {%40, 0x40000040};\nmov.b64 db, {%41, 0x40000040};\n"
    "wgmma.mma_async.sync.aligned.m64n80k16.f32.bf16.bf16 {%0, %1, %2, %3, %4, %5, %6, %7, %8, %9, %10, %11, %12, %13, %14, %15, %16, %17, %18, %19, %20, %21, %22, %23, %24, %25, %26, %27, %28, %29, %30, %31, %32, %33, %34, %35, %36, %37, %38, %39}, da, db, %42, 1, 1, 0, 0;\n}\n"
    : "+f"(d[0]), "+f"(d[1]), "+f"(d[2]), "+f"(d[3]), "+f"(d[4]), "+f"(d[5]), "+f"(d[6]), "+f"(d[7]), "+f"(d[8]), "+f"(d[9]), "+f"(d[10]), "+f"(d[11]), "+f"(d[12]), "+f"(d[13]), "+f"(d[14]), "+f"(d[15]), "+f"(d[16]), "+f"(d[17]), "+f"(d[18]), "+f"(d[19]), "+f"(d[20]), "+f"(d[21]), "+f"(d[22]), "+f"(d[23]), "+f"(d[24]), "+f"(d[25]), "+f"(d[26]), "+f"(d[27]), "+f"(d[28]), "+f"(d[29]), "+f"(d[30]), "+f"(d[31]), "+f"(d[32]), "+f"(d[33]), "+f"(d[34]), "+f"(d[35]), "+f"(d[36]), "+f"(d[37]), "+f"(d[38]), "+f"(d[39])
    : "r"(da), "r"(db), "n"(SD));
}
template<int SD> __device__ __forceinline__ void wg_rs_n64_tb1(float (&d)[32], uint32_t a0, uint32_t a1, uint32_t a2, uint32_t a3, uint32_t db) {
  asm volatile("{\n.reg .b64 db;\nmov.b64 db, {%36, 0x40000040};\n"
    "wgmma.mma_async.sync.aligned.m64n64k16.f32.bf16.bf16 {%0, %1, %2, %3, %4, %5, %6, %7, %8, %9, %10, %11, %12, %13, %14, %15, %16, %17, %18, %19, %20, %21, %22, %23, %24, %25, %26, %27, %28, %29, %30, %31}, {%32, %33, %34, %35}, db, %37, 1, 1, 1;\n}\n"
    : "+f"(d[0]), "+f"(d[1]), "+f"(d[2]), "+f"(d[3]), "+f"(d[4]), "+f"(d[5]), "+f"(d[6]), "+f"(d[7]), "+f"(d[8]), "+f"(d[9]), "+f"(d[10]), "+f"(d[11]), "+f"(d[12]), "+f"(d[13]), "+f"(d[14]), "+f"(d[15]), "+f"(d[16]), "+f"(d[17]), "+f"(d[18]), "+f"(d[19]), "+f"(d[20]), "+f"(d[21]), "+f"(d[22]), "+f"(d[23]), "+f"(d[24]), "+f"(d[25]), "+f"(d[26]), "+f"(d[27]), "+f"(d[28]), "+f"(d[29]), "+f"(d[30]), "+f"(d[31])
    : "r"(a0), "r"(a1), "r"(a2), "r"(a3), "r"(db), "n"(SD));
}


constexpr int RING = 5;
constexpr uint32_t STAGE = 32768;
constexpr uint32_t OFF_X = 32768, OFF_W = 65536, OFF_MISC = OFF_W + RING * STAGE;
constexpr int SMEM_BYTES = OFF_MISC + 256 + 1024 + 1024;

struct Ctx {
  uint32_t sA, sX, sW, full, empty, stats;
  uint32_t frag;
  uint32_t rsw;
  uint32_t hi;
  int wg, tid, lane;
};
__device__ __forceinline__ uint32_t stage_wait(const Ctx& c, int n) {
  const int q = n / RING, s = n - q * RING;
  mbar_wait(c.full + 8 * s, q & 1);
  return dlo(c.sW + s * STAGE, 0);
}
__device__ __forceinline__ void stage_release(const Ctx& c, int n) {
  const int s = n % RING;
  if (c.tid == 0) mbar_arrive(c.empty + 8 * s);
}
__device__ __forceinline__ void turn_begin(const Ctx& c) { bar_sync(5 + c.wg, 256); }
__device__ __forceinline__ void turn_end(const Ctx& c) { bar_arrive(5 + (c.wg ^ 1), 256); }
template<int FIRST, int LAST> __device__ __forceinline__ void piece_ss(const Ctx& c, float (&acc)[64], uint32_t dA, uint32_t dB) {
  dB += (16384 >> 4) << 16;
  wg_ss_n128_tb1<FIRST ? 0 : 1>(acc, dA, dB);
#pragma unroll
  for (int kk = 1; kk < 8; kk++) {
    wg_ss_n128_tb1<1>(acc, dA + (kk >> 2) * 512 + (kk & 3) * 2, dB + kk * 128);
  }
  if (LAST) turn_end(c);
}
__device__ __forceinline__ void ff_g1(const Ctx& c, float (&h)[32], uint32_t dA, uint32_t dB) {
  wg_ss_n64_tb1<0>(h, dA, dB);
#pragma unroll
  for (int kk = 1; kk < 16; kk++) {
    wg_ss_n64_tb1<1>(h, dA + (kk >> 2) * 512 + (kk & 3) * 2, dB + kk * 128);
  }
}
__device__ __forceinline__ void ff_g2(float (&acc)[64], const uint32_t (&P)[16], uint32_t dB, int half) {
  dB += ((8192 >> 4) << 16) + half * 1024;
#pragma unroll
  for (int kk = 0; kk < 4; kk++) wg_rs_n128_tb1<1>(acc, P[4 * kk], P[4 * kk + 1], P[4 * kk + 2], P[4 * kk + 3], dB + kk * 128);
}
struct NoHook { __device__ __forceinline__ void operator()() const {} };
template<int FIRST, class Hook = NoHook> __device__ __forceinline__ void gemm256(const Ctx& c, float (&acc)[64], int n, Hook hook = Hook()) {
  const uint32_t dA = dlo(c.sA, 16);
  uint32_t b = stage_wait(c, n);
  turn_begin(c);
  wg_fence(); piece_ss<FIRST, 0>(c, acc, dA, b); wg_commit();
  b = stage_wait(c, n + 1);
  wg_fence(); piece_ss<0, 1>(c, acc, dA + 1024, b); wg_commit();
  hook();
  wg_wait<1>(); stage_release(c, n);
  wg_wait<0>(); stage_release(c, n + 1);
}
__device__ __forceinline__ uint32_t frag_addr(const Ctx& c, uint32_t tile, int j) {
  return tile + (2 * c.wg + (j >> 2)) * 8192 + c.frag + ((((j & 3) * 2 + c.hi) ^ c.rsw) << 4);
}
__device__ __forceinline__ void load_half(const Ctx& c, uint32_t tile, float (&v)[64]) {
#pragma unroll
  for (int j = 0; j < 8; j++) {
    uint32_t r0, r1, r2, r3;
    ldsm_x4(frag_addr(c, tile, j), r0, r1, r2, r3);
    v[8 * j] = bf_lo(r0); v[8 * j + 1] = bf_hi(r0); v[8 * j + 2] = bf_lo(r1); v[8 * j + 3] = bf_hi(r1);
    v[8 * j + 4] = bf_lo(r2); v[8 * j + 5] = bf_hi(r2); v[8 * j + 6] = bf_lo(r3); v[8 * j + 7] = bf_hi(r3);
  }
}
__device__ __forceinline__ void store_half(const Ctx& c, uint32_t tile, const float (&v)[64], float a0, float b0, float a1, float b1) {
#pragma unroll
  for (int j = 0; j < 8; j++)
    stsm_x4(frag_addr(c, tile, j),
            pack_bf16(fmaf(v[8 * j], a0, b0), fmaf(v[8 * j + 1], a0, b0)), pack_bf16(fmaf(v[8 * j + 2], a1, b1), fmaf(v[8 * j + 3], a1, b1)),
            pack_bf16(fmaf(v[8 * j + 4], a0, b0), fmaf(v[8 * j + 5], a0, b0)), pack_bf16(fmaf(v[8 * j + 6], a1, b1), fmaf(v[8 * j + 7], a1, b1)));
}
__device__ __forceinline__ void store_half_raw(const Ctx& c, uint32_t tile, const float (&v)[64]) {
#pragma unroll
  for (int j = 0; j < 8; j++)
    stsm_x4(frag_addr(c, tile, j), pack_bf16(v[8 * j], v[8 * j + 1]), pack_bf16(v[8 * j + 2], v[8 * j + 3]),
            pack_bf16(v[8 * j + 4], v[8 * j + 5]), pack_bf16(v[8 * j + 6], v[8 * j + 7]));
}
__device__ __forceinline__ void ln_stats(const Ctx& c, const float (&v)[64], float scale, float& a0, float& b0, float& a1, float& b1) {
  float s0 = 0.f, s1 = 0.f, q0 = 0.f, q1 = 0.f, s2 = 0.f, s3 = 0.f, q2 = 0.f, q3 = 0.f;
#pragma unroll
  for (int i = 0; i < 16; i++) {
    s0 += v[4 * i]; q0 = fmaf(v[4 * i], v[4 * i], q0);
    s2 += v[4 * i + 1]; q2 = fmaf(v[4 * i + 1], v[4 * i + 1], q2);
    s1 += v[4 * i + 2]; q1 = fmaf(v[4 * i + 2], v[4 * i + 2], q1);
    s3 += v[4 * i + 3]; q3 = fmaf(v[4 * i + 3], v[4 * i + 3], q3);
  }
  s0 += s2; q0 += q2; s1 += s3; q1 += q3;
  s0 += __shfl_xor_sync(0xffffffff, s0, 1); q0 += __shfl_xor_sync(0xffffffff, q0, 1);
  s1 += __shfl_xor_sync(0xffffffff, s1, 1); q1 += __shfl_xor_sync(0xffffffff, q1, 1);
  s0 += __shfl_xor_sync(0xffffffff, s0, 2); q0 += __shfl_xor_sync(0xffffffff, q0, 2);
  s1 += __shfl_xor_sync(0xffffffff, s1, 2); q1 += __shfl_xor_sync(0xffffffff, q1, 2);
  const uint32_t row = (c.tid >> 5) * 16 + (c.lane >> 2);
  if ((c.lane & 3) == 0) {
    sts64f(c.stats + c.wg * 512 + row * 8, s0, q0);
    sts64f(c.stats + c.wg * 512 + (row + 8) * 8, s1, q1);
  }
  bar_sync(1, 256);
  const float2 o0 = lds64f(c.stats + (c.wg ^ 1) * 512 + row * 8), o1 = lds64f(c.stats + (c.wg ^ 1) * 512 + (row + 8) * 8);
  const float m0 = (s0 + o0.x) * (1.f / 256.f), m1 = (s1 + o1.x) * (1.f / 256.f);
  const float var0 = fmaxf(fmaf(-m0, m0, (q0 + o0.y) * (1.f / 256.f)), 0.f), var1 = fmaxf(fmaf(-m1, m1, (q1 + o1.y) * (1.f / 256.f)), 0.f);
  a0 = rsqrt_fast(var0 + 1e-5f) * scale; a1 = rsqrt_fast(var1 + 1e-5f) * scale;
  b0 = -m0 * a0; b1 = -m1 * a1;
}
__device__ __forceinline__ float silu_half(float h) { return fmaf(h, tanh_fast(h), h); }
__device__ __forceinline__ float silu_quarter(float h) { const float q = 0.5f * h; return fmaf(q, tanh_fast(h), q); }
__device__ __forceinline__ void silu_pack(const float (&acc)[32], uint32_t (&P)[16]) {
#pragma unroll
  for (int i = 0; i < 16; i++) P[i] = pack_bf16(silu_quarter(acc[2 * i]), silu_quarter(acc[2 * i + 1]));
}
__device__ __forceinline__ void ff_block(const Ctx& c, int n0, float (&own)[64]) {
  float oth[64], h[32];
  uint32_t P[16];
#pragma unroll
  for (int i = 0; i < 64; i++) oth[i] = 0.f;
  const uint32_t dA = dlo(c.sA, 16);
  {
    const uint32_t b = stage_wait(c, n0 + c.wg);
    turn_begin(c);
    wg_fence(); ff_g1(c, h, dA, b); wg_commit();
    turn_end(c);
    wg_wait<0>(); stage_release(c, n0 + c.wg);
    silu_pack(h, P);
  }
#pragma unroll 1
  for (int it = 1; it < 8; it++) {
    const int n = n0 + 4 * it - 2 + 2 * c.wg;
    uint32_t b = stage_wait(c, n);
    turn_begin(c);
    wg_fence(); ff_g1(c, h, dA, b); wg_commit();
    b = stage_wait(c, n + 1);
    wg_fence(); ff_g2(own, P, b, c.wg); ff_g2(oth, P, b, c.wg ^ 1); wg_commit();
    turn_end(c);
    wg_wait<1>(); stage_release(c, n);
    wg_wait<0>(); stage_release(c, n + 1);
    silu_pack(h, P);
  }
  if (c.wg == 0) bar_arrive(2, 256);
  {
    const int n = n0 + 30 + c.wg;
    const uint32_t b = stage_wait(c, n);
    turn_begin(c);
    wg_fence(); ff_g2(oth, P, b, c.wg ^ 1); wg_commit();
    ff_g2(own, P, b, c.wg); wg_commit();
    turn_end(c);
    wg_wait<1>();
    if (c.wg == 1) bar_sync(2, 256);
    const uint32_t e = (c.wg == 0 ? c.sX : c.sA) + c.tid * 16;
#pragma unroll
    for (int i = 0; i < 16; i++)
      sts128(e + i * 2048, make_uint4(__float_as_uint(oth[4 * i]), __float_as_uint(oth[4 * i + 1]), __float_as_uint(oth[4 * i + 2]), __float_as_uint(oth[4 * i + 3])));
    wg_wait<0>(); stage_release(c, n);
  }
  bar_sync(1, 256);
  const uint32_t e = (c.wg == 0 ? c.sA : c.sX) + c.tid * 16;
#pragma unroll
  for (int i = 0; i < 16; i++) {
    const uint4 u = lds128(e + i * 2048);
    own[4 * i] += __uint_as_float(u.x); own[4 * i + 1] += __uint_as_float(u.y);
    own[4 * i + 2] += __uint_as_float(u.z); own[4 * i + 3] += __uint_as_float(u.w);
  }
}
struct Maps { CUtensorMap X, W1a, W1b, Wqkv, QKVst, Q, KV, Wo, Pw1, Pw2, W2a, W2b, Out; uint16_t stage[92]; };
constexpr int NA = 44;
constexpr int NC = 45;
#define STAGE_TABLE {0x1, 0x11, 0x21, 0x2, 0x31, 0x102, 0x41, 0x202, 0x51, 0x302, 0x61, 0x402, 0x71, 0x502, 0x81, 0x602, 0x91, 0x702, 0xa1, 0x802, 0xb1, 0x902, 0xc1, 0xa02, 0xd1, 0xb02, 0xe1, 0xc02, 0xf1, 0xd02, 0xe02, 0xf02, 0x3, 0x203, 0x23, 0x223, 0x43, 0x243, 0x63, 0x263, 0x83, 0x283, 0xa3, 0x2a3, 0x7, 0x207, 0x27, 0x227, 0x8, 0x208, 0x2008, 0x2208, 0x1008, 0x1208, 0x3008, 0x3208, 0x9, 0x29, 0x209, 0x229, 0xa, 0x1a, 0x2a, 0xb, 0x3a, 0x10b, 0x4a, 0x20b, 0x5a, 0x30b, 0x6a, 0x40b, 0x7a, 0x50b, 0x8a, 0x60b, 0x9a, 0x70b, 0xaa, 0x80b, 0xba, 0x90b, 0xca, 0xa0b, 0xda, 0xb0b, 0xea, 0xc0b, 0xfa, 0xd0b, 0xe0b, 0xf0b}
__device__ __forceinline__ void load_stage(uint32_t dst, uint32_t bar, const Maps& tm, int n) {
  const uint32_t e = tm.stage[n - (n > NA)];
  mbar_expect_tx(bar, STAGE);
  tma_load_3d(dst, &tm.X + (e & 15), bar, (e >> 12) * 64, ((e >> 8) & 15) * 64, (e >> 4) & 15);
}
__device__ __forceinline__ void produce(uint32_t sW, uint32_t full, const Maps& tm, int n0, int n1) {
  uint32_t s = n0 % RING, ph = ((n0 / RING) & 1) ^ 1;
#pragma unroll 1
  for (int n = n0; n < n1; n++) {
    mbar_wait(full + 8 * RING + 8 * s, ph);
    load_stage(sW + s * STAGE, full + 8 * s, tm, n);
    if (++s == RING) { s = 0; ph ^= 1; }
  }
}
__device__ __forceinline__ Ctx make_ctx(uint32_t base) {
  Ctx c;
  c.sA = base; c.sX = base + OFF_X; c.sW = base + OFF_W;
  c.full = base + OFF_MISC; c.empty = c.full + 8 * RING; c.stats = base + OFF_MISC + 256;
  c.wg = __shfl_sync(0xffffffff, (int)(threadIdx.x >> 7), 0);
  c.tid = threadIdx.x & 127; c.lane = threadIdx.x & 31;
  const uint32_t r = (c.tid >> 5) * 16 + (c.lane & 7) + ((c.lane >> 3) & 1) * 8;
  c.frag = r * 128; c.rsw = r & 7; c.hi = c.lane >> 4;
  return c;
}

constexpr int NSTG = 4;
constexpr int KVB = 160 * 128;
constexpr int NKV = T_ / 160;
static_assert(NSTG * 2 * KVB == RING * STAGE, "the K/V ring reuses the weight ring");

struct AttCtx { uint32_t sKV, full, empty, wfull; const Maps* tm; int h, b, wg; };
__device__ __forceinline__ int kv_slot(int i) { return (i + 3) & 3; }
__device__ __forceinline__ void att_load(const AttCtx& a, int i, int v) {
  const int s = i & 3;
  mbar_expect_tx(a.full + 8 * (s + v * NSTG), KVB);
  tma_load_3d(a.sKV + kv_slot(i) * 2 * KVB + v * KVB, &a.tm->KV, a.full + 8 * (s + v * NSTG), 256 + v * 256 + a.h * 64, i * 160, a.b);
}
__device__ __forceinline__ void att_load_stage(const AttCtx& a, int i) { att_load(a, i, 0); att_load(a, i, 1); }
__device__ __forceinline__ void att_init_bars(const AttCtx& a) {
  for (int i = 0; i < NSTG; i++) { mbar_init(a.full + 8 * i, 1); mbar_init(a.full + 8 * (NSTG + i), 1); mbar_init(a.empty + 8 * i, 4); }
}
__device__ __forceinline__ void att_qk(float (&S)[40], uint32_t dQ, uint32_t kd) {
  wg_ss_n80_tb0<0>(S, dQ, kd);
#pragma unroll
  for (int kk = 1; kk < 4; kk++) wg_ss_n80_tb0<1>(S, dQ + kk * 2, kd + kk * 2);
}
__device__ __forceinline__ void att_pv(float (&O)[32], const uint32_t (&P)[20], uint32_t vd) {
#pragma unroll
  for (int kk = 0; kk < 5; kk++) wg_rs_n64_tb1<1>(O, P[kk * 4], P[kk * 4 + 1], P[kk * 4 + 2], P[kk * 4 + 3], vd + kk * 128);
}
template<bool SAFE>
__device__ __forceinline__ void att_softmax(const float (&S)[40], uint32_t (&P)[20], float (&O)[32], float& m0, float& m1, float& l0, float& l1) {
  if (SAFE) {
    float x0 = fmaxf(S[0], S[1]), x1 = fmaxf(S[2], S[3]);
#pragma unroll
    for (int i = 1; i < 10; i++) { x0 = fmaxf(x0, fmaxf(S[4 * i], S[4 * i + 1])); x1 = fmaxf(x1, fmaxf(S[4 * i + 2], S[4 * i + 3])); }
    x0 = fmaxf(x0, __shfl_xor_sync(0xffffffff, x0, 1)); x1 = fmaxf(x1, __shfl_xor_sync(0xffffffff, x1, 1));
    x0 = fmaxf(x0, __shfl_xor_sync(0xffffffff, x0, 2)); x1 = fmaxf(x1, __shfl_xor_sync(0xffffffff, x1, 2));
    const float n0 = fmaxf(m0, x0), n1 = fmaxf(m1, x1);
    const float f0 = ex2(m0 - n0), f1 = ex2(m1 - n1);
    m0 = n0; m1 = n1; l0 *= f0; l1 *= f1;
#pragma unroll
    for (int i = 0; i < 8; i++) { O[4 * i] *= f0; O[4 * i + 1] *= f0; O[4 * i + 2] *= f1; O[4 * i + 3] *= f1; }
  }
#pragma unroll
  for (int i = 0; i < 10; i++) {
    float p0, p1, p2, p3;
    if (SAFE) { p0 = ex2(S[4 * i] - m0); p1 = ex2(S[4 * i + 1] - m0); p2 = ex2(S[4 * i + 2] - m1); p3 = ex2(S[4 * i + 3] - m1); }
    else { p0 = ex2(S[4 * i]); p1 = ex2(S[4 * i + 1]); p2 = ex2(S[4 * i + 2]); p3 = ex2(S[4 * i + 3]); }
    l0 += p0 + p1; l1 += p2 + p3;
    P[2 * i] = pack_bf16(p0, p1); P[2 * i + 1] = pack_bf16(p2, p3);
  }
}
template<bool SAFE>
__device__ __forceinline__ void att_refill(const AttCtx& a, int it) {
  if ((threadIdx.x & 127) == 0) {
    mbar_arrive(a.empty + 8 * (it & 3));
    if (a.wg == (it & 3) && it >= 1) {
      const bool kv = it - 1 + NSTG < NKV;
      if (kv || (!SAFE && a.wfull)) {
        mbar_wait(a.empty + 8 * ((it - 1) & 3), ((it - 1) >> 2) & 1);
        if (kv) att_load_stage(a, it - 1 + NSTG);
        else load_stage(a.sKV + (it - 22) * STAGE, a.wfull + 8 * (it - 22), *a.tm, NC + it - 22);
      }
    }
  }
  __syncwarp();
}
constexpr uint32_t KV_STG = 2 * KVB / 16, KV_VOFF = KVB / 16, KV_HALF = 80 * 128 / 16;
template<bool SAFE>
__device__ __forceinline__ void att_pass(const AttCtx& a, bool idle, uint32_t dQ, float (&O)[32], float& l0, float& l1) {
  float S[40];
  uint32_t P[20];
  float m0 = -INFINITY, m1 = -INFINITY;
  l0 = 0.f; l1 = 0.f;
#pragma unroll
  for (int i = 0; i < 32; i++) O[i] = 0.f;
  const uint32_t dKV = dlo(a.sKV, 16);
  if (SAFE) {
#pragma unroll 1
    for (int j = 0; j < 2 * NKV; j++) {
      const int it = j >> 1, s = it & 3;
      const uint32_t kb = dKV + kv_slot(it) * KV_STG + (j & 1) * KV_HALF;
      mbar_wait(a.full + 8 * s, (it >> 2) & 1);
      wg_fence(); att_qk(S, dQ, kb); wg_commit(); wg_wait<0>();
      att_softmax<true>(S, P, O, m0, m1, l0, l1);
      mbar_wait(a.full + 8 * (NSTG + s), (it >> 2) & 1);
      wg_fence(); att_pv(O, P, kb + KV_VOFF); wg_commit(); wg_wait<0>();
      if (j & 1) att_refill<true>(a, it);
    }
  } else if (idle) {
    l0 = 1.f; l1 = 1.f;
#pragma unroll 1
    for (int it = 0; it < NKV - 1; it++) { mbar_wait(a.full + 8 * (it & 3), (it >> 2) & 1); att_refill<false>(a, it); }
  } else {
    mbar_wait(a.full, 0);
    wg_fence(); att_qk(S, dQ, dKV + 3 * KV_STG); wg_commit(); wg_wait<0>();
    att_softmax<false>(S, P, O, m0, m1, l0, l1);
    mbar_wait(a.full + 8 * NSTG, 0);
    wg_fence(); att_pv(O, P, dKV + 3 * KV_STG + KV_VOFF); att_qk(S, dQ, dKV + 3 * KV_STG + KV_HALF); wg_commit(); wg_wait<0>();
#pragma unroll 1
    for (int it = 0; it < NKV - 1; it++) {
      const int sn = (it + 1) & 3;
      const uint32_t kb = dKV + kv_slot(it) * KV_STG, kn = dKV + kv_slot(it + 1) * KV_STG, par = ((it + 1) >> 2) & 1;
      att_softmax<false>(S, P, O, m0, m1, l0, l1);
      mbar_wait(a.full + 8 * sn, par);
      wg_fence(); att_pv(O, P, kb + KV_VOFF + KV_HALF); att_qk(S, dQ, kn); wg_commit(); wg_wait<0>();
      att_refill<false>(a, it);
      att_softmax<false>(S, P, O, m0, m1, l0, l1);
      mbar_wait(a.full + 8 * (NSTG + sn), par);
      wg_fence(); att_pv(O, P, kn + KV_VOFF); att_qk(S, dQ, kn + KV_HALF); wg_commit(); wg_wait<0>();
    }
    att_softmax<false>(S, P, O, m0, m1, l0, l1);
    wg_fence(); att_pv(O, P, dKV + 3 * KV_STG + KV_VOFF + KV_HALF); wg_commit(); wg_wait<0>();
  }
  l0 += __shfl_xor_sync(0xffffffff, l0, 1); l1 += __shfl_xor_sync(0xffffffff, l1, 1);
  l0 += __shfl_xor_sync(0xffffffff, l0, 2); l1 += __shfl_xor_sync(0xffffffff, l1, 2);
}

struct Wptrs { const void* p[8]; uint32_t bytes[8]; };

constexpr uint32_t B_FULL = 0, B_EMPTY = 8 * RING, B_X = 16 * RING, B_ADONE = B_X + 8, B_Q = B_X + 16, B_EP = B_X + 24, B_ATT = B_X + 32  ,
                   B_SRDY = B_ATT + 96, B_SFREE = B_SRDY + 16;

__global__ void __launch_bounds__(512, 1) conformer_kernel(const __grid_constant__ Maps tm, const __grid_constant__ Wptrs wp, const uint4* __restrict__ dw) {
  extern __shared__ uint8_t smem_raw[];
  const uint32_t base = (smem_u32(smem_raw) + 1023) & ~1023u, misc = base + OFF_MISC;
  const uint32_t bq = blockIdx.x / 19, br = blockIdx.x - bq * 19;
  const uint32_t bid = br == 18 ? ((bq & 1) ? 125 : 128) + (bq >> 1) : blockIdx.x - bq;
  if (bid >= NWORK) return;
  const int tile = bid;
  const bool has_tile = tile < NTILE;
  const int wg = __shfl_sync(0xffffffff, (int)(threadIdx.x >> 7), 0);
  AttCtx a;
  a.sKV = base + OFF_W; a.full = misc + B_ATT; a.empty = a.full + 16 * NSTG; a.tm = &tm;
  a.h = (bid >> 4) & 3; a.b = (bid >> 6) & 1; a.wg = wg; a.wfull = has_tile ? misc + B_FULL : 0;
  const int qt = bid & 15;

  if (threadIdx.x == 256) {
    mbar_init(misc + B_X, 1);
    for (int i = 0; i < RING; i++) { mbar_init(misc + B_FULL + 8 * i, 1); mbar_init(misc + B_EMPTY + 8 * i, 1); }
    asm volatile("fence.mbarrier_init.release.cluster;" ::: "memory");
    if (has_tile) {
      mbar_expect_tx(misc + B_X, 32768);
      tma_load_3d(base + OFF_X, &tm.X, misc + B_X, 0, tile * 64, 0);
    }
  } else if (threadIdx.x >= 288 && threadIdx.x < 307) {
    const int i = threadIdx.x - 288;
    mbar_init(misc + B_ADONE + 8 * i, i == 0 ? 2 : i < 11 ? 1 : i < 15 ? 4 : i < 17 ? 128 : 1);
    asm volatile("fence.mbarrier_init.release.cluster;" ::: "memory");
  } else if (threadIdx.x >= 320 && threadIdx.x < 333) {
    prefetch_tmap(&tm.X + (threadIdx.x - 320));
  }
  __syncthreads();
  if ((threadIdx.x & 31) == 0 && threadIdx.x >= 256 && threadIdx.x < 256 + 32 * RING && has_tile) {
    const int i = (threadIdx.x - 256) >> 5;
    load_stage(base + OFF_W + i * STAGE, misc + B_FULL + 8 * i, tm, i);
  }
  __syncwarp();
  auto get_epoch = [&]() {
    uint32_t e;
    mbar_wait(misc + B_EP, 0);
    asm volatile("ld.shared.u32 %0, [%1];" : "=r"(e) : "r"(misc + 248) : "memory");
    return e;
  };

  if (wg < 2) {
    asm volatile("setmaxnreg.inc.sync.aligned.u32 232;");
    if (has_tile) {
      const Ctx c = make_ctx(base);
      if (c.wg == 1) turn_end(c);
      float own[64];
      float a0, b0, a1, b1;
      mbar_wait(misc + B_X, 0);
      load_half(c, c.sX, own);
      ln_stats(c, own, 0.5f, a0, b0, a1, b1);
      store_half(c, c.sA, own, a0, b0, a1, b1);
      fence_async_smem();
      bar_sync(1, 256);
      ff_block(c, 0, own);
      ln_stats(c, own, 1.f, a0, b0, a1, b1);
      store_half(c, c.sA, own, a0, b0, a1, b1);
      fence_async_smem();
      bar_sync(1, 256);
#pragma unroll 1
      for (int cc = 0; cc < 3; cc++) {
        float acc[64];
        const int j = 2 * cc + c.wg;
        gemm256<1>(c, acc, 32 + 2 * j, [&]() { if (cc) mbar_wait(misc + B_SFREE + 8 * c.wg, (cc - 1) & 1); });
        if (cc == 2) { bar_arrive(9, 288); if (c.tid == 0) mbar_arrive(misc + B_ADONE); }
        if (cc == 0) {
#pragma unroll
          for (int i = 0; i < 64; i++) acc[i] *= 0.125f * 1.4426950408889634f;
        }
        store_half_raw(c, c.sX, acc);
        fence_async_smem();
        mbar_arrive(misc + B_SRDY + 8 * c.wg);
      }
      mbar_wait(misc + B_SFREE + 8 * c.wg, 0);
      store_half_raw(c, c.sX, own);
    }
    else bar_sync(3 + wg, 128);
    asm volatile("setmaxnreg.dec.sync.aligned.u32 128;");
    bar_arrive(7, 384); bar_arrive(8, 384);
    __syncwarp();
  } else {
    asm volatile("setmaxnreg.dec.sync.aligned.u32 24;");
    const uint32_t full = misc + B_FULL;
    if (threadIdx.x == 320) {
      const uint32_t e = atomicAdd(&g_start, 1) / NWORK;
      asm volatile("st.shared.u32 [%0], %1;" :: "r"(misc + 248), "r"(e + 1) : "memory");
      mbar_arrive(misc + B_EP);
    }
    if (threadIdx.x == 256) {
      if (has_tile) {
        produce(base + OFF_W, full, tm, RING, NA);
        mbar_wait(full + 8 * RING + 8 * 4, 1);
        mbar_arrive(full + 8 * 4); mbar_arrive(full + 8 * RING + 8 * 4);
      }
      cnt_wait(g_cnt1 + a.b * 64, 126 * get_epoch());
      if (has_tile) mbar_wait(misc + B_ADONE, 0);
      mbar_expect_tx(misc + B_Q, 32768);
      tma_load_3d(base, &tm.Q, misc + B_Q, a.h * 64, qt * 256, a.b);
      att_load(a, 0, 0);
      mbar_wait(misc + B_Q, 0);
#pragma unroll 1
      for (int i = 1; i < NSTG; i++) att_load(a, i, 0);
    } else if (has_tile && (threadIdx.x == 320 || threadIdx.x == 352)) {
      const int w = (threadIdx.x - 320) >> 5;
      __nanosleep(8000);
#pragma unroll 1
      for (int cc = 0; cc < 3; cc++) {
        mbar_wait(misc + B_SRDY + 8 * w, cc & 1);
        tma_store_3d(&tm.QKVst, base + OFF_X + w * 16384, 0, tile * 64, 4 * cc + 2 * w);
        bulk_commit();
        bulk_wait_read();
        mbar_arrive(misc + B_SFREE + 8 * w);
        if (cc) {
          bulk_wait_all();
          if (tile <= 62) cnt_signal(g_cnt1 + 32 * (cc - 1));
          if (tile >= 62) cnt_signal(g_cnt1 + 64 + 32 * (cc - 1));
        }
      }
    } else if ((threadIdx.x >> 5) == 12) {
      if (has_tile) bar_sync(9, 288);
      if (threadIdx.x == 384) {
        cnt_wait(g_cnt1 + a.b * 64 + 32, 126 * get_epoch());
        att_load(a, 0, 1);
        mbar_wait(a.full + 8 * NSTG, 0);
#pragma unroll 1
        for (int i = 1; i < NSTG; i++) att_load(a, i, 1);
      }
    } else if (has_tile && threadIdx.x >= 288 && threadIdx.x < 296) {
      const int w = threadIdx.x - 288;
      mbar_wait(misc + B_X, 0);
      if (w >= 2) __nanosleep(4000);
      const uint32_t bytes = wp.bytes[w], per = ((bytes / NTILE) + 127) & ~127u, off = per * tile;
      if (off < bytes) l2_prefetch((const uint8_t*)wp.p[w] + off, min(per, bytes - off));
    } else if (has_tile && threadIdx.x >= 416) {
      mbar_wait(full, 0);
      const int t = threadIdx.x - 416;
#pragma unroll 1
      for (int i = t; i < 2048; i += 96) g_att[tile * 2048 + i] = make_uint4(~0u, ~0u, ~0u, ~0u);
      g_halo[tile * 128 + t] = make_uint4(~0u, ~0u, ~0u, ~0u);
      if (t < 32) g_halo[tile * 128 + 96 + t] = make_uint4(~0u, ~0u, ~0u, ~0u);
    }
    __syncwarp();
    bar_sync(5 + wg, 384);
    asm volatile("setmaxnreg.inc.sync.aligned.u32 128;");
  }

  {
    const int lane = threadIdx.x & 31, wq = (threadIdx.x >> 5) & 3;
    const uint32_t dQ = dlo(base + wg * 8192, 16);
    float O[32], l0, l1;
    mbar_wait(misc + B_Q, 0);
    att_pass<false>(a, qt * 256 + wg * 64 >= T_, dQ, O, l0, l1);
    float z0 = 0.f, z1 = 0.f, z2 = 0.f, z3 = 0.f;
#pragma unroll
    for (int i = 0; i < 8; i++) { z0 = fmaf(O[4 * i], 0.f, z0); z1 = fmaf(O[4 * i + 1], 0.f, z1); z2 = fmaf(O[4 * i + 2], 0.f, z2); z3 = fmaf(O[4 * i + 3], 0.f, z3); }
    const float z = (z0 + z1) + (z2 + z3);
    const bool ok = (l0 >= 0x1p-40f) && (l0 <= 0x1p80f) && (l1 >= 0x1p-40f) && (l1 <= 0x1p80f) && (z == 0.f);
    const bool warp_bad = !__all_sync(0xffffffff, ok);
    auto store_out = [&]() {
      const float i0 = rcp_fast(l0), i1 = rcp_fast(l1);
      const int row = qt * 256 + wg * 64 + wq * 16;
      if (row < T_) {
        const int slab = (a.b * T_ + row) / 16;
        uint4* op = g_att + (slab * 16 + a.h * 4) * 32 + lane;
#pragma unroll
        for (int j = 0; j < 4; j++)
          asm volatile("st.relaxed.gpu.global.v4.u32 [%0], {%1,%2,%3,%4};" :: "l"(op + j * 32),
                       "r"(pack_bf16(O[8 * j] * i0, O[8 * j + 1] * i0)), "r"(pack_bf16(O[8 * j + 2] * i1, O[8 * j + 3] * i1)),
                       "r"(pack_bf16(O[8 * j + 4] * i0, O[8 * j + 5] * i0)), "r"(pack_bf16(O[8 * j + 6] * i1, O[8 * j + 7] * i1)) : "memory");
      }
    };
    if (!warp_bad) store_out();
    if (__syncthreads_or(warp_bad)) {
      if (threadIdx.x == 0) {
        if (has_tile) { mbar_wait(misc + B_FULL, 1); mbar_wait(misc + B_FULL + 8, 1); }
        for (int i = 0; i < 3 * NSTG; i++) mbar_inval(a.full + 8 * i);
        att_init_bars(a);
        asm volatile("fence.mbarrier_init.release.cluster;" ::: "memory");
        fence_async_smem();
#pragma unroll 1
        for (int i = 0; i < NSTG; i++) att_load_stage(a, i);
      }
      __syncthreads();
      att_pass<true>(a, false, dQ, O, l0, l1);
      if (warp_bad) store_out();
      __syncthreads();
      if (has_tile) {
        if (threadIdx.x == 32) {
          load_stage(base + OFF_W, misc + B_X, tm, NC);
          load_stage(base + OFF_W + STAGE, misc + B_Q, tm, NC + 1);
        }
        mbar_wait(misc + B_X, 1); mbar_wait(misc + B_Q, 1);
      }
    }
  }
  if (!has_tile) return;

  if (wg < 2) {
    asm volatile("setmaxnreg.inc.sync.aligned.u32 232;");
    const Ctx c = make_ctx(base);
    float own[64];
    float a0, b0, a1, b1;
    {
      uint4 af[16];
      const int slab = tile * 4 + (c.tid >> 5);
      const uint4* ap = g_att + slab * 512 + c.lane;
#pragma unroll
      for (int i = 0; i < 16; i++)
        asm volatile("ld.global.ca.v4.u32 {%0,%1,%2,%3}, [%4];" : "=r"(af[i].x), "=r"(af[i].y), "=r"(af[i].z), "=r"(af[i].w) : "l"(ap + i * 32) : "memory");
      load_half(c, c.sX, own);
      uint32_t miss = 15;
      for (uint32_t n = 0; n < (1u << 18); n++) {
#pragma unroll
        for (int hh = 0; hh < 4; hh++)
          if ((miss >> hh) & 1) {
            uint32_t mx = 0;
#pragma unroll
            for (int i = 4 * hh; i < 4 * hh + 4; i++) mx = max(mx, max(max(af[i].x, af[i].y), max(af[i].z, af[i].w)));
            if (__any_sync(0xffffffff, mx == ~0u)) {
#pragma unroll
              for (int i = 4 * hh; i < 4 * hh + 4; i++)
                asm volatile("ld.relaxed.gpu.global.v4.u32 {%0,%1,%2,%3}, [%4];" : "=r"(af[i].x), "=r"(af[i].y), "=r"(af[i].z), "=r"(af[i].w) : "l"(ap + i * 32) : "memory");
            } else miss &= ~(1u << hh);
          }
        if (!miss) break;
      }
      const int n = NC + 2 * c.wg;
      uint32_t b = stage_wait(c, n) + ((16384 >> 4) << 16);
      turn_begin(c);
      wg_fence();
#pragma unroll
      for (int kk = 0; kk < 8; kk++) wg_rs_n128_tb1<1>(own, af[kk].x, af[kk].y, af[kk].z, af[kk].w, b + kk * 128);
      wg_commit();
      b = stage_wait(c, n + 1) + ((16384 >> 4) << 16);
      wg_fence();
#pragma unroll
      for (int kk = 0; kk < 8; kk++) wg_rs_n128_tb1<1>(own, af[8 + kk].x, af[8 + kk].y, af[8 + kk].z, af[8 + kk].w, b + kk * 128);
      wg_commit();
      turn_end(c);
      wg_wait<1>(); stage_release(c, n);
      wg_wait<0>(); stage_release(c, n + 1);
    }
    ln_stats(c, own, 0.5f, a0, b0, a1, b1);
    store_half(c, c.sA, own, a0, b0, a1, b1);
    fence_async_smem();
    bar_sync(1, 256);
    uint4 dwr[5];
#pragma unroll
    for (int i = 0; i < 5; i++) dwr[i] = __ldg(dw + i * 32 + c.wg * 16 + (c.lane & 15));
    const bool top = c.tid < 8, pub = (top || c.tid >= 120);
    uint32_t* halo_out = (uint32_t*)g_halo + (tile * 4 + (top ? (c.tid >> 2) : ((c.tid >> 2) - 28))) * 128 + c.wg * 64 + (c.lane & 3);
#pragma unroll 1
    for (int q = 0; q < 2; q++) {
      float ab[64];
      gemm256<1>(c, ab, NC + 4 + 4 * q + 2 * c.wg);
#pragma unroll
      for (int j = 0; j < 4; j++) {
        float g[8];
#pragma unroll
        for (int i = 0; i < 8; i++) g[i] = fmaf(ab[8 * j + i], tanh_fast(ab[32 + 8 * j + i]), ab[8 * j + i]);
        const uint32_t p0 = pack_bf16(g[0], g[1]), p1 = pack_bf16(g[2], g[3]), p2 = pack_bf16(g[4], g[5]), p3 = pack_bf16(g[6], g[7]);
        if (pub) {
          uint32_t* hp = halo_out + q * 32 + j * 8;
          asm volatile("st.relaxed.gpu.global.u32 [%0], %1;" :: "l"(hp), "r"(top ? p0 : p1) : "memory");
          asm volatile("st.relaxed.gpu.global.u32 [%0], %1;" :: "l"(hp + 4), "r"(top ? p2 : p3) : "memory");
        }
        stsm_x4(c.sX + (2 * c.wg + q) * 8192 + c.frag + (((j * 2 + c.hi) ^ c.rsw) << 4), p0, p1, p2, p3);
      }
    }
    bar_sync(3 + c.wg, 128);
    {
      const int wi = c.tid >> 4;
      const uint32_t col = (2 * c.wg + ((c.lane >> 3) & 1)) * 8192, ch = c.lane & 7;
      uint4 r[12];
      const int R0 = tile * 64 + wi * 8;
      const bool first = (R0 % T_) == 0, last = ((R0 + 8) % T_) == 0;
      const bool far = ((wi == 0 && !first) || (wi == 7 && !last));
      const uint4* sp = g_halo + (wi == 0 ? (tile - 1) * 4 + 2 : (tile + 1) * 4) * 32 + c.wg * 16 + (c.lane & 15);
      uint4 h0 = make_uint4(0, 0, 0, 0), h1 = h0;
      auto ld_halo = [&]() {
        asm volatile("ld.relaxed.gpu.global.v4.u32 {%0,%1,%2,%3}, [%4];" : "=r"(h0.x), "=r"(h0.y), "=r"(h0.z), "=r"(h0.w) : "l"(sp) : "memory");
        asm volatile("ld.relaxed.gpu.global.v4.u32 {%0,%1,%2,%3}, [%4];" : "=r"(h1.x), "=r"(h1.y), "=r"(h1.z), "=r"(h1.w) : "l"(sp + 32) : "memory");
      };
      if (far) ld_halo();
#pragma unroll
      for (int i = 0; i < 12; i++) {
        const int row = (wi * 8 - 2 + i) & 63;
        r[i] = lds128(c.sX + col + row * 128 + ((ch ^ (row & 7)) << 4));
      }
      uint32_t w[5][4];
#pragma unroll
      for (int k = 0; k < 5; k++) {
        w[k][0] = bmul2(dwr[k].x, 0x3F003F00u); w[k][1] = bmul2(dwr[k].y, 0x3F003F00u);
        w[k][2] = bmul2(dwr[k].z, 0x3F003F00u); w[k][3] = bmul2(dwr[k].w, 0x3F003F00u);
      }
      auto conv4 = [&](int i0, int i1, int i2, int i3, bool sync) {
        const int rows[4] = {i0, i1, i2, i3};
        uint32_t acc[4][4];
#pragma unroll
        for (int k = 0; k < 5; k++)
#pragma unroll
          for (int j = 0; j < 4; j++) {
            const uint4 x = r[rows[j] + k];
            acc[j][0] = k ? bfma2(x.x, w[k][0], acc[j][0]) : bmul2(x.x, w[0][0]);
            acc[j][1] = k ? bfma2(x.y, w[k][1], acc[j][1]) : bmul2(x.y, w[0][1]);
            acc[j][2] = k ? bfma2(x.z, w[k][2], acc[j][2]) : bmul2(x.z, w[0][2]);
            acc[j][3] = k ? bfma2(x.w, w[k][3], acc[j][3]) : bmul2(x.w, w[0][3]);
          }
#pragma unroll
        for (int j = 0; j < 4; j++)
#pragma unroll
          for (int q = 0; q < 4; q++) acc[j][q] = pack_bf16(silu_half(bf_lo(acc[j][q])), silu_half(bf_hi(acc[j][q])));
        if (sync) bar_sync(3 + c.wg, 128);
#pragma unroll
        for (int j = 0; j < 4; j++)
          sts128(c.sX + col + (wi * 8 + rows[j]) * 128 + ((ch ^ rows[j]) << 4), make_uint4(acc[j][0], acc[j][1], acc[j][2], acc[j][3]));
      };
      conv4(2, 3, 4, 5, true);
      if (far) {
        for (uint32_t n = 0; n < (1u << 18); n++) {
          const uint32_t mx = max(max(max(h0.x, h0.y), max(h0.z, h0.w)), max(max(h1.x, h1.y), max(h1.z, h1.w)));
          if (mx != ~0u) break;
          ld_halo();
        }
      }
      __syncwarp();
      if (first || (far && wi == 0)) { r[0] = h0; r[1] = h1; }
      if (last || (far && wi == 7)) { r[10] = h0; r[11] = h1; }
      conv4(0, 1, 6, 7, false);
    }
    fence_async_smem();
    bar_sync(c.wg == 0 ? 3 : 1, c.wg == 0 ? 128 : 256);
    {
      uint32_t b = stage_wait(c, NC + 12 + c.wg);
      turn_begin(c);
      wg_fence(); piece_ss<0, 0>(c, own, dlo(c.sX, 16), b); wg_commit();
      if (c.wg == 0) { turn_end(c); bar_sync(1, 256); turn_begin(c); }
      b = stage_wait(c, NC + 14 + c.wg);
      wg_fence(); piece_ss<0, 1>(c, own, dlo(c.sX, 16) + 1024, b); wg_commit();
    }
    wg_wait<1>(); stage_release(c, NC + 12 + c.wg);
    wg_wait<0>(); stage_release(c, NC + 14 + c.wg);
    ln_stats(c, own, 0.5f, a0, b0, a1, b1);
    if (c.wg == 1) { turn_begin(c); turn_end(c); }
    store_half(c, c.sA, own, a0, b0, a1, b1);
    fence_async_smem();
    bar_sync(1, 256);
    ff_block(c, NC + 16, own);
    ln_stats(c, own, 1.f, a0, b0, a1, b1);
    store_half(c, c.sX, own, a0, b0, a1, b1);
    fence_async_smem();
    bar_sync(3 + c.wg, 128);
    if (c.tid == 0) { tma_store_3d(&tm.Out, c.sX + c.wg * 16384, 0, tile * 64, 2 * c.wg); bulk_commit(); bulk_wait_read(); }
  } else {
    asm volatile("setmaxnreg.dec.sync.aligned.u32 24;");
    if (threadIdx.x == 256) {
      __nanosleep(200);
      produce(base + OFF_W, misc + B_FULL, tm, NC + 2, NC + 48);
    }
  }
}

typedef CUresult (*EncodeFn)(CUtensorMap*, CUtensorMapDataType, cuuint32_t, void*, const cuuint64_t*, const cuuint64_t*, const cuuint32_t*,
                             const cuuint32_t*, CUtensorMapInterleave, CUtensorMapSwizzle, CUtensorMapL2promotion, CUtensorMapFloatOOBfill);

CUtensorMap make_map(EncodeFn enc, const void* p, uint64_t d0, uint64_t d1, uint64_t d2, uint64_t s1, uint64_t s2, uint32_t b1, uint32_t b2) {
  CUtensorMap tm;
  cuuint64_t dims[3] = {d0, d1, d2};
  cuuint64_t strides[2] = {s1, s2};
  cuuint32_t box[3] = {64, b1, b2};
  cuuint32_t es[3] = {1, 1, 1};
  enc(&tm, CU_TENSOR_MAP_DATA_TYPE_BFLOAT16, 3, const_cast<void*>(p), dims, strides, box, es, CU_TENSOR_MAP_INTERLEAVE_NONE,
      CU_TENSOR_MAP_SWIZZLE_128B, CU_TENSOR_MAP_L2_PROMOTION_L2_256B, CU_TENSOR_MAP_FLOAT_OOB_FILL_NONE);
  return tm;
}
CUtensorMap blk_map(EncodeFn enc, const void* p, uint64_t rows, uint64_t cols, uint32_t boxrows, uint32_t boxblks) {
  return make_map(enc, p, 64, rows, cols / 64, cols * 2, 128, boxrows, boxblks);
}
CUtensorMap seq_map(EncodeFn enc, const void* p, uint64_t cols, uint32_t boxrows) {
  return make_map(enc, p, cols, T_, 2, cols * 2, cols * 2 * T_, boxrows, 1);
}

}

extern "C" void kernel_launch(void* const* d_in, const int* in_sizes, int n_in, void* d_out, int out_size) {
  (void)in_sizes; (void)n_in; (void)out_size;
  const void *x = d_in[0], *w1a = d_in[1], *w1b = d_in[2], *wqkv = d_in[3], *wo = d_in[4], *pw1 = d_in[5], *dw = d_in[6], *pw2 = d_in[7],
             *w2a = d_in[8], *w2b = d_in[9];
  void* fn = nullptr;
  cudaDriverEntryPointQueryResult qr;
  cudaGetDriverEntryPoint("cuTensorMapEncodeTiled", &fn, cudaEnableDefault, &qr);
  EncodeFn enc = (EncodeFn)fn;
  void* qkv;
  cudaGetSymbolAddress(&qkv, g_qkv);
  cudaFuncSetAttribute(conformer_kernel, cudaFuncAttributeMaxDynamicSharedMemorySize, SMEM_BYTES);

  Wptrs wp;
  const void* ws[8] = {w1a, w1b, wqkv, wo, pw1, pw2, w2a, w2b};
  const uint32_t wb[8] = {524288, 524288, 393216, 131072, 262144, 131072, 524288, 524288};
  for (int i = 0; i < 8; i++) { wp.p[i] = ws[i]; wp.bytes[i] = wb[i]; }
  Maps tm;
  const uint16_t tab[92] = STAGE_TABLE;
  for (int i = 0; i < 92; i++) tm.stage[i] = tab[i];
  tm.X = blk_map(enc, x, ROWS, 256, 64, 4);
  tm.W1a = blk_map(enc, w1a, 256, 1024, 256, 1);
  tm.W1b = blk_map(enc, w1b, 1024, 256, 64, 4);
  tm.Wqkv = blk_map(enc, wqkv, 256, 768, 128, 2);
  tm.QKVst = blk_map(enc, qkv, ROWS, 768, 64, 2);
  tm.Q = seq_map(enc, qkv, 768, 256);
  tm.KV = seq_map(enc, qkv, 768, 160);
  tm.Wo = blk_map(enc, wo, 256, 256, 128, 2);
  tm.Pw1 = make_map(enc, pw1, 256, 256, 2, 1024, 512, 128, 2);
  tm.Pw2 = blk_map(enc, pw2, 256, 256, 128, 2);
  tm.W2a = blk_map(enc, w2a, 256, 1024, 256, 1);
  tm.W2b = blk_map(enc, w2b, 1024, 256, 64, 4);
  tm.Out = blk_map(enc, d_out, ROWS, 256, 64, 2);
  conformer_kernel<<<NCTA, 512, SMEM_BYTES, cudaStreamPerThread>>>(tm, wp, (const uint4*)dw);
}
```
